```python
import torch

def _softmax(x, axis=-1):
    return torch.softmax(x, dim=axis)

def _gelu(x):
    return torch.nn.functional.gelu(x, approximate='tanh')

def _silu(x):
    return torch.nn.functional.silu(x)

def _sigmoid(x):
    return torch.sigmoid(x)

def _layernorm(x, axis=-1, eps=1e-05):
    m = x.mean(dim=axis, keepdim=True)
    v = x.var(dim=axis, keepdim=True, unbiased=False)
    return (x - m) / torch.sqrt(v + eps)

def _scatter_add(tgt, idx, src, axis=0):
    return tgt.clone().index_add_(axis, idx, src)

def _segment_sum(src, seg, n):
    out = torch.zeros((n,) + src.shape[1:], dtype=src.dtype)
    return out.index_add_(0, seg, src)

def _pad(x, pw):
    flat = tuple((v for pair in reversed(pw) for v in pair))
    return torch.nn.functional.pad(x, flat)
kernel_name = 'recurrent_scan__memory_aug_recurrent_mem_tr__glu_gated_glu__prompt'

def setup_inputs():

    _w = lambda a: (lambda t: t.to(torch.bfloat16) if t.is_floating_point() else t)(torch.as_tensor(a))

    def _A_setup():
        B, S, Dm = (1, 2048, 1024)
        H, Dh = (32, 128)
        M, seg = (8, 32)
        seg = min(seg, S)
        S = S // seg * seg
        return {'x': _w((lambda *s: torch.randn(*s, dtype=torch.bfloat16) * 0.05)(B, S, Dm)), 'mem0': _w((lambda *s: torch.randn(*s, dtype=torch.bfloat16) * 0.2)(B, M, Dm)), 'Wq': _w((lambda *s: torch.randn(*s, dtype=torch.bfloat16) * 0.8)(Dm, H, Dh) * Dm ** (-0.5)), 'Wk': _w((lambda *s: torch.randn(*s, dtype=torch.bfloat16) * 0.8)(Dm, H, Dh) * Dm ** (-0.5)), 'Wv': _w((lambda *s: torch.randn(*s, dtype=torch.bfloat16) * 0.2)(Dm, H, Dh) * Dm ** (-0.5)), 'Wo': _w((lambda *s: torch.randn(*s, dtype=torch.bfloat16) * 0.2)(H, Dh, Dm) * (H * Dh) ** (-0.5)), 'seg_len': seg}
    _A_in = _A_setup()

    def _B_setup():
        B, S, D, F = (1, 2048, 1024, 3584)
        return {'x': _w((lambda *s: torch.randn(*s, dtype=torch.bfloat16) * 0.05)(B, S, D)), 'w_gate': _w((lambda *s: torch.randn(*s, dtype=torch.bfloat16) * 0.2)(D, F)), 'w_up': _w((lambda *s: torch.randn(*s, dtype=torch.bfloat16) * 0.1)(D, F)), 'w_down': _w((lambda *s: torch.randn(*s, dtype=torch.bfloat16) * 0.1)(F, D))}
    _B_in = _B_setup()
    return {'A_x': _A_in['x'], 'A_mem0': _A_in['mem0'], 'A_Wq': _A_in['Wq'], 'A_Wk': _A_in['Wk'], 'A_Wv': _A_in['Wv'], 'A_Wo': _A_in['Wo'], 'A_seg_len': _A_in['seg_len'], 'B_x': _B_in['x'], 'B_w_gate': _B_in['w_gate'], 'B_w_up': _B_in['w_up'], 'B_w_down': _B_in['w_down']}

def reference(A_x, A_mem0, A_Wq, A_Wk, A_Wv, A_Wo, A_seg_len, B_x, B_w_gate, B_w_up, B_w_down):

    def _A_ref(x, mem0, Wq, Wk, Wv, Wo, seg_len):
        B, S, Dm = x.shape
        H, Dh = (Wq.shape[1], Wq.shape[2])
        M = mem0.shape[1]
        scale = Dh ** (-0.5)
        n_seg = S // seg_len
        L = M + seg_len
        idx = torch.arange(L)
        mask = (idx[:, None] < M) | (idx[:, None] >= idx[None, :])
        mem = mem0
        outs = []
        for s in range(n_seg):
            xs = x[:, s * seg_len:(s + 1) * seg_len, :].clone()
            h = torch.concatenate([mem, xs], axis=1)
            q = torch.einsum('btd,dhe->bhte', h, Wq)
            k = torch.einsum('btd,dhe->bhte', h, Wk)
            v = torch.einsum('btd,dhe->bhte', h, Wv)
            scores = torch.einsum('bhqe,bhke->bhqk', q, k) * scale
            scores = torch.where(mask[None, None], scores, -1000000000.0)
            p = _softmax(scores, axis=-1)
            o = torch.einsum('bhqk,bhke->bhqe', p, v)
            o = torch.einsum('bhte,hed->btd', o, Wo)
            mem = o[:, :M, :].clone()
            outs.append(o[:, M:, :])
        return torch.concatenate(outs, axis=1)

    def _B_ref(x, w_gate, w_up, w_down):
        g = torch.einsum('bsd,df->bsf', x, w_gate)
        u = torch.einsum('bsd,df->bsf', x, w_up)
        h = _sigmoid(g) * u
        return torch.einsum('bsf,fd->bsd', h, w_down)
    x = A_x
    xn = _layernorm(x, axis=-1)
    s = _A_ref(xn, A_mem0, A_Wq, A_Wk, A_Wv, A_Wo, A_seg_len)
    g = _silu(_B_ref(xn, B_w_gate, B_w_up, B_w_down))
    return x + s * g
```

```cpp
#include <cuda_runtime.h>
#include <cuda_bf16.h>
#include <cuda.h>
#include <stdint.h>

namespace {

constexpr int SEQ = 2048, DM = 1024, HD = 4096, FF = 3584, NSEG = 64;

__device__ __align__(1024) __nv_bfloat16 g_xn[SEQ * DM];
__device__ __align__(1024) __nv_bfloat16 g_ox[SEQ * HD];
__device__ __align__(1024) __nv_bfloat16 g_h[SEQ * FF];
__device__ __align__(1024) __nv_bfloat16 g_y[SEQ * DM];
__device__ __align__(1024) uint4 g_xmem[4][1024];
__device__ __align__(1024) uint4 g_xo[4][4096];

__device__ __forceinline__ uint32_t smem_u32(const void* p) { return (uint32_t)__cvta_generic_to_shared(p); }
__device__ __forceinline__ uint32_t mapa(uint32_t a, uint32_t r) {
    uint32_t o; asm("mapa.shared::cluster.u32 %0, %1, %2;" : "=r"(o) : "r"(a), "r"(r)); return o;
}
__device__ __forceinline__ void mbar_init(uint32_t a, uint32_t cnt) {
    asm volatile("mbarrier.init.shared.b64 [%0], %1;" :: "r"(a), "r"(cnt) : "memory");
}
__device__ __forceinline__ void mbar_expect(uint32_t a, uint32_t bytes) {
    asm volatile("mbarrier.arrive.expect_tx.shared.b64 _, [%0], %1;" :: "r"(a), "r"(bytes) : "memory");
}
__device__ __forceinline__ void mbar_arrive_cluster(uint32_t a) {
    asm volatile("mbarrier.arrive.shared::cluster.b64 _, [%0];" :: "r"(a) : "memory");
}
__device__ __forceinline__ bool mbar_try(uint32_t a, uint32_t par) {
    uint32_t ok;
    asm volatile("{\n.reg .pred p;\nmbarrier.try_wait.parity.shared::cta.b64 p, [%1], %2;\nselp.u32 %0, 1, 0, p;\n}"
                 : "=r"(ok) : "r"(a), "r"(par) : "memory");
    return ok;
}
__device__ __forceinline__ void mbar_wait(uint32_t a, uint32_t par) {
    if (mbar_try(a, par)) return;
    uint32_t it = 0;
    while (!mbar_try(a, par)) { if (++it > (1u << 22)) __trap(); }
}
__device__ __forceinline__ void tma2d(uint32_t dst, const CUtensorMap* m, int c0, int c1, uint32_t bar) {
    asm volatile("cp.async.bulk.tensor.2d.shared::cluster.global.mbarrier::complete_tx::bytes [%0], [%1, {%3, %4}], [%2];"
                 :: "r"(dst), "l"(m), "r"(bar), "r"(c0), "r"(c1) : "memory");
}
__device__ __forceinline__ void tma2d_mc(uint32_t dst, const CUtensorMap* m, int c0, int c1, uint32_t bar, uint16_t mask) {
    asm volatile("cp.async.bulk.tensor.2d.shared::cluster.global.mbarrier::complete_tx::bytes.multicast::cluster [%0], [%1, {%3, %4}], [%2], %5;"
                 :: "r"(dst), "l"(m), "r"(bar), "r"(c0), "r"(c1), "h"(mask) : "memory");
}
__device__ __forceinline__ void tma2d_store(const CUtensorMap* m, int c0, int c1, uint32_t src) {
    asm volatile("cp.async.bulk.tensor.2d.global.shared::cta.bulk_group [%0, {%1, %2}], [%3];"
                 :: "l"(m), "r"(c0), "r"(c1), "r"(src) : "memory");
}
__device__ __forceinline__ void bar_sync(int id, int n) { asm volatile("bar.sync %0, %1;" :: "r"(id), "r"(n) : "memory"); }
__device__ __forceinline__ void fence_async() { asm volatile("fence.proxy.async.shared::cta;" ::: "memory"); }
__device__ __forceinline__ void cluster_sync() {
    asm volatile("barrier.cluster.arrive.release.aligned;\nbarrier.cluster.wait.acquire.aligned;" ::: "memory");
}
__device__ __forceinline__ void ldsm4(uint32_t* r, uint32_t a) {
    asm volatile("ldmatrix.sync.aligned.m8n8.x4.shared.b16 {%0,%1,%2,%3}, [%4];"
                 : "=r"(r[0]), "=r"(r[1]), "=r"(r[2]), "=r"(r[3]) : "r"(a) : "memory");
}
__device__ __forceinline__ void ldsm4t(uint32_t* r, uint32_t a) {
    asm volatile("ldmatrix.sync.aligned.m8n8.x4.trans.shared.b16 {%0,%1,%2,%3}, [%4];"
                 : "=r"(r[0]), "=r"(r[1]), "=r"(r[2]), "=r"(r[3]) : "r"(a) : "memory");
}
__device__ __forceinline__ void stsm4(uint32_t a, uint32_t r0, uint32_t r1, uint32_t r2, uint32_t r3) {
    asm volatile("stmatrix.sync.aligned.m8n8.x4.shared.b16 [%0], {%1,%2,%3,%4};" :: "r"(a), "r"(r0), "r"(r1), "r"(r2), "r"(r3) : "memory");
}
__device__ __forceinline__ void stsm4t(uint32_t a, uint32_t r0, uint32_t r1, uint32_t r2, uint32_t r3) {
    asm volatile("stmatrix.sync.aligned.m8n8.x4.trans.shared.b16 [%0], {%1,%2,%3,%4};" :: "r"(a), "r"(r0), "r"(r1), "r"(r2), "r"(r3) : "memory");
}
__device__ __forceinline__ void stsm2(uint32_t a, uint32_t r0, uint32_t r1) {
    asm volatile("stmatrix.sync.aligned.m8n8.x2.shared.b16 [%0], {%1,%2};" :: "r"(a), "r"(r0), "r"(r1) : "memory");
}
__device__ __forceinline__ void stsm2t(uint32_t a, uint32_t r0, uint32_t r1) {
    asm volatile("stmatrix.sync.aligned.m8n8.x2.trans.shared.b16 [%0], {%1,%2};" :: "r"(a), "r"(r0), "r"(r1) : "memory");
}
__device__ __forceinline__ uint32_t movm(uint32_t a) {
    uint32_t d; asm volatile("movmatrix.sync.aligned.m8n8.trans.b16 %0, %1;" : "=r"(d) : "r"(a)); return d;
}
__device__ __forceinline__ void mma16(float* d, uint32_t a0, uint32_t a1, uint32_t a2, uint32_t a3, uint32_t b0, uint32_t b1) {
    asm volatile("mma.sync.aligned.m16n8k16.row.col.f32.bf16.bf16.f32 {%0,%1,%2,%3}, {%4,%5,%6,%7}, {%8,%9}, {%0,%1,%2,%3};"
                 : "+f"(d[0]), "+f"(d[1]), "+f"(d[2]), "+f"(d[3]) : "r"(a0), "r"(a1), "r"(a2), "r"(a3), "r"(b0), "r"(b1));
}
__device__ __forceinline__ void mma8(float* d, uint32_t a0, uint32_t a1, uint32_t b0) {
    asm volatile("mma.sync.aligned.m16n8k8.row.col.f32.bf16.bf16.f32 {%0,%1,%2,%3}, {%4,%5}, {%6}, {%0,%1,%2,%3};"
                 : "+f"(d[0]), "+f"(d[1]), "+f"(d[2]), "+f"(d[3]) : "r"(a0), "r"(a1), "r"(b0));
}
__device__ __forceinline__ uint32_t pack2(float lo, float hi) {
    uint32_t r; asm("cvt.rn.bf16x2.f32 %0, %1, %2;" : "=r"(r) : "f"(hi), "f"(lo)); return r;
}
__device__ __forceinline__ float bf_lo(uint32_t v) { return __uint_as_float(v << 16); }
__device__ __forceinline__ float bf_hi(uint32_t v) { return __uint_as_float(v & 0xFFFF0000u); }
__device__ __forceinline__ float ex2(float x) { float y; asm("ex2.approx.ftz.f32 %0, %1;" : "=f"(y) : "f"(x)); return y; }
__device__ __forceinline__ float rcp(float x) { float y; asm("rcp.approx.ftz.f32 %0, %1;" : "=f"(y) : "f"(x)); return y; }
__device__ __forceinline__ void sts4f(uint32_t a, float x, float y, float z, float w) {
    asm volatile("st.shared.v4.f32 [%0], {%1,%2,%3,%4};" :: "r"(a), "f"(x), "f"(y), "f"(z), "f"(w) : "memory");
}
__device__ __forceinline__ void sts4u(uint32_t a, uint4 v) {
    asm volatile("st.shared.v4.u32 [%0], {%1,%2,%3,%4};" :: "r"(a), "r"(v.x), "r"(v.y), "r"(v.z), "r"(v.w) : "memory");
}
__device__ __forceinline__ float4 lds4f(uint32_t a) {
    float4 v; asm volatile("ld.shared.v4.f32 {%0,%1,%2,%3}, [%4];" : "=f"(v.x), "=f"(v.y), "=f"(v.z), "=f"(v.w) : "r"(a) : "memory"); return v;
}
__device__ __forceinline__ float2 lds2f(uint32_t a) {
    float2 v; asm volatile("ld.shared.v2.f32 {%0,%1}, [%2];" : "=f"(v.x), "=f"(v.y) : "r"(a) : "memory"); return v;
}
__device__ __forceinline__ uint4 lds4u(uint32_t a) {
    uint4 v; asm volatile("ld.shared.v4.u32 {%0,%1,%2,%3}, [%4];" : "=r"(v.x), "=r"(v.y), "=r"(v.z), "=r"(v.w) : "r"(a) : "memory"); return v;
}
__device__ __forceinline__ uint2 lds2u(uint32_t a) {
    uint2 v; asm volatile("ld.shared.v2.u32 {%0,%1}, [%2];" : "=r"(v.x), "=r"(v.y) : "r"(a) : "memory"); return v;
}
__device__ __forceinline__ void st_async4(uint32_t a, uint32_t bar, uint32_t x, uint32_t y, uint32_t z, uint32_t w) {
    asm volatile("st.async.shared::cluster.mbarrier::complete_tx::bytes.v4.b32 [%0], {%1,%2,%3,%4}, [%5];"
                 :: "r"(a), "r"(x), "r"(y), "r"(z), "r"(w), "r"(bar) : "memory");
}
__device__ __forceinline__ void st_async2(uint32_t a, uint32_t bar, uint32_t x, uint32_t y) {
    asm volatile("st.async.shared::cluster.mbarrier::complete_tx::bytes.v2.b32 [%0], {%1,%2}, [%3];"
                 :: "r"(a), "r"(x), "r"(y), "r"(bar) : "memory");
}
__device__ __forceinline__ uint4 ld_relaxed4(const uint4* p) {
    uint4 v;
    asm volatile("ld.relaxed.gpu.global.v4.u32 {%0,%1,%2,%3}, [%4];" : "=r"(v.x), "=r"(v.y), "=r"(v.z), "=r"(v.w) : "l"(p) : "memory");
    return v;
}
__device__ __forceinline__ void st_relaxed4(uint4* p, uint4 v) {
    asm volatile("st.relaxed.gpu.global.v4.u32 [%0], {%1,%2,%3,%4};" :: "l"(p), "r"(v.x), "r"(v.y), "r"(v.z), "r"(v.w) : "memory");
}
__device__ __forceinline__ void st_relaxed1(void* p, uint32_t v) {
    asm volatile("st.relaxed.gpu.global.u32 [%0], %1;" :: "l"(p), "r"(v) : "memory");
}
__device__ __forceinline__ uint32_t umax4(uint4 v) { return max(max(v.x, v.y), max(v.z, v.w)); }
__device__ __forceinline__ void wg_fence() { asm volatile("wgmma.fence.sync.aligned;" ::: "memory"); }
__device__ __forceinline__ void wg_commit() { asm volatile("wgmma.commit_group.sync.aligned;" ::: "memory"); }
template <int N> __device__ __forceinline__ void wg_wait() { asm volatile("wgmma.wait_group.sync.aligned %0;" :: "n"(N) : "memory"); }
template <int N> __device__ __forceinline__ void reg_fence(float* d) {
#pragma unroll
    for (int i = 0; i < N; i++) asm volatile("" : "+f"(d[i]) :: "memory");
}
#define ACC16(d) "+f"(d[0]), "+f"(d[1]), "+f"(d[2]), "+f"(d[3]), "+f"(d[4]), "+f"(d[5]), "+f"(d[6]), "+f"(d[7]), \
                 "+f"(d[8]), "+f"(d[9]), "+f"(d[10]), "+f"(d[11]), "+f"(d[12]), "+f"(d[13]), "+f"(d[14]), "+f"(d[15])
#define DESC_HI_SW128 "0x40000040"
#define OUT16(d) "=f"(d[0]), "=f"(d[1]), "=f"(d[2]), "=f"(d[3]), "=f"(d[4]), "=f"(d[5]), "=f"(d[6]), "=f"(d[7]), \
                 "=f"(d[8]), "=f"(d[9]), "=f"(d[10]), "=f"(d[11]), "=f"(d[12]), "=f"(d[13]), "=f"(d[14]), "=f"(d[15])
template <int ACCUM>
__device__ __forceinline__ void wg32_rs(float* d, const uint32_t* a, uint32_t db) {
    if (ACCUM)
        asm volatile("{\n.reg .b64 db;\nmov.b64 db, {%20, " DESC_HI_SW128 "};\n"
                     "wgmma.mma_async.sync.aligned.m64n32k16.f32.bf16.bf16 {%0,%1,%2,%3,%4,%5,%6,%7,%8,%9,%10,%11,%12,%13,%14,%15}, "
                     "{%16,%17,%18,%19}, db, 1, 1, 1, 0;\n}"
                     : ACC16(d) : "r"(a[0]), "r"(a[1]), "r"(a[2]), "r"(a[3]), "r"(db));
    else
        asm volatile("{\n.reg .b64 db;\nmov.b64 db, {%20, " DESC_HI_SW128 "};\n"
                     "wgmma.mma_async.sync.aligned.m64n32k16.f32.bf16.bf16 {%0,%1,%2,%3,%4,%5,%6,%7,%8,%9,%10,%11,%12,%13,%14,%15}, "
                     "{%16,%17,%18,%19}, db, 0, 1, 1, 0;\n}"
                     : OUT16(d) : "r"(a[0]), "r"(a[1]), "r"(a[2]), "r"(a[3]), "r"(db));
}
__device__ __forceinline__ void wg32_ss(float* d, uint32_t da, uint32_t db) {
    asm volatile("{\n.reg .b64 da, db;\nmov.b64 da, {%16, " DESC_HI_SW128 "};\nmov.b64 db, {%17, " DESC_HI_SW128 "};\n"
                 "wgmma.mma_async.sync.aligned.m64n32k16.f32.bf16.bf16 {%0,%1,%2,%3,%4,%5,%6,%7,%8,%9,%10,%11,%12,%13,%14,%15}, "
                 "da, db, 1, 1, 1, 1, 0;\n}"
                 : ACC16(d) : "r"(da), "r"(db));
}
template <int N>
__device__ __forceinline__ void wg8_chain(float* d, uint32_t da, uint32_t db) {
    wg_fence();
    asm volatile("{\n.reg .b64 da, db;\nmov.b64 da, {%4, " DESC_HI_SW128 "};\nmov.b64 db, {%5, 0x10};\n"
                 "wgmma.mma_async.sync.aligned.m64n8k16.f32.bf16.bf16 {%0,%1,%2,%3}, da, db, 0, 1, 1, 1, 0;\n}"
                 : "=f"(d[0]), "=f"(d[1]), "=f"(d[2]), "=f"(d[3]) : "r"(da), "r"(db));
#pragma unroll
    for (int i = 1; i < N; i++)
        asm volatile("{\n.reg .b64 da, db;\nmov.b64 da, {%4, " DESC_HI_SW128 "};\nmov.b64 db, {%5, 0x10};\n"
                     "wgmma.mma_async.sync.aligned.m64n8k16.f32.bf16.bf16 {%0,%1,%2,%3}, da, db, 1, 1, 1, 1, 0;\n}"
                     : "+f"(d[0]), "+f"(d[1]), "+f"(d[2]), "+f"(d[3]) : "r"(da + i * 128), "r"(db + i * 16));
    wg_commit();
    wg_wait<0>();
    reg_fence<4>(d);
}

__global__ void __launch_bounds__(256) ln_kernel(const __nv_bfloat16* __restrict__ x, const __nv_bfloat16* __restrict__ mem0) {
    const int lane = threadIdx.x & 31, row = blockIdx.x * 8 + (threadIdx.x >> 5);
    const uint4* src = reinterpret_cast<const uint4*>(x + (size_t)row * DM);
    uint4 v[4];
#pragma unroll
    for (int j = 0; j < 4; j++) v[j] = src[j * 32 + lane];
    const int gi = blockIdx.x * 256 + threadIdx.x;
    const uint4 poison = make_uint4(~0u, ~0u, ~0u, ~0u);
    if (gi < 1024) {
        uint4 m = reinterpret_cast<const uint4*>(mem0)[(gi & 7) * 128 + (gi >> 3)];
        if (m.x == ~0u) m.x = 0x7FFF7FFFu;
        if (m.y == ~0u) m.y = 0x7FFF7FFFu;
        if (m.z == ~0u) m.z = 0x7FFF7FFFu;
        if (m.w == ~0u) m.w = 0x7FFF7FFFu;
        g_xmem[0][gi] = m;
    } else if (gi < 4096) {
        (&g_xmem[0][0])[gi] = poison;
    } else if (gi < 4096 + 16384) {
        (&g_xo[0][0])[gi - 4096] = poison;
    }
    float f[32];
#pragma unroll
    for (int j = 0; j < 4; j++) {
        f[j * 8 + 0] = bf_lo(v[j].x); f[j * 8 + 1] = bf_hi(v[j].x); f[j * 8 + 2] = bf_lo(v[j].y); f[j * 8 + 3] = bf_hi(v[j].y);
        f[j * 8 + 4] = bf_lo(v[j].z); f[j * 8 + 5] = bf_hi(v[j].z); f[j * 8 + 6] = bf_lo(v[j].w); f[j * 8 + 7] = bf_hi(v[j].w);
    }
    float s = 0.f;
#pragma unroll
    for (int i = 0; i < 32; i++) s += f[i];
#pragma unroll
    for (int o = 16; o; o >>= 1) s += __shfl_xor_sync(~0u, s, o);
    const float mean = s * (1.f / DM);
    float q = 0.f;
#pragma unroll
    for (int i = 0; i < 32; i++) { f[i] -= mean; q += f[i] * f[i]; }
#pragma unroll
    for (int o = 16; o; o >>= 1) q += __shfl_xor_sync(~0u, q, o);
    const float r = 1.f / sqrtf(q * (1.f / DM) + 1e-5f);
    uint4* dst = reinterpret_cast<uint4*>(g_xn + (size_t)row * DM);
#pragma unroll
    for (int j = 0; j < 4; j++)
        dst[j * 32 + lane] = make_uint4(pack2(f[j * 8] * r, f[j * 8 + 1] * r), pack2(f[j * 8 + 2] * r, f[j * 8 + 3] * r),
                                        pack2(f[j * 8 + 4] * r, f[j * 8 + 5] * r), pack2(f[j * 8 + 6] * r, f[j * 8 + 7] * r));
}

constexpr uint32_t C_WS = 0, C_WO = 65536, C_XN = 153600, C_MB = 186368, C_MISC = 202752, C_SMEM = 232448;
constexpr uint32_t C_BAR = C_MISC;
constexpr uint32_t C_RED0 = C_MISC + 256;
constexpr uint32_t C_RED1Q = C_RED0 + 2048, C_QX = C_RED1Q + 2048, C_KX = C_QX + 4096, C_QM = C_KX + 4096, C_KM = C_QM + 1024,
                   C_XSL = C_KM + 1024, C_OL = C_XSL + 5120;
constexpr uint32_t C_V = C_RED0 + 2048, C_PL = C_V + 20480, C_SL = C_PL + 4096, C_RED1V = C_WO + 42 * 2048;
static_assert(C_OL + 3072 <= C_SMEM && C_SL + 2560 <= C_SMEM, "smem overflow");
enum { B_W0 = 0, B_W1, B_W2, B_WS, B_WO, B_XF, B_XE, B_SC, B_P0, B_P1, B_XS, B_OL, B_NUM };
constexpr float SM_SCALE = 0.08838834764831845f * 1.4426950408889634f;

#define TS(i)

template <bool ISV>
__device__ __forceinline__ void chain_body(const CUtensorMap* tA, const CUtensorMap* tB, const CUtensorMap* tWo, const CUtensorMap* tXn,
                                           const uint32_t sb, const int cl, const int rank) {
    const int tid = threadIdx.x, lane = tid & 31;
    const int wg = __shfl_sync(~0u, tid >> 7, 0), w4 = __shfl_sync(~0u, (tid >> 5) & 3, 0);
    const int t128 = tid & 127, g = lane >> 2, t = lane & 3;
    const int role = rank % 3, hb = rank - role, head = 2 * cl + (rank >= 3);
    const uint32_t bar = sb + C_BAR;
    const int ostart = rank * 43 - (rank >= 3), on0 = ISV ? 21 : 22;

    const int colA = head * 128 + (ISV ? 0 : role * 64), colB = head * 128 + (ISV ? 64 : role * 64);
    if (tid == 0) {
        for (int j = 0; j < 3; j++) {
            mbar_expect(bar + (B_W0 + j) * 8, 65536);
            for (int w = 0; w < 2; w++) {
                tma2d(sb + j * 65536 + w * 32768, tA, colA, w * 512 + j * 128, bar + (B_W0 + j) * 8);
                tma2d(sb + j * 65536 + w * 32768 + 16384, tB, colB, w * 512 + j * 128, bar + (B_W0 + j) * 8);
            }
        }
    }
    uint32_t wa[24][4], wb[24][4];
    const int kr = (lane & 7) + ((lane >> 4) << 3);
    const uint32_t a_off = wg * 32768 + kr * 128 + (((w4 * 2 + ((lane >> 3) & 1)) ^ (kr & 7)) << 4);
#pragma unroll
    for (int j = 0; j < 3; j++) {
        mbar_wait(bar + (B_W0 + j) * 8, 0);
#pragma unroll
        for (int i = 0; i < 8; i++) {
            ldsm4t(wa[j * 8 + i], sb + j * 65536 + a_off + i * 2048);
            ldsm4t(wb[j * 8 + i], sb + j * 65536 + a_off + 16384 + i * 2048);
        }
        if (j != 1) {
            __syncthreads();
            if (j == 0) {
                if (tid == 0) {
                    mbar_expect(bar + B_WS * 8, 65536);
                    for (int w = 0; w < 2; w++) {
                        tma2d(sb + C_WS + w * 32768, tA, colA, w * 512 + 384, bar + B_WS * 8);
                        tma2d(sb + C_WS + w * 32768 + 16384, tB, colB, w * 512 + 384, bar + B_WS * 8);
                    }
                }
            } else if (tid < 32) {
                if (lane == 0) mbar_expect(bar + B_WO * 8, (on0 + 21) * 2048);
                __syncwarp();
                for (int i = lane; i < on0 + 21; i += 32) tma2d(sb + C_WO + i * 2048, tWo, cl * 64, (ostart + i) * 16, bar + B_WO * 8);
            }
        }
    }
    asm volatile("griddepcontrol.wait;" ::: "memory");
    asm volatile("griddepcontrol.launch_dependents;" ::: "memory");
    const uint32_t xeA = mapa(bar + B_XE * 8, 2), xeB = mapa(bar + B_XE * 8, 5);
    if (lane == 0) mbar_arrive_cluster(xeA);

    const uint32_t mbw = sb + C_MB + wg * 8192;
    const uint32_t red_out = sb + (wg == 0 ? C_RED0 : (ISV ? C_RED1V : C_RED1Q)) + t128 * 16;
    const uint32_t red_in = sb + (wg == 1 ? C_RED0 : (ISV ? C_RED1V : C_RED1Q)) + t128 * 16;
    const uint32_t xn_desc = (((sb + C_XN + wg * 16384) & 0x3FFFF) >> 4) | (1u << 16);
    const uint32_t ws_desc = (((sb + C_WS + wg * 32768) & 0x3FFFF) >> 4) | (1u << 16);
    const uint32_t wo_desc = (((sb + C_WO + (wg ? on0 : 0) * 2048) & 0x3FFFF) >> 4) | (1u << 16);
    const uint32_t mb_desc = ((mbw & 0x3FFFF) >> 4) | (8u << 16);
    const int oks = ostart + (wg ? on0 : 0), onk = wg ? 21 : on0;
    const uint4 poison = make_uint4(~0u, ~0u, ~0u, ~0u);

#pragma unroll 1
    for (int s = -1; s <= (ISV ? NSEG : NSEG - 1); s++) {
        TS(0);
        if (ISV && rank == 2 && tid == 128 && s < NSEG - 1) {
            mbar_wait(bar + B_XE * 8, (s + 1) & 1);
            for (int i = 0; i < 8; i++)
                tma2d_mc(sb + C_XN + i * 4096, tXn, (i >> 2) * 512 + (i & 3) * 64, (s + 1) * 32, bar + B_XF * 8, 0x3F);
        }
        if (s >= 0 && s < NSEG) {
            const uint4* src = &g_xmem[s & 3][wg * 512 + t128];
            uint4 v[4];
            uint32_t it = 0;
            while (true) {
#pragma unroll
                for (int j = 0; j < 4; j++) v[j] = ld_relaxed4(src + j * 128);
                if (max(max(umax4(v[0]), umax4(v[1])), max(umax4(v[2]), umax4(v[3]))) != ~0u) break;
                if (++it > (1u << 22)) __trap();
            }
#pragma unroll
            for (int j = 0; j < 4; j++) sts4u(mbw + t128 * 16 + j * 2048, v[j]);
            if (s == 0) mbar_wait(bar + B_WO * 8, 0);
            bar_sync(1 + wg, 128);
            TS(1);
            float ca[4] = {0.f, 0.f, 0.f, 0.f}, cb[4] = {0.f, 0.f, 0.f, 0.f};
            {
                uint32_t b[2][4], pf[4][4];
                ldsm4(b[0], mbw + lane * 16);
#pragma unroll
                for (int kp = 0; kp < 16; kp++) {
                    const int grp = kp >> 2, ph = kp & 3;
                    const int nx = kp + 1, nk = ((nx & 3) < 3) ? (nx >> 2) * 3 + (nx & 3) : 12 + (nx >> 2);
                    if (nx < 16) ldsm4(b[nx & 1], mbw + lane * 16 + nk * 512);
                    const uint32_t* bb = b[kp & 1];
                    if (ph < 2) {
                        ldsm4t(pf[ph * 2], sb + C_WS + a_off + (grp * 2 + ph) * 2048);
                        ldsm4t(pf[ph * 2 + 1], sb + C_WS + a_off + 16384 + (grp * 2 + ph) * 2048);
                    }
                    if (ph < 3) {
                        const int q = (grp * 3 + ph) * 2;
                        mma16(ca, wa[q][0], wa[q][1], wa[q][2], wa[q][3], bb[0], bb[1]);
                        mma16(cb, wb[q][0], wb[q][1], wb[q][2], wb[q][3], bb[0], bb[1]);
                        mma16(ca, wa[q + 1][0], wa[q + 1][1], wa[q + 1][2], wa[q + 1][3], bb[2], bb[3]);
                        mma16(cb, wb[q + 1][0], wb[q + 1][1], wb[q + 1][2], wb[q + 1][3], bb[2], bb[3]);
                    } else {
                        mma16(ca, pf[0][0], pf[0][1], pf[0][2], pf[0][3], bb[0], bb[1]);
                        mma16(cb, pf[1][0], pf[1][1], pf[1][2], pf[1][3], bb[0], bb[1]);
                        mma16(ca, pf[2][0], pf[2][1], pf[2][2], pf[2][3], bb[2], bb[3]);
                        mma16(cb, pf[3][0], pf[3][1], pf[3][2], pf[3][3], bb[2], bb[3]);
                    }
                }
            }
            if (wg == 0) sts4f(red_out, cb[0], cb[1], cb[2], cb[3]); else sts4f(red_out, ca[0], ca[1], ca[2], ca[3]);
            TS(2);
            __syncthreads();
            const float4 r = lds4f(red_in);
            const uint32_t p0 = wg == 0 ? pack2(ca[0] + r.x, ca[1] + r.y) : pack2(cb[0] + r.x, cb[1] + r.y);
            const uint32_t p1 = wg == 0 ? pack2(ca[2] + r.z, ca[3] + r.w) : pack2(cb[2] + r.z, cb[3] + r.w);
            if (!ISV) {
                stsm2t(sb + C_QM + wg * 1024 + w4 * 256 + (lane & 15) * 16, p0, p1);
            } else {
                const int rr = lane & 7, hf = (lane >> 3) & 1;
                const int rho = 32 * (2 * wg + (w4 >> 1)) + 8 * (rr >> 1) + 2 * (2 * (w4 & 1) + hf) + (rr & 1);
                stsm2(sb + C_V + (s & 1) * 10240 + rho * 80 + 64, p0, p1);
            }
            __syncthreads();
            TS(3);
        }
        if (!ISV) {
            if (s >= 0) {
                const int warp = wg * 4 + w4;
                if (warp < 3 && s < NSEG - 1) {
                    uint32_t q[2][4], k0[2][4], k1[2][4];
                    ldsm4(q[0], sb + C_QM + lane * 16);
                    ldsm4(q[1], sb + C_QM + 512 + lane * 16);
                    const uint32_t ka = warp < 2 ? sb + C_KX + (lane >> 3) * 512 + (16 * warp + (lane & 7)) * 16 : sb + C_KM + lane * 16;
                    const uint32_t kst = warp < 2 ? 2048 : 512;
                    ldsm4(k0[0], ka); ldsm4(k0[1], ka + kst);
                    float s0[4] = {0.f, 0.f, 0.f, 0.f}, s1[4] = {0.f, 0.f, 0.f, 0.f};
                    const uint32_t dst = mapa(sb + C_SL + role * 1280 + warp * 512, hb + 2), db = mapa(bar + B_SC * 8, hb + 2);
                    if (warp < 2) {
                        ldsm4(k1[0], ka + 128); ldsm4(k1[1], ka + 128 + kst);
#pragma unroll
                        for (int i = 0; i < 2; i++) {
                            mma16(s0, q[i][0], 0, q[i][1], 0, k0[i][0], k0[i][1]);
                            mma16(s1, q[i][0], 0, q[i][1], 0, k1[i][0], k1[i][1]);
                            mma16(s0, q[i][2], 0, q[i][3], 0, k0[i][2], k0[i][3]);
                            mma16(s1, q[i][2], 0, q[i][3], 0, k1[i][2], k1[i][3]);
                        }
                        st_async4(dst + lane * 16, db, __float_as_uint(s0[0]), __float_as_uint(s0[1]), __float_as_uint(s1[0]), __float_as_uint(s1[1]));
                    } else {
#pragma unroll
                        for (int i = 0; i < 2; i++) {
                            mma16(s0, q[i][0], 0, q[i][1], 0, k0[i][0], k0[i][1]);
                            mma16(s1, q[i][2], 0, q[i][3], 0, k0[i][2], k0[i][3]);
                        }
                        st_async2(dst + lane * 8, db, __float_as_uint(s0[0] + s1[0]), __float_as_uint(s0[1] + s1[1]));
                    }
                }
                TS(4);
                {
                    const int mh = warp >= 3, ti = warp - 3 * mh;
                    const uint32_t ka = ti ? sb + C_KX + (lane >> 3) * 512 + (8 * (ti - 1) + (lane & 7)) * 16 : sb + C_KM + lane * 16;
                    const uint32_t kst = ti ? 2048 : 512;
                    const uint32_t qa = sb + C_QX + (lane >> 4) * 512 + (16 * mh + (lane & 15)) * 16;
                    uint32_t k[2][4], q[4][4];
                    ldsm4(k[0], ka); ldsm4(k[1], ka + kst);
#pragma unroll
                    for (int i = 0; i < 4; i++) ldsm4(q[i], qa + i * 1024);
                    float s0[4] = {0.f, 0.f, 0.f, 0.f};
#pragma unroll
                    for (int i = 0; i < 4; i++) mma16(s0, q[i][0], q[i][1], q[i][2], q[i][3], k[i >> 1][(i & 1) * 2], k[i >> 1][(i & 1) * 2 + 1]);
                    st_async4(mapa(sb + C_XSL + role * 2560 + ti * 512 + lane * 16, hb + mh), mapa(bar + B_XS * 8, hb + mh),
                              __float_as_uint(s0[0]), __float_as_uint(s0[1]), __float_as_uint(s0[2]), __float_as_uint(s0[3]));
                }
                if (warp == 0) {
                    mbar_wait(bar + B_XS * 8, s & 1);
                    if (lane == 0) mbar_expect(bar + B_XS * 8, role ? 5120 : 3072);
                    float e[5][4];
                    float m0 = -INFINITY, m1 = -INFINITY;
#pragma unroll
                    for (int i = 0; i < 5; i++) {
                        if (i < 3 || role) {
                            const float4 a = lds4f(sb + C_XSL + i * 512 + lane * 16), b = lds4f(sb + C_XSL + 2560 + i * 512 + lane * 16);
                            e[i][0] = a.x + b.x; e[i][1] = a.y + b.y; e[i][2] = a.z + b.z; e[i][3] = a.w + b.w;
                            if (i > 0) {
                                const int d = 16 * role + g - (8 * (i - 1) + 2 * t);
                                if (d < 0) e[i][0] = -INFINITY;
                                if (d < 1) e[i][1] = -INFINITY;
                                if (d + 8 < 0) e[i][2] = -INFINITY;
                                if (d + 8 < 1) e[i][3] = -INFINITY;
                            }
                        } else {
                            e[i][0] = e[i][1] = e[i][2] = e[i][3] = -INFINITY;
                        }
                        m0 = fmaxf(m0, fmaxf(e[i][0], e[i][1])); m1 = fmaxf(m1, fmaxf(e[i][2], e[i][3]));
                    }
                    m0 = fmaxf(m0, __shfl_xor_sync(~0u, m0, 1)); m1 = fmaxf(m1, __shfl_xor_sync(~0u, m1, 1));
                    m0 = fmaxf(m0, __shfl_xor_sync(~0u, m0, 2)); m1 = fmaxf(m1, __shfl_xor_sync(~0u, m1, 2));
                    float l0 = 0.f, l1 = 0.f;
#pragma unroll
                    for (int i = 0; i < 5; i++) {
                        e[i][0] = ex2((e[i][0] - m0) * SM_SCALE); e[i][1] = ex2((e[i][1] - m0) * SM_SCALE);
                        e[i][2] = ex2((e[i][2] - m1) * SM_SCALE); e[i][3] = ex2((e[i][3] - m1) * SM_SCALE);
                        l0 += e[i][0] + e[i][1]; l1 += e[i][2] + e[i][3];
                    }
                    l0 += __shfl_xor_sync(~0u, l0, 1); l1 += __shfl_xor_sync(~0u, l1, 1);
                    l0 += __shfl_xor_sync(~0u, l0, 2); l1 += __shfl_xor_sync(~0u, l1, 2);
                    l0 = rcp(l0); l1 = rcp(l1);
                    uint32_t p[5][2];
#pragma unroll
                    for (int i = 0; i < 5; i++) { p[i][0] = pack2(e[i][0] * l0, e[i][1] * l0); p[i][1] = pack2(e[i][2] * l1, e[i][3] * l1); }
                    const uint32_t dst = mapa(sb + C_PL + (s & 1) * 2048 + role * 768, hb + 2), db = mapa(bar + (B_P0 + (s & 1)) * 8, hb + 2);
                    st_async2(dst + lane * 8, db, p[0][0], p[0][1]);
                    st_async4(dst + 256 + lane * 16, db, p[1][0], p[1][1], p[2][0], p[2][1]);
                    if (role) st_async4(dst + 768 + lane * 16, db, p[3][0], p[3][1], p[4][0], p[4][1]);
                }
            }
        } else {
            const int ss = s - wg;
            if (ss >= 0 && ss < NSEG - 1 + wg) {
                uint32_t vx[4][4], vm[4];
                const uint32_t vb = sb + C_V + (ss & 1) * 10240 + w4 * 2560;
#pragma unroll
                for (int j = 0; j < 4; j++) ldsm4(vx[j], vb + (8 * j + (lane & 7)) * 80 + (lane >> 3) * 16);
                ldsm4(vm, vb + lane * 80 + 64);
                if (wg == 0) {
                    uint4* dst = &g_xo[s & 3][(16 * head + 4 * w4 + t) * 8 + g];
                    mbar_wait(bar + B_SC * 8, s & 1);
                    TS(4);
                    const float4 a0 = lds4f(sb + C_SL + lane * 16), b0 = lds4f(sb + C_SL + 1280 + lane * 16);
                    const float4 a1 = lds4f(sb + C_SL + 512 + lane * 16), b1 = lds4f(sb + C_SL + 1280 + 512 + lane * 16);
                    const float2 a2 = lds2f(sb + C_SL + 1024 + lane * 8), b2 = lds2f(sb + C_SL + 1280 + 1024 + lane * 8);
                    if (tid == 0) mbar_expect(bar + B_SC * 8, 2560);
                    float e[10] = {a0.x + b0.x, a0.y + b0.y, a0.z + b0.z, a0.w + b0.w, a1.x + b1.x, a1.y + b1.y, a1.z + b1.z, a1.w + b1.w,
                                   a2.x + b2.x, a2.y + b2.y};
                    float m = fmaxf(fmaxf(fmaxf(e[0], e[1]), fmaxf(e[2], e[3])), fmaxf(fmaxf(e[4], e[5]), fmaxf(e[6], e[7])));
                    m = fmaxf(m, fmaxf(e[8], e[9]));
                    m = fmaxf(m, __shfl_xor_sync(~0u, m, 1));
                    m = fmaxf(m, __shfl_xor_sync(~0u, m, 2));
                    uint32_t p[5];
                    float l = 0.f;
#pragma unroll
                    for (int i = 0; i < 5; i++) {
                        p[i] = pack2(ex2((e[2 * i] - m) * SM_SCALE), ex2((e[2 * i + 1] - m) * SM_SCALE));
                        l += bf_lo(p[i]) + bf_hi(p[i]);
                    }
                    float o[4][4];
#pragma unroll
                    for (int j = 0; j < 4; j++) { o[j][0] = o[j][1] = o[j][2] = o[j][3] = 0.f; mma16(o[j], p[0], 0, p[1], 0, vx[j][0], vx[j][1]); }
#pragma unroll
                    for (int j = 0; j < 4; j++) mma16(o[j], p[2], 0, p[3], 0, vx[j][2], vx[j][3]);
#pragma unroll
                    for (int j = 0; j < 4; j++) mma8(o[j], p[4], 0, vm[j]);
                    l += __shfl_xor_sync(~0u, l, 1);
                    l += __shfl_xor_sync(~0u, l, 2);
                    l = rcp(l);
                    st_relaxed4(dst, make_uint4(pack2(o[0][0] * l, o[0][1] * l), pack2(o[1][0] * l, o[1][1] * l),
                                                pack2(o[2][0] * l, o[2][1] * l), pack2(o[3][0] * l, o[3][1] * l)));
                    st_relaxed4(&g_xo[(s + 2) & 3][(16 * head + 4 * w4 + t) * 8 + g], poison);
                } else {
                    const uint32_t pb = bar + (B_P0 + (ss & 1)) * 8, pl = sb + C_PL + (ss & 1) * 2048;
                    mbar_wait(pb, (ss >> 1) & 1);
                    const uint2 pm0 = lds2u(pl + lane * 8), pm1 = lds2u(pl + 768 + lane * 8);
                    const uint4 p0 = lds4u(pl + 256 + lane * 16), p1 = lds4u(pl + 1024 + lane * 16), p2 = lds4u(pl + 1536 + lane * 16);
                    if (tid == 128) mbar_expect(pb, 2048);
                    __nv_bfloat16* orow = g_ox + (size_t)(ss * 32 + g) * HD + head * 128 + 32 * w4 + 8 * t;
#pragma unroll
                    for (int mh = 0; mh < 2; mh++) {
                        float o[4][4];
#pragma unroll
                        for (int j = 0; j < 4; j++) {
                            o[j][0] = o[j][1] = o[j][2] = o[j][3] = 0.f;
                            if (mh == 0) {
                                mma8(o[j], pm0.x, pm0.y, vm[j]);
                                mma16(o[j], p0.x, p0.y, p0.z, p0.w, vx[j][0], vx[j][1]);
                            } else {
                                mma8(o[j], pm1.x, pm1.y, vm[j]);
                                mma16(o[j], p1.x, p1.y, p1.z, p1.w, vx[j][0], vx[j][1]);
                                mma16(o[j], p2.x, p2.y, p2.z, p2.w, vx[j][2], vx[j][3]);
                            }
                        }
                        *reinterpret_cast<uint4*>(orow + (size_t)(16 * mh) * HD) =
                            make_uint4(pack2(o[0][0], o[0][1]), pack2(o[1][0], o[1][1]), pack2(o[2][0], o[2][1]), pack2(o[3][0], o[3][1]));
                        *reinterpret_cast<uint4*>(orow + (size_t)(16 * mh + 8) * HD) =
                            make_uint4(pack2(o[0][2], o[0][3]), pack2(o[1][2], o[1][3]), pack2(o[2][2], o[2][3]), pack2(o[3][2], o[3][3]));
                    }
                }
            }
            if (s >= 0 && s < NSEG - 1) __syncthreads();
        }
        if (s >= NSEG - 1) continue;
        TS(5);
        mbar_wait(bar + B_XF * 8, 0);
        if (tid == 0) mbar_expect(bar + B_XF * 8, 32768);
        TS(6);
        float xa[16], xb[16];
        wg_fence();
        wg32_rs<0>(xa, wa[0], xn_desc);
        wg32_rs<0>(xb, wb[0], xn_desc);
#pragma unroll
        for (int i = 1; i < 16; i++) {
            wg32_rs<1>(xa, wa[i], xn_desc + (i >> 2) * 256 + (i & 3) * 2);
            wg32_rs<1>(xb, wb[i], xn_desc + (i >> 2) * 256 + (i & 3) * 2);
        }
        wg_commit();
        wg_wait<0>();
        reg_fence<16>(xa); reg_fence<16>(xb);
        if (lane == 0) mbar_arrive_cluster(xeB);
        TS(7);
        if (ISV && rank == 5 && tid == 128) {
            mbar_wait(bar + B_XE * 8, (s + 1) & 1);
            for (int i = 0; i < 8; i++)
                tma2d_mc(sb + C_XN + i * 4096, tXn, (i >> 2) * 512 + 256 + (i & 3) * 64, (s + 1) * 32, bar + B_XF * 8, 0x3F);
        }
        if (s >= 0) {
            const uint4* src = &g_xo[s & 3][oks * 16 + t128];
            const bool has2 = t128 + 256 < onk * 16;
            uint4 v[3];
            uint32_t it = 0;
            while (true) {
                v[0] = ld_relaxed4(src); v[1] = ld_relaxed4(src + 128); v[2] = ld_relaxed4(src + (has2 ? 256 : 0));
                if (max(max(umax4(v[0]), umax4(v[1])), umax4(v[2])) != ~0u) break;
                if (++it > (1u << 22)) __trap();
            }
#pragma unroll
            for (int j = 0; j < 3; j++) sts4u(mbw + t128 * 16 + j * 2048, v[j]);
            fence_async();
            bar_sync(1 + wg, 128);
            TS(8);
            float co[4];
            if (!ISV && wg == 0) wg8_chain<22>(co, wo_desc, mb_desc);
            else wg8_chain<21>(co, wo_desc, mb_desc);
            TS(9);
            if (wg == 1) sts4f(red_out, co[0], co[1], co[2], co[3]);
            __syncthreads();
            if (wg == 0) {
                const float4 r = lds4f(red_in);
                const int owner = w4 + (w4 >> 1);
                st_async4(mapa(sb + C_OL + rank * 512 + lane * 16, owner), mapa(bar + B_OL * 8, owner),
                          __float_as_uint(co[0] + r.x), __float_as_uint(co[1] + r.y), __float_as_uint(co[2] + r.z), __float_as_uint(co[3] + r.w));
                TS(10);
                if (!ISV && w4 == 0) {
                    const int slice = cl * 4 + (rank >= 3 ? rank - 1 : rank);
                    char* dst = reinterpret_cast<char*>(&g_xmem[(s + 1) & 3][slice * 16]) + lane * 4;
                    mbar_wait(bar + B_OL * 8, s & 1);
                    float4 a[6];
#pragma unroll
                    for (int i = 0; i < 6; i++) a[i] = lds4f(sb + C_OL + i * 512 + lane * 16);
                    if (lane == 0) mbar_expect(bar + B_OL * 8, 3072);
                    const uint32_t r0 = movm(pack2((a[0].x + a[1].x) + (a[2].x + a[3].x) + (a[4].x + a[5].x), (a[0].y + a[1].y) + (a[2].y + a[3].y) + (a[4].y + a[5].y)));
                    const uint32_t r1 = movm(pack2((a[0].z + a[1].z) + (a[2].z + a[3].z) + (a[4].z + a[5].z), (a[0].w + a[1].w) + (a[2].w + a[3].w) + (a[4].w + a[5].w)));
                    st_relaxed1(dst, r0);
                    st_relaxed1(dst + 128, r1);
                    char* pz = reinterpret_cast<char*>(&g_xmem[(s + 3) & 3][slice * 16]) + lane * 4;
                    st_relaxed1(pz, ~0u);
                    st_relaxed1(pz + 128, ~0u);
                }
            }
        } else {
            mbar_wait(bar + B_WS * 8, 0);
        }
        TS(11);
        mbar_wait(bar + B_XF * 8, 1);
        if (tid == 0) mbar_expect(bar + B_XF * 8, 32768);
        TS(12);
        wg_fence();
#pragma unroll
        for (int i = 0; i < 8; i++) {
            wg32_rs<1>(xa, wa[16 + i], xn_desc + (i >> 2) * 256 + (i & 3) * 2);
            wg32_rs<1>(xb, wb[16 + i], xn_desc + (i >> 2) * 256 + (i & 3) * 2);
        }
#pragma unroll
        for (int i = 0; i < 8; i++) {
            wg32_ss(xa, ws_desc + i * 128, xn_desc + (2 + (i >> 2)) * 256 + (i & 3) * 2);
            wg32_ss(xb, ws_desc + 1024 + i * 128, xn_desc + (2 + (i >> 2)) * 256 + (i & 3) * 2);
        }
        wg_commit();
        wg_wait<0>();
        reg_fence<16>(xa); reg_fence<16>(xb);
        if (lane == 0) mbar_arrive_cluster(xeA);
        TS(13);
        {
            const uint32_t so = (mbw ^ 8192) + t128 * 16;
#pragma unroll
            for (int j = 0; j < 4; j++) {
                if (wg == 0) sts4f(so + j * 2048, xb[4 * j], xb[4 * j + 1], xb[4 * j + 2], xb[4 * j + 3]);
                else sts4f(so + j * 2048, xa[4 * j], xa[4 * j + 1], xa[4 * j + 2], xa[4 * j + 3]);
            }
            __syncthreads();
            uint32_t lo[4], hi[4];
#pragma unroll
            for (int j = 0; j < 4; j++) {
                const float4 r = lds4f(mbw + t128 * 16 + j * 2048);
                lo[j] = wg == 0 ? pack2(xa[4 * j] + r.x, xa[4 * j + 1] + r.y) : pack2(xb[4 * j] + r.x, xb[4 * j + 1] + r.y);
                hi[j] = wg == 0 ? pack2(xa[4 * j + 2] + r.z, xa[4 * j + 3] + r.w) : pack2(xb[4 * j + 2] + r.z, xb[4 * j + 3] + r.w);
            }
            if (!ISV) {
                const uint32_t d = sb + C_QX + wg * 4096 + w4 * 1024 + lane * 16;
                stsm4t(d, lo[0], lo[1], lo[2], lo[3]);
                stsm4t(d + 512, hi[0], hi[1], hi[2], hi[3]);
            } else {
                const int rr = lane & 7;
                const int rho = 32 * (2 * wg + (w4 >> 1)) + 8 * (rr >> 1) + 4 * (w4 & 1) + (rr & 1);
                const uint32_t d = sb + C_V + ((s + 1) & 1) * 10240 + rho * 80 + (lane >> 3) * 16;
                stsm4(d, lo[0], lo[1], lo[2], lo[3]);
                stsm4(d + 160, hi[0], hi[1], hi[2], hi[3]);
            }
        }
        TS(14);
    }
}

__global__ void __cluster_dims__(6, 1, 1) __launch_bounds__(256, 1)
chain_kernel(const __grid_constant__ CUtensorMap tq, const __grid_constant__ CUtensorMap tk, const __grid_constant__ CUtensorMap tv,
             const __grid_constant__ CUtensorMap two, const __grid_constant__ CUtensorMap txn) {
    extern __shared__ __align__(1024) uint8_t smem[];
    const uint32_t sb = smem_u32(smem);
    const int rank = blockIdx.x % 6, cl = blockIdx.x / 6, role = rank % 3;
    if (threadIdx.x == 0) {
        if (sb & 1023) __trap();
        const uint32_t bar = sb + C_BAR;
        for (int i = 0; i < B_NUM; i++) mbar_init(bar + i * 8, i == B_XE ? 48 : 1);
        mbar_expect(bar + B_XF * 8, 32768);
        if (role == 2) {
            mbar_expect(bar + B_SC * 8, 2560);
            mbar_expect(bar + B_P0 * 8, 2048);
            mbar_expect(bar + B_P1 * 8, 2048);
        } else {
            mbar_expect(bar + B_XS * 8, role ? 5120 : 3072);
            mbar_expect(bar + B_OL * 8, 3072);
        }
        asm volatile("fence.mbarrier_init.release.cluster;" ::: "memory");
        fence_async();
    }
    __syncthreads();
    cluster_sync();
    if (role == 2) chain_body<true>(&tv, &tv, &two, &txn, sb, cl, rank);
    else chain_body<false>(&tq, &tk, &two, &txn, sb, cl, rank);
    __syncthreads();
    cluster_sync();
}

constexpr int G_STAGES = 4;
constexpr uint32_t G_STAGE = 49152, G_EPI = G_STAGES * G_STAGE, G_BAR = G_EPI + 32768, G_SMEM = G_BAR + 256;

__device__ __forceinline__ void wg256(float* d, uint32_t da, uint32_t db, uint32_t accum) {
    asm volatile("{\n.reg .b64 da, db;\n.reg .pred p;\nsetp.ne.u32 p, %130, 0;\nmov.b64 da, {%128, " DESC_HI_SW128 "};\nmov.b64 db, {%129, " DESC_HI_SW128 "};\n"
                 "wgmma.mma_async.sync.aligned.m64n256k16.f32.bf16.bf16 {"
                 "%0,%1,%2,%3,%4,%5,%6,%7,%8,%9,%10,%11,%12,%13,%14,%15,%16,%17,%18,%19,%20,%21,%22,%23,%24,%25,%26,%27,%28,%29,%30,%31,"
                 "%32,%33,%34,%35,%36,%37,%38,%39,%40,%41,%42,%43,%44,%45,%46,%47,%48,%49,%50,%51,%52,%53,%54,%55,%56,%57,%58,%59,%60,%61,%62,%63,"
                 "%64,%65,%66,%67,%68,%69,%70,%71,%72,%73,%74,%75,%76,%77,%78,%79,%80,%81,%82,%83,%84,%85,%86,%87,%88,%89,%90,%91,%92,%93,%94,%95,"
                 "%96,%97,%98,%99,%100,%101,%102,%103,%104,%105,%106,%107,%108,%109,%110,%111,%112,%113,%114,%115,%116,%117,%118,%119,%120,%121,%122,%123,%124,%125,%126,%127"
                 "}, da, db, p, 1, 1, 0, 1;\n}"
                 : ACC16(d), ACC16((d + 16)), ACC16((d + 32)), ACC16((d + 48)), ACC16((d + 64)), ACC16((d + 80)), ACC16((d + 96)), ACC16((d + 112))
                 : "r"(da), "r"(db), "r"(accum));
}
__device__ __forceinline__ float sigmoidf_(float v) { return rcp(1.f + ex2(-1.4426950408889634f * v)); }

template <int MODE>
__global__ void __cluster_dims__(2, 1, 1) __launch_bounds__(384, 1)
gemm_kernel(const __grid_constant__ CUtensorMap tA, const __grid_constant__ CUtensorMap tB0, const __grid_constant__ CUtensorMap tB1,
            const __grid_constant__ CUtensorMap tOut, const __grid_constant__ CUtensorMap tX, const __grid_constant__ CUtensorMap tY) {
    constexpr int KB = MODE == 0 ? DM / 64 : (MODE == 1 ? FF / 64 : HD / 64);
    constexpr int NT = MODE == 0 ? FF / 128 : DM / 256;
    constexpr int NTILES = NT * 8;
    extern __shared__ __align__(1024) uint8_t smem[];
    const uint32_t sb = smem_u32(smem);
    const uint32_t full = sb + G_BAR, empty = full + 64;
    const int tid = threadIdx.x, lane = tid & 31;
    const int wg = __shfl_sync(~0u, tid >> 7, 0);
    const int rank = blockIdx.x & 1, pair = blockIdx.x >> 1, npair = gridDim.x >> 1;
    if (tid == 0) {
        if (sb & 1023) __trap();
        for (int i = 0; i < G_STAGES; i++) { mbar_init(full + i * 8, 1); mbar_init(empty + i * 8, 16); }
        asm volatile("fence.mbarrier_init.release.cluster;" ::: "memory");
        fence_async();
    }
    __syncthreads();
    cluster_sync();
    if (wg == 0) {
        asm volatile("setmaxnreg.dec.sync.aligned.u32 40;");
        if (tid == 0) {
            uint32_t st = 0, ph = 1;
            for (int tile = pair; tile < NTILES; tile += npair) {
                const int mp = tile & 7, nt = tile >> 3, row0 = (mp * 2 + rank) * 128;
                const CUtensorMap* tB = (MODE == 0 && rank) ? &tB1 : &tB0;
                const int bcol = MODE == 0 ? nt * 128 : nt * 256 + rank * 128;
                for (int kb = 0; kb < KB; kb++) {
                    mbar_wait(empty + st * 8, ph);
                    const uint32_t base = sb + st * G_STAGE;
                    mbar_expect(full + st * 8, G_STAGE);
                    tma2d(base, &tA, kb * 64, row0, full + st * 8);
                    tma2d_mc(base + 16384 + rank * 16384, tB, bcol, kb * 64, full + st * 8, 3);
                    tma2d_mc(base + 16384 + rank * 16384 + 8192, tB, bcol + 64, kb * 64, full + st * 8, 3);
                    if (++st == G_STAGES) { st = 0; ph ^= 1; }
                }
                if (MODE == 2) {
                    for (int q = 0; q < 4; q++) {
                        mbar_wait(empty + st * 8, ph);
                        const uint32_t base = sb + st * G_STAGE;
                        mbar_expect(full + st * 8, 32768);
                        tma2d(base, &tX, nt * 256 + q * 64, row0, full + st * 8);
                        tma2d(base + 16384, &tY, nt * 256 + q * 64, row0, full + st * 8);
                        if (++st == G_STAGES) { st = 0; ph ^= 1; }
                    }
                }
            }
        }
        __syncwarp();
        cluster_sync();
    } else {
        asm volatile("setmaxnreg.inc.sync.aligned.u32 232;");
        const int cw = wg - 1, w4 = (tid >> 5) & 3;
        const uint32_t empty_dst = mapa(empty, lane & 1);
        const uint32_t epi = sb + G_EPI + cw * 16384;
        const int er = w4 * 16 + (lane & 15), ec = lane >> 4;
        uint32_t st = 0, ph = 0;
        float acc[128];
        for (int tile = pair; tile < NTILES; tile += npair) {
            const int mp = tile & 7, nt = tile >> 3, row0 = (mp * 2 + rank) * 128 + cw * 64;
            uint32_t prev = 0;
#pragma unroll 1
            for (int kb = 0; kb < KB; kb++) {
                mbar_wait(full + st * 8, ph);
                const uint32_t base = sb + st * G_STAGE;
                const uint32_t da = (((base + cw * 8192) & 0x3FFFF) >> 4) | (1u << 16);
                const uint32_t db = (((base + 16384) & 0x3FFFF) >> 4) | (512u << 16);
                wg_fence();
#pragma unroll
                for (int k = 0; k < 4; k++) wg256(acc, da + k * 2, db + k * 128, (kb | k) != 0);
                wg_commit();
                if (kb > 0) {
                    wg_wait<1>();
                    if (lane < 2) mbar_arrive_cluster(empty_dst + prev * 8);
                }
                prev = st;
                if (++st == G_STAGES) { st = 0; ph ^= 1; }
            }
            wg_wait<0>();
            reg_fence<128>(acc);
            if (lane < 2) mbar_arrive_cluster(empty_dst + prev * 8);
#pragma unroll
            for (int hp = 0; hp < (MODE == 0 ? 1 : 2); hp++) {
                uint32_t o[32];
#pragma unroll
                for (int bx = 0; bx < 2; bx++) {
                    uint32_t xa = 0;
                    if (MODE == 2) {
                        mbar_wait(full + st * 8, ph);
                        xa = sb + st * G_STAGE + (cw * 64 + er) * 128;
                    }
#pragma unroll
                    for (int j = 0; j < 4; j++) {
                        const int a0 = hp * 64 + bx * 32 + j * 8;
                        uint32_t* oo = o + bx * 16 + j * 4;
                        if (MODE == 0) {
#pragma unroll
                            for (int i = 0; i < 4; i++)
                                oo[i] = pack2(sigmoidf_(acc[a0 + 2 * i]) * acc[64 + a0 + 2 * i], sigmoidf_(acc[a0 + 2 * i + 1]) * acc[64 + a0 + 2 * i + 1]);
                        } else if (MODE == 1) {
#pragma unroll
                            for (int i = 0; i < 4; i++)
                                oo[i] = pack2(sigmoidf_(acc[a0 + 2 * i]) * acc[a0 + 2 * i], sigmoidf_(acc[a0 + 2 * i + 1]) * acc[a0 + 2 * i + 1]);
                        } else {
                            uint32_t xv[4], yv[4];
                            const uint32_t ad = xa + (((2 * j + ec) ^ (er & 7)) << 4);
                            ldsm4(xv, ad); ldsm4(yv, ad + 16384);
#pragma unroll
                            for (int i = 0; i < 4; i++)
                                oo[i] = pack2(fmaf(acc[a0 + 2 * i], bf_lo(yv[i]), bf_lo(xv[i])), fmaf(acc[a0 + 2 * i + 1], bf_hi(yv[i]), bf_hi(xv[i])));
                        }
                    }
                    if (MODE == 2) {
                        __syncwarp();
                        if (lane < 2) mbar_arrive_cluster(empty_dst + st * 8);
                        if (++st == G_STAGES) { st = 0; ph ^= 1; }
                    }
                }
                if ((tid & 127) == 0) asm volatile("cp.async.bulk.wait_group.read 0;" ::: "memory");
                bar_sync(1 + cw, 128);
#pragma unroll
                for (int bx = 0; bx < 2; bx++)
#pragma unroll
                    for (int j = 0; j < 4; j++) {
                        const uint32_t* oo = o + bx * 16 + j * 4;
                        stsm4(epi + bx * 8192 + er * 128 + (((2 * j + ec) ^ (er & 7)) << 4), oo[0], oo[1], oo[2], oo[3]);
                    }
                fence_async();
                bar_sync(1 + cw, 128);
                if ((tid & 127) == 0) {
                    const int col = MODE == 0 ? nt * 128 : nt * 256 + hp * 128;
                    tma2d_store(&tOut, col, row0, epi);
                    tma2d_store(&tOut, col + 64, row0, epi + 8192);
                    asm volatile("cp.async.bulk.commit_group;" ::: "memory");
                }
            }
        }
        if ((tid & 127) == 0) asm volatile("cp.async.bulk.wait_group 0;" ::: "memory");
        __syncwarp();
        cluster_sync();
    }
}

typedef CUresult (*EncodeFn)(CUtensorMap*, CUtensorMapDataType, cuuint32_t, void*, const cuuint64_t*, const cuuint64_t*, const cuuint32_t*,
                             const cuuint32_t*, CUtensorMapInterleave, CUtensorMapSwizzle, CUtensorMapL2promotion, CUtensorMapFloatOOBfill);

CUtensorMap make_map(EncodeFn enc, const void* p, int rows, int cols, int box_rows) {
    CUtensorMap m;
    cuuint64_t dims[2] = {(cuuint64_t)cols, (cuuint64_t)rows}, strides[1] = {(cuuint64_t)cols * 2};
    cuuint32_t box[2] = {64, (cuuint32_t)box_rows}, es[2] = {1, 1};
    enc(&m, CU_TENSOR_MAP_DATA_TYPE_BFLOAT16, 2, const_cast<void*>(p), dims, strides, box, es, CU_TENSOR_MAP_INTERLEAVE_NONE,
        CU_TENSOR_MAP_SWIZZLE_128B, CU_TENSOR_MAP_L2_PROMOTION_L2_128B, CU_TENSOR_MAP_FLOAT_OOB_FILL_NONE);
    return m;
}

}

extern "C" void kernel_launch(void* const* d_in, const int* in_sizes, int n_in, void* d_out, int out_size) {
    const __nv_bfloat16* x = (const __nv_bfloat16*)d_in[0];
    const __nv_bfloat16* mem0 = (const __nv_bfloat16*)d_in[1];
    void* fn = nullptr;
    cudaDriverEntryPointQueryResult qr;
    cudaGetDriverEntryPoint("cuTensorMapEncodeTiled", &fn, cudaEnableDefault, &qr);
    EncodeFn enc = (EncodeFn)fn;
    void *xn, *ox, *h, *y;
    cudaGetSymbolAddress(&xn, g_xn); cudaGetSymbolAddress(&ox, g_ox); cudaGetSymbolAddress(&h, g_h); cudaGetSymbolAddress(&y, g_y);

    const CUtensorMap tq = make_map(enc, d_in[2], DM, HD, 128), tk = make_map(enc, d_in[3], DM, HD, 128), tv = make_map(enc, d_in[4], DM, HD, 128);
    const CUtensorMap two16 = make_map(enc, d_in[5], HD, DM, 16), txn32 = make_map(enc, xn, SEQ, DM, 32);
    const CUtensorMap txn128 = make_map(enc, xn, SEQ, DM, 128), tg = make_map(enc, d_in[8], DM, FF, 64), tu = make_map(enc, d_in[9], DM, FF, 64);
    const CUtensorMap th64 = make_map(enc, h, SEQ, FF, 64), th128 = make_map(enc, h, SEQ, FF, 128), td = make_map(enc, d_in[10], FF, DM, 64);
    const CUtensorMap ty64 = make_map(enc, y, SEQ, DM, 64), ty128 = make_map(enc, y, SEQ, DM, 128), tx128 = make_map(enc, x, SEQ, DM, 128);
    const CUtensorMap tox = make_map(enc, ox, SEQ, HD, 128), two64 = make_map(enc, d_in[5], HD, DM, 64), tout = make_map(enc, d_out, SEQ, DM, 64);

    cudaFuncSetAttribute(chain_kernel, cudaFuncAttributeMaxDynamicSharedMemorySize, C_SMEM);
    cudaFuncSetAttribute(gemm_kernel<0>, cudaFuncAttributeMaxDynamicSharedMemorySize, G_SMEM);
    cudaFuncSetAttribute(gemm_kernel<1>, cudaFuncAttributeMaxDynamicSharedMemorySize, G_SMEM);
    cudaFuncSetAttribute(gemm_kernel<2>, cudaFuncAttributeMaxDynamicSharedMemorySize, G_SMEM);

    cudaStream_t st = cudaStreamPerThread;
    ln_kernel<<<SEQ / 8, 256, 0, st>>>(x, mem0);
    chain_kernel<<<96, 256, C_SMEM, st>>>(tq, tk, tv, two16, txn32);
    gemm_kernel<0><<<132, 384, G_SMEM, st>>>(txn128, tg, tu, th64, th64, th64);
    gemm_kernel<1><<<64, 384, G_SMEM, st>>>(th128, td, td, ty64, ty64, ty64);
    gemm_kernel<2><<<64, 384, G_SMEM, st>>>(tox, two64, two64, tout, tx128, ty128);
}
```

```cpp
#include <cuda_runtime.h>
#include <cuda_bf16.h>
#include <cuda.h>
#include <stdint.h>

namespace {

constexpr int SEQ = 2048, DM = 1024, HD = 4096, FF = 3584, NSEG = 64;

__device__ __align__(1024) __nv_bfloat16 g_xn[SEQ * DM];
__device__ __align__(1024) uint4 g_xc[SEQ * DM / 8];
__device__ __align__(1024) __nv_bfloat16 g_ox[SEQ * HD];
__device__ __align__(1024) __nv_bfloat16 g_h[SEQ * FF];
__device__ __align__(1024) __nv_bfloat16 g_y[SEQ * DM];
__device__ __align__(1024) uint4 g_xmem[4][1024];
__device__ __align__(1024) uint4 g_xo[4][4096];

__device__ __forceinline__ uint32_t smem_u32(const void* p) { return (uint32_t)__cvta_generic_to_shared(p); }
__device__ __forceinline__ uint32_t mapa(uint32_t a, uint32_t r) {
    uint32_t o; asm("mapa.shared::cluster.u32 %0, %1, %2;" : "=r"(o) : "r"(a), "r"(r)); return o;
}
__device__ __forceinline__ void mbar_init(uint32_t a, uint32_t cnt) {
    asm volatile("mbarrier.init.shared.b64 [%0], %1;" :: "r"(a), "r"(cnt) : "memory");
}
__device__ __forceinline__ void mbar_expect(uint32_t a, uint32_t bytes) {
    asm volatile("mbarrier.arrive.expect_tx.shared.b64 _, [%0], %1;" :: "r"(a), "r"(bytes) : "memory");
}
__device__ __forceinline__ void mbar_arrive_cluster(uint32_t a) {
    asm volatile("mbarrier.arrive.shared::cluster.b64 _, [%0];" :: "r"(a) : "memory");
}
__device__ __forceinline__ bool mbar_try(uint32_t a, uint32_t par) {
    uint32_t ok;
    asm volatile("{\n.reg .pred p;\nmbarrier.try_wait.parity.shared::cta.b64 p, [%1], %2;\nselp.u32 %0, 1, 0, p;\n}"
                 : "=r"(ok) : "r"(a), "r"(par) : "memory");
    return ok;
}
__device__ __forceinline__ void mbar_wait(uint32_t a, uint32_t par) {
    if (mbar_try(a, par)) return;
    uint32_t it = 0;
    while (!mbar_try(a, par)) { if (++it > (1u << 22)) __trap(); }
}
__device__ __forceinline__ void tma2d(uint32_t dst, const CUtensorMap* m, int c0, int c1, uint32_t bar) {
    asm volatile("cp.async.bulk.tensor.2d.shared::cluster.global.mbarrier::complete_tx::bytes [%0], [%1, {%3, %4}], [%2];"
                 :: "r"(dst), "l"(m), "r"(bar), "r"(c0), "r"(c1) : "memory");
}
__device__ __forceinline__ void tma2d_mc(uint32_t dst, const CUtensorMap* m, int c0, int c1, uint32_t bar, uint16_t mask) {
    asm volatile("cp.async.bulk.tensor.2d.shared::cluster.global.mbarrier::complete_tx::bytes.multicast::cluster [%0], [%1, {%3, %4}], [%2], %5;"
                 :: "r"(dst), "l"(m), "r"(bar), "r"(c0), "r"(c1), "h"(mask) : "memory");
}
__device__ __forceinline__ void bulk_mc(uint32_t dst, const void* src, uint32_t bytes, uint32_t bar, uint16_t mask) {
    asm volatile("cp.async.bulk.shared::cluster.global.mbarrier::complete_tx::bytes.multicast::cluster [%0], [%1], %2, [%3], %4;"
                 :: "r"(dst), "l"(src), "r"(bytes), "r"(bar), "h"(mask) : "memory");
}
__device__ __forceinline__ void bar_arrive(int id, int n) { asm volatile("bar.arrive %0, %1;" :: "r"(id), "r"(n) : "memory"); }
__device__ __forceinline__ uint32_t junk() { uint32_t r; asm volatile("" : "=r"(r)); return r; }
__device__ __forceinline__ uint32_t clk() { uint32_t c; asm volatile("mov.u32 %0, %%clock;" : "=r"(c)); return c; }
__device__ __forceinline__ void tma2d_store(const CUtensorMap* m, int c0, int c1, uint32_t src) {
    asm volatile("cp.async.bulk.tensor.2d.global.shared::cta.bulk_group [%0, {%1, %2}], [%3];"
                 :: "l"(m), "r"(c0), "r"(c1), "r"(src) : "memory");
}
__device__ __forceinline__ void bar_sync(int id, int n) { asm volatile("bar.sync %0, %1;" :: "r"(id), "r"(n) : "memory"); }
__device__ __forceinline__ void fence_async() { asm volatile("fence.proxy.async.shared::cta;" ::: "memory"); }
__device__ __forceinline__ void cluster_sync() {
    asm volatile("barrier.cluster.arrive.release.aligned;\nbarrier.cluster.wait.acquire.aligned;" ::: "memory");
}
__device__ __forceinline__ void ldsm4(uint32_t* r, uint32_t a) {
    asm volatile("ldmatrix.sync.aligned.m8n8.x4.shared.b16 {%0,%1,%2,%3}, [%4];"
                 : "=r"(r[0]), "=r"(r[1]), "=r"(r[2]), "=r"(r[3]) : "r"(a) : "memory");
}
__device__ __forceinline__ void ldsm4t(uint32_t* r, uint32_t a) {
    asm volatile("ldmatrix.sync.aligned.m8n8.x4.trans.shared.b16 {%0,%1,%2,%3}, [%4];"
                 : "=r"(r[0]), "=r"(r[1]), "=r"(r[2]), "=r"(r[3]) : "r"(a) : "memory");
}
__device__ __forceinline__ void stsm4(uint32_t a, uint32_t r0, uint32_t r1, uint32_t r2, uint32_t r3) {
    asm volatile("stmatrix.sync.aligned.m8n8.x4.shared.b16 [%0], {%1,%2,%3,%4};" :: "r"(a), "r"(r0), "r"(r1), "r"(r2), "r"(r3) : "memory");
}
__device__ __forceinline__ void stsm4t(uint32_t a, uint32_t r0, uint32_t r1, uint32_t r2, uint32_t r3) {
    asm volatile("stmatrix.sync.aligned.m8n8.x4.trans.shared.b16 [%0], {%1,%2,%3,%4};" :: "r"(a), "r"(r0), "r"(r1), "r"(r2), "r"(r3) : "memory");
}
__device__ __forceinline__ void stsm2(uint32_t a, uint32_t r0, uint32_t r1) {
    asm volatile("stmatrix.sync.aligned.m8n8.x2.shared.b16 [%0], {%1,%2};" :: "r"(a), "r"(r0), "r"(r1) : "memory");
}
__device__ __forceinline__ void stsm2t(uint32_t a, uint32_t r0, uint32_t r1) {
    asm volatile("stmatrix.sync.aligned.m8n8.x2.trans.shared.b16 [%0], {%1,%2};" :: "r"(a), "r"(r0), "r"(r1) : "memory");
}
__device__ __forceinline__ uint32_t movm(uint32_t a) {
    uint32_t d; asm volatile("movmatrix.sync.aligned.m8n8.trans.b16 %0, %1;" : "=r"(d) : "r"(a)); return d;
}
__device__ __forceinline__ void mma16(float* d, uint32_t a0, uint32_t a1, uint32_t a2, uint32_t a3, uint32_t b0, uint32_t b1) {
    asm volatile("mma.sync.aligned.m16n8k16.row.col.f32.bf16.bf16.f32 {%0,%1,%2,%3}, {%4,%5,%6,%7}, {%8,%9}, {%0,%1,%2,%3};"
                 : "+f"(d[0]), "+f"(d[1]), "+f"(d[2]), "+f"(d[3]) : "r"(a0), "r"(a1), "r"(a2), "r"(a3), "r"(b0), "r"(b1));
}
__device__ __forceinline__ void mma8(float* d, uint32_t a0, uint32_t a1, uint32_t b0) {
    asm volatile("mma.sync.aligned.m16n8k8.row.col.f32.bf16.bf16.f32 {%0,%1,%2,%3}, {%4,%5}, {%6}, {%0,%1,%2,%3};"
                 : "+f"(d[0]), "+f"(d[1]), "+f"(d[2]), "+f"(d[3]) : "r"(a0), "r"(a1), "r"(b0));
}
__device__ __forceinline__ uint32_t pack2(float lo, float hi) {
    uint32_t r; asm("cvt.rn.bf16x2.f32 %0, %1, %2;" : "=r"(r) : "f"(hi), "f"(lo)); return r;
}
__device__ __forceinline__ float bf_lo(uint32_t v) { return __uint_as_float(v << 16); }
__device__ __forceinline__ float bf_hi(uint32_t v) { return __uint_as_float(v & 0xFFFF0000u); }
__device__ __forceinline__ float ex2(float x) { float y; asm("ex2.approx.ftz.f32 %0, %1;" : "=f"(y) : "f"(x)); return y; }
__device__ __forceinline__ float rcp(float x) { float y; asm("rcp.approx.ftz.f32 %0, %1;" : "=f"(y) : "f"(x)); return y; }
__device__ __forceinline__ void sts4f(uint32_t a, float x, float y, float z, float w) {
    asm volatile("st.shared.v4.f32 [%0], {%1,%2,%3,%4};" :: "r"(a), "f"(x), "f"(y), "f"(z), "f"(w) : "memory");
}
__device__ __forceinline__ void sts4u(uint32_t a, uint4 v) {
    asm volatile("st.shared.v4.u32 [%0], {%1,%2,%3,%4};" :: "r"(a), "r"(v.x), "r"(v.y), "r"(v.z), "r"(v.w) : "memory");
}
__device__ __forceinline__ float4 lds4f(uint32_t a) {
    float4 v; asm volatile("ld.shared.v4.f32 {%0,%1,%2,%3}, [%4];" : "=f"(v.x), "=f"(v.y), "=f"(v.z), "=f"(v.w) : "r"(a) : "memory"); return v;
}
__device__ __forceinline__ float2 lds2f(uint32_t a) {
    float2 v; asm volatile("ld.shared.v2.f32 {%0,%1}, [%2];" : "=f"(v.x), "=f"(v.y) : "r"(a) : "memory"); return v;
}
__device__ __forceinline__ uint4 lds4u(uint32_t a) {
    uint4 v; asm volatile("ld.shared.v4.u32 {%0,%1,%2,%3}, [%4];" : "=r"(v.x), "=r"(v.y), "=r"(v.z), "=r"(v.w) : "r"(a) : "memory"); return v;
}
__device__ __forceinline__ uint2 lds2u(uint32_t a) {
    uint2 v; asm volatile("ld.shared.v2.u32 {%0,%1}, [%2];" : "=r"(v.x), "=r"(v.y) : "r"(a) : "memory"); return v;
}
__device__ __forceinline__ void st_async4(uint32_t a, uint32_t bar, uint32_t x, uint32_t y, uint32_t z, uint32_t w) {
    asm volatile("st.async.shared::cluster.mbarrier::complete_tx::bytes.v4.b32 [%0], {%1,%2,%3,%4}, [%5];"
                 :: "r"(a), "r"(x), "r"(y), "r"(z), "r"(w), "r"(bar) : "memory");
}
__device__ __forceinline__ void st_async2(uint32_t a, uint32_t bar, uint32_t x, uint32_t y) {
    asm volatile("st.async.shared::cluster.mbarrier::complete_tx::bytes.v2.b32 [%0], {%1,%2}, [%3];"
                 :: "r"(a), "r"(x), "r"(y), "r"(bar) : "memory");
}
__device__ __forceinline__ void st_async1(uint32_t a, uint32_t bar, uint32_t x) {
    asm volatile("st.async.shared::cluster.mbarrier::complete_tx::bytes.b32 [%0], %1, [%2];" :: "r"(a), "r"(x), "r"(bar) : "memory");
}
__device__ __forceinline__ uint4 ld_relaxed4(const uint4* p) {
    uint4 v;
    asm volatile("ld.relaxed.gpu.global.v4.u32 {%0,%1,%2,%3}, [%4];" : "=r"(v.x), "=r"(v.y), "=r"(v.z), "=r"(v.w) : "l"(p) : "memory");
    return v;
}
__device__ __forceinline__ void st_relaxed4(uint4* p, uint4 v) {
    asm volatile("st.relaxed.gpu.global.v4.u32 [%0], {%1,%2,%3,%4};" :: "l"(p), "r"(v.x), "r"(v.y), "r"(v.z), "r"(v.w) : "memory");
}
__device__ __forceinline__ void st_relaxed1(void* p, uint32_t v) {
    asm volatile("st.relaxed.gpu.global.u32 [%0], %1;" :: "l"(p), "r"(v) : "memory");
}
__device__ __forceinline__ uint32_t umax4(uint4 v) { return max(max(v.x, v.y), max(v.z, v.w)); }
__device__ __forceinline__ void wg_fence() { asm volatile("wgmma.fence.sync.aligned;" ::: "memory"); }
__device__ __forceinline__ void wg_commit() { asm volatile("wgmma.commit_group.sync.aligned;" ::: "memory"); }
template <int N> __device__ __forceinline__ void wg_wait() { asm volatile("wgmma.wait_group.sync.aligned %0;" :: "n"(N) : "memory"); }
template <int N> __device__ __forceinline__ void reg_fence(float* d) {
#pragma unroll
    for (int i = 0; i < N; i++) asm volatile("" : "+f"(d[i]) :: "memory");
}
#define ACC16(d) "+f"(d[0]), "+f"(d[1]), "+f"(d[2]), "+f"(d[3]), "+f"(d[4]), "+f"(d[5]), "+f"(d[6]), "+f"(d[7]), \
                 "+f"(d[8]), "+f"(d[9]), "+f"(d[10]), "+f"(d[11]), "+f"(d[12]), "+f"(d[13]), "+f"(d[14]), "+f"(d[15])
#define DESC_HI_SW128 "0x40000040"
#define OUT16(d) "=f"(d[0]), "=f"(d[1]), "=f"(d[2]), "=f"(d[3]), "=f"(d[4]), "=f"(d[5]), "=f"(d[6]), "=f"(d[7]), \
                 "=f"(d[8]), "=f"(d[9]), "=f"(d[10]), "=f"(d[11]), "=f"(d[12]), "=f"(d[13]), "=f"(d[14]), "=f"(d[15])
template <int ACCUM>
__device__ __forceinline__ void wg32_rs(float* d, const uint32_t* a, uint32_t db) {
    if (ACCUM)
        asm volatile("{\n.reg .b64 db;\nmov.b64 db, {%20, " DESC_HI_SW128 "};\n"
                     "wgmma.mma_async.sync.aligned.m64n32k16.f32.bf16.bf16 {%0,%1,%2,%3,%4,%5,%6,%7,%8,%9,%10,%11,%12,%13,%14,%15}, "
                     "{%16,%17,%18,%19}, db, 1, 1, 1, 0;\n}"
                     : ACC16(d) : "r"(a[0]), "r"(a[1]), "r"(a[2]), "r"(a[3]), "r"(db));
    else
        asm volatile("{\n.reg .b64 db;\nmov.b64 db, {%20, " DESC_HI_SW128 "};\n"
                     "wgmma.mma_async.sync.aligned.m64n32k16.f32.bf16.bf16 {%0,%1,%2,%3,%4,%5,%6,%7,%8,%9,%10,%11,%12,%13,%14,%15}, "
                     "{%16,%17,%18,%19}, db, 0, 1, 1, 0;\n}"
                     : OUT16(d) : "r"(a[0]), "r"(a[1]), "r"(a[2]), "r"(a[3]), "r"(db));
}
__device__ __forceinline__ void wg32_ss(float* d, uint32_t da, uint32_t db) {
    asm volatile("{\n.reg .b64 da, db;\nmov.b64 da, {%16, " DESC_HI_SW128 "};\nmov.b64 db, {%17, " DESC_HI_SW128 "};\n"
                 "wgmma.mma_async.sync.aligned.m64n32k16.f32.bf16.bf16 {%0,%1,%2,%3,%4,%5,%6,%7,%8,%9,%10,%11,%12,%13,%14,%15}, "
                 "da, db, 1, 1, 1, 1, 0;\n}"
                 : ACC16(d) : "r"(da), "r"(db));
}
template <int N>
__device__ __forceinline__ void wg8_chain(float* d, uint32_t da, uint32_t db) {
    wg_fence();
    asm volatile("{\n.reg .b64 da, db;\nmov.b64 da, {%4, " DESC_HI_SW128 "};\nmov.b64 db, {%5, 0x10};\n"
                 "wgmma.mma_async.sync.aligned.m64n8k16.f32.bf16.bf16 {%0,%1,%2,%3}, da, db, 0, 1, 1, 1, 0;\n}"
                 : "=f"(d[0]), "=f"(d[1]), "=f"(d[2]), "=f"(d[3]) : "r"(da), "r"(db));
#pragma unroll
    for (int i = 1; i < N; i++)
        asm volatile("{\n.reg .b64 da, db;\nmov.b64 da, {%4, " DESC_HI_SW128 "};\nmov.b64 db, {%5, 0x10};\n"
                     "wgmma.mma_async.sync.aligned.m64n8k16.f32.bf16.bf16 {%0,%1,%2,%3}, da, db, 1, 1, 1, 1, 0;\n}"
                     : "+f"(d[0]), "+f"(d[1]), "+f"(d[2]), "+f"(d[3]) : "r"(da + i * 128), "r"(db + i * 16));
    wg_commit();
    wg_wait<0>();
    reg_fence<4>(d);
}

__global__ void __launch_bounds__(256) ln_kernel(const __nv_bfloat16* __restrict__ x, const __nv_bfloat16* __restrict__ mem0) {
    const int lane = threadIdx.x & 31, row = blockIdx.x * 8 + (threadIdx.x >> 5);
    const uint4* src = reinterpret_cast<const uint4*>(x + (size_t)row * DM);
    uint4 v[4];
#pragma unroll
    for (int j = 0; j < 4; j++) v[j] = src[j * 32 + lane];
    const int gi = blockIdx.x * 256 + threadIdx.x;
    const uint4 poison = make_uint4(~0u, ~0u, ~0u, ~0u);
    if (gi < 1024) {
        uint4 m = reinterpret_cast<const uint4*>(mem0)[(gi & 7) * 128 + (gi >> 3)];
        if (m.x == ~0u) m.x = 0x7FFF7FFFu;
        if (m.y == ~0u) m.y = 0x7FFF7FFFu;
        if (m.z == ~0u) m.z = 0x7FFF7FFFu;
        if (m.w == ~0u) m.w = 0x7FFF7FFFu;
        g_xmem[0][gi] = m;
    } else if (gi < 4096) {
        (&g_xmem[0][0])[gi] = poison;
    } else if (gi < 4096 + 16384) {
        (&g_xo[0][0])[gi - 4096] = poison;
    }
    float f[32];
#pragma unroll
    for (int j = 0; j < 4; j++) {
        f[j * 8 + 0] = bf_lo(v[j].x); f[j * 8 + 1] = bf_hi(v[j].x); f[j * 8 + 2] = bf_lo(v[j].y); f[j * 8 + 3] = bf_hi(v[j].y);
        f[j * 8 + 4] = bf_lo(v[j].z); f[j * 8 + 5] = bf_hi(v[j].z); f[j * 8 + 6] = bf_lo(v[j].w); f[j * 8 + 7] = bf_hi(v[j].w);
    }
    float s = 0.f;
#pragma unroll
    for (int i = 0; i < 32; i++) s += f[i];
#pragma unroll
    for (int o = 16; o; o >>= 1) s += __shfl_xor_sync(~0u, s, o);
    const float mean = s * (1.f / DM);
    float q = 0.f;
#pragma unroll
    for (int i = 0; i < 32; i++) { f[i] -= mean; q += f[i] * f[i]; }
#pragma unroll
    for (int o = 16; o; o >>= 1) q += __shfl_xor_sync(~0u, q, o);
    const float r = 1.f / sqrtf(q * (1.f / DM) + 1e-5f);
    uint4* dst = reinterpret_cast<uint4*>(g_xn + (size_t)row * DM);
    uint4* dst2 = g_xc + (row >> 5) * 4096 + (lane >> 3) * 256 + (row & 31) * 8 + ((lane & 7) ^ (row & 7));
#pragma unroll
    for (int j = 0; j < 4; j++) {
        const uint4 o = make_uint4(pack2(f[j * 8] * r, f[j * 8 + 1] * r), pack2(f[j * 8 + 2] * r, f[j * 8 + 3] * r),
                                   pack2(f[j * 8 + 4] * r, f[j * 8 + 5] * r), pack2(f[j * 8 + 6] * r, f[j * 8 + 7] * r));
        dst[j * 32 + lane] = o;
        dst2[(j & 1) * 2048 + (j >> 1) * 1024] = o;
    }
}

constexpr uint32_t C_WS = 0, C_WO = 65536, C_XN = 153600, C_MB = 186368, C_MISC = 202752, C_SMEM = 232448;
constexpr uint32_t C_BAR = C_MISC;
constexpr uint32_t C_RED0 = C_MISC + 256;
constexpr uint32_t C_RED1Q = C_RED0 + 2048, C_QX = C_RED1Q + 2048, C_KX = C_QX + 4096, C_QM = C_KX + 4096, C_KM = C_QM + 1024,
                   C_XSL = C_KM + 1024, C_OL = C_XSL + 5120;
constexpr uint32_t C_V = C_RED0 + 2048, C_PL = C_V + 20480, C_SL = C_PL + 4096, C_RED1V = C_WO + 42 * 2048;
static_assert(C_OL + 3072 <= C_SMEM && C_SL + 2560 <= C_SMEM, "smem overflow");
enum { B_W0 = 0, B_W1, B_W2, B_WS, B_WO, B_XF, B_XE, B_SC, B_P0, B_P1, B_XS, B_OL, B_NUM };
constexpr float SM_SCALE = 0.08838834764831845f * 1.4426950408889634f;

#define TS(i)
#define NOFILL 0
#define DLY1 0
#define DLY2 0

template <bool ISV>
__device__ __forceinline__ void chain_body(const CUtensorMap* tA, const CUtensorMap* tB, const CUtensorMap* tWo,
                                           const uint32_t sb, const int cl, const int rank) {
    const int tid = threadIdx.x;
    uint32_t l16_ = __shfl_sync(~0u, (tid & 31) * 16, tid & 31);
    const int wg = __shfl_sync(~0u, tid >> 7, 0), w4 = __shfl_sync(~0u, (tid >> 5) & 3, 0), warp = wg * 4 + w4;
    const int lane = tid & 31;
    const int role = rank % 3, hb = rank - role, head = 2 * cl + (rank >= 3);
    const uint32_t bar = sb + C_BAR;
    constexpr int ONK = ISV ? 42 : 43;
    const int ostart = rank * 43 - (rank >= 3);

    const int colA = head * 128 + (ISV ? 0 : role * 64), colB = head * 128 + (ISV ? 64 : role * 64);
    auto load_chunk = [&](uint32_t dst, int j, uint32_t b) {
        mbar_expect(b, 65536);
        tma2d(dst, tA, colA, j * 128, b);
        tma2d(dst + 16384, tB, colB, j * 128, b);
        tma2d(dst + 32768, tB, colB, 512 + j * 128, b);
        tma2d(dst + 49152, tA, colA, 512 + j * 128, b);
    };
    if (tid == 0)
        for (int j = 0; j < 3; j++) load_chunk(sb + j * 65536, j, bar + (B_W0 + j) * 8);
    uint32_t wk[24][4], wv[24][4];
    const int kr = (lane & 7) + ((lane >> 4) << 3);
    const uint32_t a_adr = sb + wg * 32768 + kr * 128 + (((w4 * 2 + ((lane >> 3) & 1)) ^ (kr & 7)) << 4);
#pragma unroll
    for (int j = 0; j < 3; j++) {
        mbar_wait(bar + (B_W0 + j) * 8, 0);
#pragma unroll
        for (int i = 0; i < 8; i++) {
            ldsm4t(wk[j * 8 + i], a_adr + j * 65536 + i * 2048);
            ldsm4t(wv[j * 8 + i], a_adr + j * 65536 + 16384 + i * 2048);
        }
        if (j != 1) {
            __syncthreads();
            if (j == 0) {
                if (tid == 0) load_chunk(sb + C_WS, 3, bar + B_WS * 8);
            } else if (tid < 32) {
                if (lane == 0) mbar_expect(bar + B_WO * 8, ONK * 2048);
                __syncwarp();
                for (int i = lane; i < ONK; i += 32) tma2d(sb + C_WO + i * 2048, tWo, cl * 64, (ostart + i) * 16, bar + B_WO * 8);
            }
        }
    }
    asm volatile("griddepcontrol.wait;" ::: "memory");
    asm volatile("griddepcontrol.launch_dependents;" ::: "memory");
    if (lane == 0) mbar_arrive_cluster(mapa(bar + B_XE * 8, 2));

    constexpr uint32_t RED1 = ISV ? C_RED1V : C_RED1Q;
    const uint32_t mbw = sb + C_MB + wg * 8192;
    const uint32_t xn_desc = (((sb + C_XN + wg * 16384) & 0x3FFFF) >> 4) | (1u << 16);
    const uint32_t ws_desc = (((sb + C_WS + wg * 32768) & 0x3FFFF) >> 4) | (1u << 16);
    uint32_t tref = 0;

#pragma unroll 1
    for (int s = -1; s <= (ISV ? NSEG : NSEG - 1); s++) {
        asm volatile("" : "+r"(l16_));
        const uint32_t l16 = l16_;
        const int lane = l16 >> 4, t128 = w4 * 32 + lane;
        TS(0);
        if (s >= 0 && s < NSEG) {
            const char* src = reinterpret_cast<const char*>(&g_xmem[s & 3][wg * 512 + w4 * 32]) + l16;
            if (DLY2) { while (clk() - tref < DLY2) {} }
            uint4 v[4];
            uint32_t it = 0;
            while (true) {
#pragma unroll
                for (int j = 0; j < 4; j++) v[j] = ld_relaxed4(reinterpret_cast<const uint4*>(src + j * 2048));
                if (max(max(umax4(v[0]), umax4(v[1])), max(umax4(v[2]), umax4(v[3]))) != ~0u) break;
                if (++it > (1u << 22)) __trap();
            }
#pragma unroll
            for (int j = 0; j < 4; j++) sts4u(mbw + w4 * 512 + l16 + j * 2048, v[j]);
            bar_sync(1 + wg, 128);
            if (DLY1) tref = clk();
            TS(1);
        }
        if (ISV && !NOFILL && rank == 2 && warp == 4 && s < NSEG - 1) {
            if (lane == 0) {
                mbar_wait(bar + B_XE * 8, (s + 1) & 1);
                bulk_mc(sb + C_XN, g_xc + (s + 1) * 4096, 32768, bar + B_XF * 8, 0x3F);
            }
            __syncwarp();
        }
        if (s >= 0 && s < NSEG) {
            float ck[4] = {0.f, 0.f, 0.f, 0.f}, cv[4] = {0.f, 0.f, 0.f, 0.f};
            {
                uint32_t b[2][4], pf[4][4];
                ldsm4(b[0], mbw + l16);
#pragma unroll
                for (int kp = 0; kp < 16; kp++) {
                    const int grp = kp >> 2, ph = kp & 3;
                    const int nx = kp + 1, nk = ((nx & 3) < 3) ? (nx >> 2) * 3 + (nx & 3) : 12 + (nx >> 2);
                    if (nx < 16) ldsm4(b[nx & 1], mbw + l16 + nk * 512);
                    const uint32_t* bb = b[kp & 1];
                    if (ph < 2) {
                        ldsm4t(pf[ph * 2], a_adr + C_WS + (grp * 2 + ph) * 2048);
                        ldsm4t(pf[ph * 2 + 1], a_adr + C_WS + 16384 + (grp * 2 + ph) * 2048);
                    }
                    if (ph < 3) {
                        const int q = (grp * 3 + ph) * 2;
                        mma16(cv, wv[q][0], wv[q][1], wv[q][2], wv[q][3], bb[0], bb[1]);
                        mma16(ck, wk[q][0], wk[q][1], wk[q][2], wk[q][3], bb[0], bb[1]);
                        mma16(cv, wv[q + 1][0], wv[q + 1][1], wv[q + 1][2], wv[q + 1][3], bb[2], bb[3]);
                        mma16(ck, wk[q + 1][0], wk[q + 1][1], wk[q + 1][2], wk[q + 1][3], bb[2], bb[3]);
                    } else {
                        mma16(cv, pf[1][0], pf[1][1], pf[1][2], pf[1][3], bb[0], bb[1]);
                        mma16(ck, pf[0][0], pf[0][1], pf[0][2], pf[0][3], bb[0], bb[1]);
                        mma16(cv, pf[3][0], pf[3][1], pf[3][2], pf[3][3], bb[2], bb[3]);
                        mma16(ck, pf[2][0], pf[2][1], pf[2][2], pf[2][3], bb[2], bb[3]);
                    }
                }
            }
            sts4f(sb + (wg ? RED1 : C_RED0) + w4 * 512 + l16, cv[0], cv[1], cv[2], cv[3]);
            TS(2);
            if (!ISV) {
                const int mh = warp >= 3, ti = warp - 3 * mh;
                const uint32_t kl = sb + C_KX + (lane >> 3) * 512 + (lane & 7) * 16;
                const uint32_t dst = mapa(sb + C_SL + role * 1280 + warp * 512, hb + 2), db = mapa(bar + B_SC * 8, hb + 2);
                const uint32_t qa = sb + C_QM + ((lane >> 4) + ((lane >> 3) & 1) * 4) * 128 + (lane & 7) * 16;
                auto finish = [&]() {
                    bar_sync(0, 256);
                    const float4 r = lds4f(sb + (wg ? C_RED0 : RED1) + w4 * 512 + l16);
                    stsm2t(sb + C_QM + wg * 1024 + w4 * 256 + (l16 & 255), pack2(ck[0] + r.x, ck[1] + r.y), pack2(ck[2] + r.z, ck[3] + r.w));
                    bar_sync(0, 256);
                    TS(3);
                };
                if (warp < 2) {
                    uint32_t k0[2][4], k1[2][4], q0[4], q1[4];
                    ldsm4(k0[0], kl + warp * 256); ldsm4(k0[1], kl + warp * 256 + 2048);
                    ldsm4(k1[0], kl + warp * 256 + 128); ldsm4(k1[1], kl + warp * 256 + 128 + 2048);
                    finish();
                    ldsm4(q0, qa); ldsm4(q1, qa + 256);
                    float s0[4] = {0.f, 0.f, 0.f, 0.f}, s1[4] = {0.f, 0.f, 0.f, 0.f}, s2[4] = {0.f, 0.f, 0.f, 0.f}, s3[4] = {0.f, 0.f, 0.f, 0.f};
                    mma16(s0, q0[0], q0[1], q0[2], q0[3], k0[0][0], k0[0][1]);
                    mma16(s1, q0[0], q0[1], q0[2], q0[3], k0[1][0], k0[1][1]);
                    mma16(s2, q0[0], q0[1], q0[2], q0[3], k1[0][0], k1[0][1]);
                    mma16(s3, q0[0], q0[1], q0[2], q0[3], k1[1][0], k1[1][1]);
                    mma16(s0, q1[0], q1[1], q1[2], q1[3], k0[0][2], k0[0][3]);
                    mma16(s1, q1[0], q1[1], q1[2], q1[3], k0[1][2], k0[1][3]);
                    mma16(s2, q1[0], q1[1], q1[2], q1[3], k1[0][2], k1[0][3]);
                    mma16(s3, q1[0], q1[1], q1[2], q1[3], k1[1][2], k1[1][3]);
                    if (s < NSEG - 1)
                        st_async4(dst + l16, db, __float_as_uint(s0[0] + s1[2]), __float_as_uint(s0[1] + s1[3]),
                                  __float_as_uint(s2[0] + s3[2]), __float_as_uint(s2[1] + s3[3]));
                } else {
                    finish();
                    if (warp == 2) {
                        uint32_t q0[4], q1[4], m0[4], m1[4];
                        ldsm4(q0, qa); ldsm4(m0, sb + C_KM + l16); ldsm4(m1, sb + C_KM + 512 + l16); ldsm4(q1, qa + 256);
                        float s0[4] = {0.f, 0.f, 0.f, 0.f}, s1[4] = {0.f, 0.f, 0.f, 0.f};
                        mma16(s0, q0[0], q0[1], q0[2], q0[3], m0[0], m0[1]);
                        mma16(s1, q0[0], q0[1], q0[2], q0[3], m1[0], m1[1]);
                        mma16(s0, q1[0], q1[1], q1[2], q1[3], m0[2], m0[3]);
                        mma16(s1, q1[0], q1[1], q1[2], q1[3], m1[2], m1[3]);
                        if (s < NSEG - 1) st_async2(dst + (l16 >> 1), db, __float_as_uint(s0[0] + s1[2]), __float_as_uint(s0[1] + s1[3]));
                    }
                }
                TS(4);
                if (!NOFILL) {
                    const uint32_t ka = ti ? kl + (ti - 1) * 128 : sb + C_KM + l16;
                    const uint32_t qx = sb + C_QX + (lane >> 4) * 512 + mh * 256 + (l16 & 255);
                    uint32_t k[2][4], q[4][4];
                    ldsm4(k[0], ka); ldsm4(k[1], ka + (ti ? 2048 : 512));
#pragma unroll
                    for (int i = 0; i < 4; i++) ldsm4(q[i], qx + i * 1024);
                    float s0[4] = {0.f, 0.f, 0.f, 0.f};
#pragma unroll
                    for (int i = 0; i < 4; i++) mma16(s0, q[i][0], q[i][1], q[i][2], q[i][3], k[i >> 1][(i & 1) * 2], k[i >> 1][(i & 1) * 2 + 1]);
                    st_async4(mapa(sb + C_XSL + role * 2560 + ti * 512, hb + mh) + l16, mapa(bar + B_XS * 8, hb + mh),
                              __float_as_uint(s0[0]), __float_as_uint(s0[1]), __float_as_uint(s0[2]), __float_as_uint(s0[3]));
                }
            } else {
                const int rr = lane & 7;
                const uint32_t d = sb + C_V + (s & 1) * 10240 + (32 * (2 * wg + (w4 >> 1)) + 4 * (w4 & 1)) * 80 + 64 +
                                   (8 * (rr >> 1) + 2 * ((lane >> 3) & 1) + (rr & 1)) * 80;
                __syncthreads();
                const float4 r = lds4f(sb + (wg ? C_RED0 : RED1) + w4 * 512 + l16);
                stsm2(d, pack2(ck[0] + r.x, ck[1] + r.y), pack2(ck[2] + r.z, ck[3] + r.w));
                __syncthreads();
                TS(3);
            }
        }
        if (ISV) {
            const int ss = s - wg;
            if (ss >= 0 && ss < NSEG - 1 + wg && !(NOFILL && wg)) {
                uint32_t vx[4][4], vm[4];
                const uint32_t vb = sb + C_V + (ss & 1) * 10240 + w4 * 2560;
#pragma unroll
                for (int j = 0; j < 4; j++) ldsm4(vx[j], vb + j * 640 + (lane & 7) * 80 + (lane >> 3) * 16);
                ldsm4(vm, vb + lane * 80 + 64);
                if (wg == 0) {
                    const uint32_t oo = ((lane & 3) * 8 + (lane >> 2)) * 16;
                    char* dst = reinterpret_cast<char*>(&g_xo[s & 3][(16 * head + 4 * w4) * 8]) + oo;
                    char* dpz = reinterpret_cast<char*>(&g_xo[(s + 2) & 3][(16 * head + 4 * w4) * 8]) + oo;
                    st_relaxed4(reinterpret_cast<uint4*>(dpz), make_uint4(~0u, ~0u, ~0u, ~0u));
                    mbar_wait(bar + B_SC * 8, s & 1);
                    TS(4);
                    const float4 a0 = lds4f(sb + C_SL + l16), b0 = lds4f(sb + C_SL + 1280 + l16);
                    const float4 a1 = lds4f(sb + C_SL + 512 + l16), b1 = lds4f(sb + C_SL + 1280 + 512 + l16);
                    const float2 a2 = lds2f(sb + C_SL + 1024 + (l16 >> 1)), b2 = lds2f(sb + C_SL + 1280 + 1024 + (l16 >> 1));
                    const float e[10] = {a0.x + b0.x, a0.y + b0.y, a0.z + b0.z, a0.w + b0.w, a1.x + b1.x, a1.y + b1.y, a1.z + b1.z, a1.w + b1.w,
                                         a2.x + b2.x, a2.y + b2.y};
                    float m = fmaxf(fmaxf(fmaxf(e[0], e[1]), fmaxf(e[2], e[3])), fmaxf(fmaxf(e[4], e[5]), fmaxf(e[6], e[7])));
                    m = fmaxf(m, fmaxf(e[8], e[9]));
                    m = fmaxf(fmaxf(m, __shfl_xor_sync(~0u, m, 1)), fmaxf(__shfl_xor_sync(~0u, m, 2), __shfl_xor_sync(~0u, m, 3)));
                    m *= -SM_SCALE;
                    float x[10];
#pragma unroll
                    for (int i = 0; i < 10; i++) x[i] = ex2(fmaf(e[i], SM_SCALE, m));
                    float o[4][4];
                    const uint32_t p0 = pack2(x[0], x[1]), p1 = pack2(x[2], x[3]), j0 = junk(), j1 = junk();
#pragma unroll
                    for (int j = 0; j < 4; j++) { o[j][0] = o[j][1] = o[j][2] = o[j][3] = 0.f; mma16(o[j], p0, j0, p1, j1, vx[j][0], vx[j][1]); }
                    const uint32_t p2 = pack2(x[4], x[5]), p3 = pack2(x[6], x[7]), j2 = junk(), j3 = junk();
#pragma unroll
                    for (int j = 0; j < 4; j++) mma16(o[j], p2, j2, p3, j3, vx[j][2], vx[j][3]);
                    const uint32_t p4 = pack2(x[8], x[9]), j4 = junk();
                    float l = (((x[0] + x[1]) + (x[2] + x[3])) + ((x[4] + x[5]) + (x[6] + x[7]))) + (x[8] + x[9]);
                    l = (l + __shfl_xor_sync(~0u, l, 1)) + (__shfl_xor_sync(~0u, l, 2) + __shfl_xor_sync(~0u, l, 3));
#pragma unroll
                    for (int j = 0; j < 4; j++) mma8(o[j], p4, j4, vm[j]);
                    l = rcp(l);
                    st_relaxed4(reinterpret_cast<uint4*>(dst), make_uint4(pack2(o[0][0] * l, o[0][1] * l), pack2(o[1][0] * l, o[1][1] * l),
                                                                          pack2(o[2][0] * l, o[2][1] * l), pack2(o[3][0] * l, o[3][1] * l)));
                    if (t128 == 0) mbar_expect(bar + B_SC * 8, 2560);
                } else {
                    const uint32_t pb = bar + (B_P0 + (ss & 1)) * 8, pl = sb + C_PL + (ss & 1) * 2048;
                    mbar_wait(pb, (ss >> 1) & 1);
                    const uint2 pm0 = lds2u(pl + (l16 >> 1)), pm1 = lds2u(pl + 768 + (l16 >> 1));
                    const uint4 p0 = lds4u(pl + 256 + l16), p1 = lds4u(pl + 1024 + l16), p2 = lds4u(pl + 1536 + l16);
                    if (t128 == 0) mbar_expect(pb, 2048);
                    __nv_bfloat16* orow = g_ox + (size_t)(ss * 32) * HD + head * 128 + 32 * w4 + ((lane >> 2) * HD + 8 * (lane & 3));
#pragma unroll
                    for (int mh = 0; mh < 2; mh++) {
                        float o[4][4];
#pragma unroll
                        for (int j = 0; j < 4; j++) {
                            o[j][0] = o[j][1] = o[j][2] = o[j][3] = 0.f;
                            if (mh == 0) {
                                mma8(o[j], pm0.x, pm0.y, vm[j]);
                                mma16(o[j], p0.x, p0.y, p0.z, p0.w, vx[j][0], vx[j][1]);
                            } else {
                                mma8(o[j], pm1.x, pm1.y, vm[j]);
                                mma16(o[j], p1.x, p1.y, p1.z, p1.w, vx[j][0], vx[j][1]);
                                mma16(o[j], p2.x, p2.y, p2.z, p2.w, vx[j][2], vx[j][3]);
                            }
                        }
                        *reinterpret_cast<uint4*>(orow + (size_t)(16 * mh) * HD) =
                            make_uint4(pack2(o[0][0], o[0][1]), pack2(o[1][0], o[1][1]), pack2(o[2][0], o[2][1]), pack2(o[3][0], o[3][1]));
                        *reinterpret_cast<uint4*>(orow + (size_t)(16 * mh + 8) * HD) =
                            make_uint4(pack2(o[0][2], o[0][3]), pack2(o[1][2], o[1][3]), pack2(o[2][2], o[2][3]), pack2(o[3][2], o[3][3]));
                    }
                }
            }
            if (s >= NSEG - 1) continue;
            if (wg == 0) bar_arrive(3, 256); else bar_sync(3, 256);
        }
        auto token_softmax = [&]() {
                if (!NOFILL) {
                    mbar_wait(bar + B_XS * 8, s & 1);
                    const int hi = w4 - 2;
                    const uint32_t src = sb + C_XSL + l16 + hi * 8;
                    const int d0 = 16 * role + 8 * hi + (lane >> 2) - 2 * (lane & 3);
                    float e[10];
                    float m = -INFINITY;
#pragma unroll
                    for (int i = 0; i < 5; i++) {
                        if (i < 3 || role) {
                            const float2 a = lds2f(src + i * 512), b = lds2f(src + 2560 + i * 512);
                            e[2 * i] = (i > 0 && d0 < 8 * (i - 1)) ? -INFINITY : a.x + b.x;
                            e[2 * i + 1] = (i > 0 && d0 < 8 * (i - 1) + 1) ? -INFINITY : a.y + b.y;
                        } else {
                            e[2 * i] = e[2 * i + 1] = -INFINITY;
                        }
                        m = fmaxf(m, fmaxf(e[2 * i], e[2 * i + 1]));
                    }
                    m = fmaxf(m, __shfl_xor_sync(~0u, m, 1));
                    m = fmaxf(m, __shfl_xor_sync(~0u, m, 2));
                    m *= -SM_SCALE;
                    float l = 0.f;
#pragma unroll
                    for (int i = 0; i < 10; i++) { e[i] = ex2(fmaf(e[i], SM_SCALE, m)); l += e[i]; }
                    l += __shfl_xor_sync(~0u, l, 1);
                    l += __shfl_xor_sync(~0u, l, 2);
                    l = rcp(l);
                    const uint32_t dst = mapa(sb + C_PL + (s & 1) * 2048 + role * 768 + hi * 4, hb + 2), db = mapa(bar + (B_P0 + (s & 1)) * 8, hb + 2);
                    st_async1(dst + (l16 >> 1), db, pack2(e[0] * l, e[1] * l));
                    st_async1(dst + 256 + l16, db, pack2(e[2] * l, e[3] * l));
                    st_async1(dst + 264 + l16, db, pack2(e[4] * l, e[5] * l));
                    if (role) {
                        st_async1(dst + 768 + l16, db, pack2(e[6] * l, e[7] * l));
                        st_async1(dst + 776 + l16, db, pack2(e[8] * l, e[9] * l));
                    }
                    if (w4 == 2 && lane == 0) mbar_expect(bar + B_XS * 8, role ? 5120 : 3072);
                }
        };
        if (!ISV && s == NSEG - 1) {
            if (warp >= 6) token_softmax();
            break;
        }
        TS(5);
        float xk[16], xv[16];
        {
            if (!NOFILL) {
                mbar_wait(bar + B_XF * 8, 0);
                if (warp == 0 && lane == 0) mbar_expect(bar + B_XF * 8, 32768);
                TS(6);
                wg_fence();
                wg32_rs<0>(xk, wk[0], xn_desc);
                wg32_rs<0>(xv, wv[0], xn_desc);
#pragma unroll
                for (int i = 1; i < 16; i++) {
                    wg32_rs<1>(xk, wk[i], xn_desc + (i >> 2) * 256 + (i & 3) * 2);
                    wg32_rs<1>(xv, wv[i], xn_desc + (i >> 2) * 256 + (i & 3) * 2);
                }
                wg_commit();
                wg_wait<0>();
                reg_fence<16>(xk); reg_fence<16>(xv);
                if (lane == 0) mbar_arrive_cluster(mapa(bar + B_XE * 8, 5));
            }
            TS(7);
            if (s >= 0) {
                const char* src = reinterpret_cast<const char*>(&g_xo[s & 3][ostart * 16 + warp * 32]) + l16;
                const uint32_t o2 = (warp * 32 + lane + 512 < ONK * 16) ? 8192 : 0;
                if (DLY1) { while (clk() - tref < DLY1) {} }
                uint4 v[3];
                uint32_t it = 0;
                while (true) {
                    v[0] = ld_relaxed4(reinterpret_cast<const uint4*>(src)); v[1] = ld_relaxed4(reinterpret_cast<const uint4*>(src + 4096));
                    v[2] = ld_relaxed4(reinterpret_cast<const uint4*>(src + o2));
                    if (max(max(umax4(v[0]), umax4(v[1])), umax4(v[2])) != ~0u) break;
                    if (++it > (1u << 22)) __trap();
                }
#pragma unroll
                for (int j = 0; j < 3; j++) sts4u(sb + C_MB + warp * 512 + l16 + j * 4096, v[j]);
                fence_async();
                if (wg == 0) {
                    const int owner = w4 + (w4 >> 1);
                    const uint32_t dst = mapa(sb + C_OL + rank * 512, owner) + l16, db = mapa(bar + B_OL * 8, owner);
                    bar_sync(4, 256);
                    if (DLY2) tref = clk();
                    TS(8);
                    float co[4];
                    wg8_chain<ONK>(co, (((sb + C_WO) & 0x3FFFF) >> 4) | (1u << 16), (((sb + C_MB) & 0x3FFFF) >> 4) | (8u << 16));
                    st_async4(dst, db, __float_as_uint(co[0]), __float_as_uint(co[1]), __float_as_uint(co[2]), __float_as_uint(co[3]));
                    bar_arrive(5, 256);
                    TS(9);
                } else {
                    bar_arrive(4, 256);
                    if (DLY2) tref = clk();
                }
            } else {
                mbar_wait(bar + B_WS * 8, 0);
                mbar_wait(bar + B_WO * 8, 0);
            }
            if (ISV && !NOFILL && rank == 5 && warp == 4) {
                if (lane == 0) {
                    mbar_wait(bar + B_XE * 8, (s + 1) & 1);
                    bulk_mc(sb + C_XN, g_xc + (s + 1) * 4096 + 2048, 32768, bar + B_XF * 8, 0x3F);
                }
                __syncwarp();
            }
        }
        if (!ISV && wg == 1 && s >= 0) {
            if (w4 >= 2) {
                token_softmax();
            } else if (w4 == 0) {
                const int slice = cl * 4 + (rank >= 3 ? rank - 1 : rank);
                char* dst = reinterpret_cast<char*>(&g_xmem[(s + 1) & 3][slice * 16]) + (l16 >> 2);
                char* pz = reinterpret_cast<char*>(&g_xmem[(s + 3) & 3][slice * 16]) + (l16 >> 2);
                st_relaxed1(pz, ~0u);
                st_relaxed1(pz + 128, ~0u);
                mbar_wait(bar + B_OL * 8, s & 1);
                TS(10);
                float4 a = lds4f(sb + C_OL + l16), b = lds4f(sb + C_OL + 512 + l16), c = lds4f(sb + C_OL + 1024 + l16);
                {
                    const float4 d = lds4f(sb + C_OL + 1536 + l16), e = lds4f(sb + C_OL + 2048 + l16), f = lds4f(sb + C_OL + 2560 + l16);
                    a.x = (a.x + b.x) + (c.x + d.x) + (e.x + f.x); a.y = (a.y + b.y) + (c.y + d.y) + (e.y + f.y);
                    a.z = (a.z + b.z) + (c.z + d.z) + (e.z + f.z); a.w = (a.w + b.w) + (c.w + d.w) + (e.w + f.w);
                }
                const uint32_t r0 = movm(pack2(a.x, a.y)), r1 = movm(pack2(a.z, a.w));
                st_relaxed1(dst, r0);
                st_relaxed1(dst + 128, r1);
                if (lane == 0) mbar_expect(bar + B_OL * 8, 3072);
            }
        }
        if (wg == 1 && s >= 0) bar_sync(5, 256);
        TS(11);
        if (NOFILL) continue;
        mbar_wait(bar + B_XF * 8, 1);
        if (warp == 0 && lane == 0) mbar_expect(bar + B_XF * 8, 32768);
        TS(12);
        wg_fence();
#pragma unroll
        for (int i = 0; i < 8; i++) {
            wg32_rs<1>(xv, wv[16 + i], xn_desc + (i >> 2) * 256 + (i & 3) * 2);
            wg32_rs<1>(xk, wk[16 + i], xn_desc + (i >> 2) * 256 + (i & 3) * 2);
        }
#pragma unroll
        for (int i = 0; i < 8; i++) {
            wg32_ss(xv, ws_desc + 1024 + i * 128, xn_desc + (2 + (i >> 2)) * 256 + (i & 3) * 2);
            wg32_ss(xk, ws_desc + i * 128, xn_desc + (2 + (i >> 2)) * 256 + (i & 3) * 2);
        }
        wg_commit();
        wg_wait<0>();
        reg_fence<16>(xk); reg_fence<16>(xv);
        if (lane == 0) mbar_arrive_cluster(mapa(bar + B_XE * 8, 2));
        TS(13);
        {
#pragma unroll
            for (int j = 0; j < 4; j++) sts4f(sb + C_MB + (wg ^ 1) * 8192 + w4 * 512 + l16 + j * 2048, xv[4 * j], xv[4 * j + 1], xv[4 * j + 2], xv[4 * j + 3]);
            __syncthreads();
            uint32_t lo[4], hi[4];
#pragma unroll
            for (int j = 0; j < 4; j++) {
                const float4 r = lds4f(mbw + w4 * 512 + l16 + j * 2048);
                lo[j] = pack2(xk[4 * j] + r.x, xk[4 * j + 1] + r.y);
                hi[j] = pack2(xk[4 * j + 2] + r.z, xk[4 * j + 3] + r.w);
            }
            if (!ISV) {
                const uint32_t d = sb + C_QX + wg * 4096 + w4 * 1024 + l16;
                stsm4t(d, lo[0], lo[1], lo[2], lo[3]);
                stsm4t(d + 512, hi[0], hi[1], hi[2], hi[3]);
            } else {
                const int rr = lane & 7;
                const uint32_t d = sb + C_V + ((s + 1) & 1) * 10240 + (32 * (2 * wg + (w4 >> 1)) + 4 * (w4 & 1)) * 80 +
                                   (8 * (rr >> 1) + (rr & 1)) * 80 + (lane >> 3) * 16;
                stsm4(d, lo[0], lo[1], lo[2], lo[3]);
                stsm4(d + 160, hi[0], hi[1], hi[2], hi[3]);
            }
        }
    }
}

__global__ void __cluster_dims__(6, 1, 1) __launch_bounds__(256, 1)
chain_kernel(const __grid_constant__ CUtensorMap tq, const __grid_constant__ CUtensorMap tk, const __grid_constant__ CUtensorMap tv,
             const __grid_constant__ CUtensorMap two) {
    extern __shared__ __align__(1024) uint8_t smem[];
    const uint32_t sb = smem_u32(smem);
    const int rank = blockIdx.x % 6, cl = blockIdx.x / 6, role = rank % 3;
    if (threadIdx.x == 0) {
        if (sb & 1023) __trap();
        const uint32_t bar = sb + C_BAR;
        for (int i = 0; i < B_NUM; i++) mbar_init(bar + i * 8, i == B_XE ? 48 : 1);
        mbar_expect(bar + B_XF * 8, 32768);
        if (role == 2) {
            mbar_expect(bar + B_SC * 8, 2560);
            mbar_expect(bar + B_P0 * 8, 2048);
            mbar_expect(bar + B_P1 * 8, 2048);
        } else {
            mbar_expect(bar + B_XS * 8, role ? 5120 : 3072);
            mbar_expect(bar + B_OL * 8, 3072);
        }
        asm volatile("fence.mbarrier_init.release.cluster;" ::: "memory");
        fence_async();
    }
    __syncthreads();
    cluster_sync();
    if (role == 2) chain_body<true>(&tv, &tv, &two, sb, cl, rank);
    else chain_body<false>(&tq, &tk, &two, sb, cl, rank);
    __syncthreads();
    cluster_sync();
}

constexpr int G_STAGES = 4;
constexpr uint32_t G_STAGE = 49152, G_EPI = G_STAGES * G_STAGE, G_BAR = G_EPI + 32768, G_SMEM = G_BAR + 256;

__device__ __forceinline__ void wg256(float* d, uint32_t da, uint32_t db, uint32_t accum) {
    asm volatile("{\n.reg .b64 da, db;\n.reg .pred p;\nsetp.ne.u32 p, %130, 0;\nmov.b64 da, {%128, " DESC_HI_SW128 "};\nmov.b64 db, {%129, " DESC_HI_SW128 "};\n"
                 "wgmma.mma_async.sync.aligned.m64n256k16.f32.bf16.bf16 {"
                 "%0,%1,%2,%3,%4,%5,%6,%7,%8,%9,%10,%11,%12,%13,%14,%15,%16,%17,%18,%19,%20,%21,%22,%23,%24,%25,%26,%27,%28,%29,%30,%31,"
                 "%32,%33,%34,%35,%36,%37,%38,%39,%40,%41,%42,%43,%44,%45,%46,%47,%48,%49,%50,%51,%52,%53,%54,%55,%56,%57,%58,%59,%60,%61,%62,%63,"
                 "%64,%65,%66,%67,%68,%69,%70,%71,%72,%73,%74,%75,%76,%77,%78,%79,%80,%81,%82,%83,%84,%85,%86,%87,%88,%89,%90,%91,%92,%93,%94,%95,"
                 "%96,%97,%98,%99,%100,%101,%102,%103,%104,%105,%106,%107,%108,%109,%110,%111,%112,%113,%114,%115,%116,%117,%118,%119,%120,%121,%122,%123,%124,%125,%126,%127"
                 "}, da, db, p, 1, 1, 0, 1;\n}"
                 : ACC16(d), ACC16((d + 16)), ACC16((d + 32)), ACC16((d + 48)), ACC16((d + 64)), ACC16((d + 80)), ACC16((d + 96)), ACC16((d + 112))
                 : "r"(da), "r"(db), "r"(accum));
}
__device__ __forceinline__ float sigmoidf_(float v) { return rcp(1.f + ex2(-1.4426950408889634f * v)); }

template <int MODE>
__global__ void __cluster_dims__(2, 1, 1) __launch_bounds__(384, 1)
gemm_kernel(const __grid_constant__ CUtensorMap tA, const __grid_constant__ CUtensorMap tB0, const __grid_constant__ CUtensorMap tB1,
            const __grid_constant__ CUtensorMap tOut, const __grid_constant__ CUtensorMap tX, const __grid_constant__ CUtensorMap tY) {
    constexpr int KB = MODE == 0 ? DM / 64 : (MODE == 1 ? FF / 64 : HD / 64);
    constexpr int NT = MODE == 0 ? FF / 128 : DM / 256;
    constexpr int NTILES = NT * 8;
    extern __shared__ __align__(1024) uint8_t smem[];
    const uint32_t sb = smem_u32(smem);
    const uint32_t full = sb + G_BAR, empty = full + 64;
    const int tid = threadIdx.x, lane = tid & 31;
    const int wg = __shfl_sync(~0u, tid >> 7, 0);
    const int rank = blockIdx.x & 1, pair = blockIdx.x >> 1, npair = gridDim.x >> 1;
    if (tid == 0) {
        if (sb & 1023) __trap();
        for (int i = 0; i < G_STAGES; i++) { mbar_init(full + i * 8, 1); mbar_init(empty + i * 8, 16); }
        asm volatile("fence.mbarrier_init.release.cluster;" ::: "memory");
        fence_async();
    }
    __syncthreads();
    cluster_sync();
    if (wg == 0) {
        asm volatile("setmaxnreg.dec.sync.aligned.u32 40;");
        if (tid == 0) {
            uint32_t st = 0, ph = 1;
            for (int tile = pair; tile < NTILES; tile += npair) {
                const int mp = tile & 7, nt = tile >> 3, row0 = (mp * 2 + rank) * 128;
                const CUtensorMap* tB = (MODE == 0 && rank) ? &tB1 : &tB0;
                const int bcol = MODE == 0 ? nt * 128 : nt * 256 + rank * 128;
                for (int kb = 0; kb < KB; kb++) {
                    mbar_wait(empty + st * 8, ph);
                    const uint32_t base = sb + st * G_STAGE;
                    mbar_expect(full + st * 8, G_STAGE);
                    tma2d(base, &tA, kb * 64, row0, full + st * 8);
                    tma2d_mc(base + 16384 + rank * 16384, tB, bcol, kb * 64, full + st * 8, 3);
                    tma2d_mc(base + 16384 + rank * 16384 + 8192, tB, bcol + 64, kb * 64, full + st * 8, 3);
                    if (++st == G_STAGES) { st = 0; ph ^= 1; }
                }
                if (MODE == 2) {
                    for (int q = 0; q < 4; q++) {
                        mbar_wait(empty + st * 8, ph);
                        const uint32_t base = sb + st * G_STAGE;
                        mbar_expect(full + st * 8, 32768);
                        tma2d(base, &tX, nt * 256 + q * 64, row0, full + st * 8);
                        tma2d(base + 16384, &tY, nt * 256 + q * 64, row0, full + st * 8);
                        if (++st == G_STAGES) { st = 0; ph ^= 1; }
                    }
                }
            }
        }
        __syncwarp();
        cluster_sync();
    } else {
        asm volatile("setmaxnreg.inc.sync.aligned.u32 232;");
        const int cw = wg - 1, w4 = (tid >> 5) & 3;
        const uint32_t empty_dst = mapa(empty, lane & 1);
        const uint32_t epi = sb + G_EPI + cw * 16384;
        const int er = w4 * 16 + (lane & 15), ec = lane >> 4;
        uint32_t st = 0, ph = 0;
        float acc[128];
        for (int tile = pair; tile < NTILES; tile += npair) {
            const int mp = tile & 7, nt = tile >> 3, row0 = (mp * 2 + rank) * 128 + cw * 64;
            uint32_t prev = 0;
#pragma unroll 1
            for (int kb = 0; kb < KB; kb++) {
                mbar_wait(full + st * 8, ph);
                const uint32_t base = sb + st * G_STAGE;
                const uint32_t da = (((base + cw * 8192) & 0x3FFFF) >> 4) | (1u << 16);
                const uint32_t db = (((base + 16384) & 0x3FFFF) >> 4) | (512u << 16);
                wg_fence();
#pragma unroll
                for (int k = 0; k < 4; k++) wg256(acc, da + k * 2, db + k * 128, (kb | k) != 0);
                wg_commit();
                if (kb > 0) {
                    wg_wait<1>();
                    if (lane < 2) mbar_arrive_cluster(empty_dst + prev * 8);
                }
                prev = st;
                if (++st == G_STAGES) { st = 0; ph ^= 1; }
            }
            wg_wait<0>();
            reg_fence<128>(acc);
            if (lane < 2) mbar_arrive_cluster(empty_dst + prev * 8);
#pragma unroll
            for (int hp = 0; hp < (MODE == 0 ? 1 : 2); hp++) {
                uint32_t o[32];
#pragma unroll
                for (int bx = 0; bx < 2; bx++) {
                    uint32_t xa = 0;
                    if (MODE == 2) {
                        mbar_wait(full + st * 8, ph);
                        xa = sb + st * G_STAGE + (cw * 64 + er) * 128;
                    }
#pragma unroll
                    for (int j = 0; j < 4; j++) {
                        const int a0 = hp * 64 + bx * 32 + j * 8;
                        uint32_t* oo = o + bx * 16 + j * 4;
                        if (MODE == 0) {
#pragma unroll
                            for (int i = 0; i < 4; i++)
                                oo[i] = pack2(sigmoidf_(acc[a0 + 2 * i]) * acc[64 + a0 + 2 * i], sigmoidf_(acc[a0 + 2 * i + 1]) * acc[64 + a0 + 2 * i + 1]);
                        } else if (MODE == 1) {
#pragma unroll
                            for (int i = 0; i < 4; i++)
                                oo[i] = pack2(sigmoidf_(acc[a0 + 2 * i]) * acc[a0 + 2 * i], sigmoidf_(acc[a0 + 2 * i + 1]) * acc[a0 + 2 * i + 1]);
                        } else {
                            uint32_t xv[4], yv[4];
                            const uint32_t ad = xa + (((2 * j + ec) ^ (er & 7)) << 4);
                            ldsm4(xv, ad); ldsm4(yv, ad + 16384);
#pragma unroll
                            for (int i = 0; i < 4; i++)
                                oo[i] = pack2(fmaf(acc[a0 + 2 * i], bf_lo(yv[i]), bf_lo(xv[i])), fmaf(acc[a0 + 2 * i + 1], bf_hi(yv[i]), bf_hi(xv[i])));
                        }
                    }
                    if (MODE == 2) {
                        __syncwarp();
                        if (lane < 2) mbar_arrive_cluster(empty_dst + st * 8);
                        if (++st == G_STAGES) { st = 0; ph ^= 1; }
                    }
                }
                if ((tid & 127) == 0) asm volatile("cp.async.bulk.wait_group.read 0;" ::: "memory");
                bar_sync(1 + cw, 128);
#pragma unroll
                for (int bx = 0; bx < 2; bx++)
#pragma unroll
                    for (int j = 0; j < 4; j++) {
                        const uint32_t* oo = o + bx * 16 + j * 4;
                        stsm4(epi + bx * 8192 + er * 128 + (((2 * j + ec) ^ (er & 7)) << 4), oo[0], oo[1], oo[2], oo[3]);
                    }
                fence_async();
                bar_sync(1 + cw, 128);
                if ((tid & 127) == 0) {
                    const int col = MODE == 0 ? nt * 128 : nt * 256 + hp * 128;
                    tma2d_store(&tOut, col, row0, epi);
                    tma2d_store(&tOut, col + 64, row0, epi + 8192);
                    asm volatile("cp.async.bulk.commit_group;" ::: "memory");
                }
            }
        }
        if ((tid & 127) == 0) asm volatile("cp.async.bulk.wait_group 0;" ::: "memory");
        __syncwarp();
        cluster_sync();
    }
}

typedef CUresult (*EncodeFn)(CUtensorMap*, CUtensorMapDataType, cuuint32_t, void*, const cuuint64_t*, const cuuint64_t*, const cuuint32_t*,
                             const cuuint32_t*, CUtensorMapInterleave, CUtensorMapSwizzle, CUtensorMapL2promotion, CUtensorMapFloatOOBfill);

CUtensorMap make_map(EncodeFn enc, const void* p, int rows, int cols, int box_rows) {
    CUtensorMap m;
    cuuint64_t dims[2] = {(cuuint64_t)cols, (cuuint64_t)rows}, strides[1] = {(cuuint64_t)cols * 2};
    cuuint32_t box[2] = {64, (cuuint32_t)box_rows}, es[2] = {1, 1};
    enc(&m, CU_TENSOR_MAP_DATA_TYPE_BFLOAT16, 2, const_cast<void*>(p), dims, strides, box, es, CU_TENSOR_MAP_INTERLEAVE_NONE,
        CU_TENSOR_MAP_SWIZZLE_128B, CU_TENSOR_MAP_L2_PROMOTION_L2_128B, CU_TENSOR_MAP_FLOAT_OOB_FILL_NONE);
    return m;
}

}

extern "C" void kernel_launch(void* const* d_in, const int* in_sizes, int n_in, void* d_out, int out_size) {
    const __nv_bfloat16* x = (const __nv_bfloat16*)d_in[0];
    const __nv_bfloat16* mem0 = (const __nv_bfloat16*)d_in[1];
    void* fn = nullptr;
    cudaDriverEntryPointQueryResult qr;
    cudaGetDriverEntryPoint("cuTensorMapEncodeTiled", &fn, cudaEnableDefault, &qr);
    EncodeFn enc = (EncodeFn)fn;
    void *xn, *ox, *h, *y;
    cudaGetSymbolAddress(&xn, g_xn); cudaGetSymbolAddress(&ox, g_ox); cudaGetSymbolAddress(&h, g_h); cudaGetSymbolAddress(&y, g_y);

    const CUtensorMap tq = make_map(enc, d_in[2], DM, HD, 128), tk = make_map(enc, d_in[3], DM, HD, 128), tv = make_map(enc, d_in[4], DM, HD, 128);
    const CUtensorMap two16 = make_map(enc, d_in[5], HD, DM, 16);
    const CUtensorMap txn128 = make_map(enc, xn, SEQ, DM, 128), tg = make_map(enc, d_in[8], DM, FF, 64), tu = make_map(enc, d_in[9], DM, FF, 64);
    const CUtensorMap th64 = make_map(enc, h, SEQ, FF, 64), th128 = make_map(enc, h, SEQ, FF, 128), td = make_map(enc, d_in[10], FF, DM, 64);
    const CUtensorMap ty64 = make_map(enc, y, SEQ, DM, 64), ty128 = make_map(enc, y, SEQ, DM, 128), tx128 = make_map(enc, x, SEQ, DM, 128);
    const CUtensorMap tox = make_map(enc, ox, SEQ, HD, 128), two64 = make_map(enc, d_in[5], HD, DM, 64), tout = make_map(enc, d_out, SEQ, DM, 64);

    cudaFuncSetAttribute(chain_kernel, cudaFuncAttributeMaxDynamicSharedMemorySize, C_SMEM);
    cudaFuncSetAttribute(gemm_kernel<0>, cudaFuncAttributeMaxDynamicSharedMemorySize, G_SMEM);
    cudaFuncSetAttribute(gemm_kernel<1>, cudaFuncAttributeMaxDynamicSharedMemorySize, G_SMEM);
    cudaFuncSetAttribute(gemm_kernel<2>, cudaFuncAttributeMaxDynamicSharedMemorySize, G_SMEM);

    cudaStream_t st = cudaStreamPerThread;
    ln_kernel<<<SEQ / 8, 256, 0, st>>>(x, mem0);
    chain_kernel<<<96, 256, C_SMEM, st>>>(tq, tk, tv, two16);
    gemm_kernel<0><<<132, 384, G_SMEM, st>>>(txn128, tg, tu, th64, th64, th64);
    gemm_kernel<1><<<64, 384, G_SMEM, st>>>(th128, td, td, ty64, ty64, ty64);
    gemm_kernel<2><<<64, 384, G_SMEM, st>>>(tox, two64, two64, tout, tx128, ty128);
}
```

```cpp
#include <cuda_runtime.h>
#include <cuda_bf16.h>
#include <cuda.h>
#include <stdint.h>

namespace {

constexpr int SEQ = 2048, DM = 1024, HD = 4096, FF = 3584, NSEG = 64;

__device__ __align__(1024) __nv_bfloat16 g_xn[SEQ * DM];
__device__ __align__(1024) uint4 g_xc[SEQ * DM / 8];
__device__ __align__(1024) __nv_bfloat16 g_ox[SEQ * HD];
__device__ __align__(1024) __nv_bfloat16 g_h[SEQ * FF];
__device__ __align__(1024) __nv_bfloat16 g_y[SEQ * DM];
__device__ __align__(1024) uint4 g_xmem[4][1024];
__device__ __align__(1024) uint4 g_xo[4][4096];
#define FSTR 8
__device__ __align__(1024) uint32_t g_flag[2][96 * FSTR];

__device__ __forceinline__ uint32_t smem_u32(const void* p) { return (uint32_t)__cvta_generic_to_shared(p); }
__device__ __forceinline__ uint32_t mapa(uint32_t a, uint32_t r) {
    uint32_t o; asm("mapa.shared::cluster.u32 %0, %1, %2;" : "=r"(o) : "r"(a), "r"(r)); return o;
}
__device__ __forceinline__ void mbar_init(uint32_t a, uint32_t cnt) {
    asm volatile("mbarrier.init.shared.b64 [%0], %1;" :: "r"(a), "r"(cnt) : "memory");
}
__device__ __forceinline__ void mbar_expect(uint32_t a, uint32_t bytes) {
    asm volatile("mbarrier.arrive.expect_tx.shared.b64 _, [%0], %1;" :: "r"(a), "r"(bytes) : "memory");
}
__device__ __forceinline__ void mbar_arrive_cluster(uint32_t a) {
    asm volatile("mbarrier.arrive.shared::cluster.b64 _, [%0];" :: "r"(a) : "memory");
}
__device__ __forceinline__ void spin_guard(uint32_t& it) {
    asm volatile("{\n.reg .pred p;\nadd.u32 %0, %0, 1;\nsetp.gt.u32 p, %0, 0x400000;\n@p st.shared.u32 [%0], %0;\n}" : "+r"(it));
}
__device__ __forceinline__ void mbar_wait(uint32_t a, uint32_t par) {
    asm volatile("{\n.reg .pred p;\n.reg .u32 i;\nmov.u32 i, 0;\n"
                 "WL:\nmbarrier.try_wait.parity.shared::cta.b64 p, [%0], %1;\n@p bra WD;\n"
                 "add.u32 i, i, 1;\nsetp.gt.u32 p, i, 0x400000;\n@p st.shared.u32 [i], i;\nbra WL;\nWD:\n}" :: "r"(a), "r"(par) : "memory");
}
__device__ __forceinline__ void mbar_arrive(uint32_t a) { asm volatile("mbarrier.arrive.shared.b64 _, [%0];" :: "r"(a) : "memory"); }
__device__ __forceinline__ void tma2d(uint32_t dst, const CUtensorMap* m, int c0, int c1, uint32_t bar) {
    asm volatile("cp.async.bulk.tensor.2d.shared::cluster.global.mbarrier::complete_tx::bytes [%0], [%1, {%3, %4}], [%2];"
                 :: "r"(dst), "l"(m), "r"(bar), "r"(c0), "r"(c1) : "memory");
}
__device__ __forceinline__ void tma2d_mc(uint32_t dst, const CUtensorMap* m, int c0, int c1, uint32_t bar, uint16_t mask) {
    asm volatile("cp.async.bulk.tensor.2d.shared::cluster.global.mbarrier::complete_tx::bytes.multicast::cluster [%0], [%1, {%3, %4}], [%2], %5;"
                 :: "r"(dst), "l"(m), "r"(bar), "r"(c0), "r"(c1), "h"(mask) : "memory");
}
__device__ __forceinline__ void bulk_mc(uint32_t dst, const void* src, uint32_t bytes, uint32_t bar, uint16_t mask) {
    asm volatile("cp.async.bulk.shared::cluster.global.mbarrier::complete_tx::bytes.multicast::cluster [%0], [%1], %2, [%3], %4;"
                 :: "r"(dst), "l"(src), "r"(bytes), "r"(bar), "h"(mask) : "memory");
}
__device__ __forceinline__ void bulk_ld(uint32_t dst, const void* src, uint32_t bytes, uint32_t bar) {
    asm volatile("cp.async.bulk.shared::cluster.global.mbarrier::complete_tx::bytes [%0], [%1], %2, [%3];"
                 :: "r"(dst), "l"(src), "r"(bytes), "r"(bar) : "memory");
}
__device__ __forceinline__ uint32_t gtick() { uint32_t c; asm volatile("mov.u32 %0, %%globaltimer_lo;" : "=r"(c)); return c >> 5; }
__device__ __forceinline__ uint32_t gtick_dep(uint32_t zero) {
    uint32_t c;
    asm volatile("{\n.reg .pred p;\nsetp.eq.u32 p, %1, 0;\nmov.u32 %0, 0;\n@p mov.u32 %0, %%globaltimer_lo;\n}" : "=r"(c) : "r"(zero));
    return c >> 5;
}
__device__ __forceinline__ uint32_t ld_relaxed1(const void* p) {
    uint32_t v; asm volatile("ld.relaxed.gpu.global.u32 %0, [%1];" : "=r"(v) : "l"(p) : "memory"); return v;
}
__device__ __forceinline__ bool any_nan(float a, float b) {
    uint32_t r;
    asm volatile("{\n.reg .pred p;\nsetp.nan.f32 p, %1, %2;\nvote.sync.any.pred p, p, 0xffffffff;\nselp.u32 %0, 1, 0, p;\n}" : "=r"(r) : "f"(a), "f"(b));
    return r;
}
__device__ __forceinline__ void bar_arrive(int id, int n) { asm volatile("bar.arrive %0, %1;" :: "r"(id), "r"(n) : "memory"); }
__device__ __forceinline__ uint32_t clk() { uint32_t c; asm volatile("mov.u32 %0, %%clock;" : "=r"(c)); return c; }
__device__ __forceinline__ void tma2d_store(const CUtensorMap* m, int c0, int c1, uint32_t src) {
    asm volatile("cp.async.bulk.tensor.2d.global.shared::cta.bulk_group [%0, {%1, %2}], [%3];"
                 :: "l"(m), "r"(c0), "r"(c1), "r"(src) : "memory");
}
__device__ __forceinline__ void bar_sync(int id, int n) { asm volatile("bar.sync %0, %1;" :: "r"(id), "r"(n) : "memory"); }
__device__ __forceinline__ void fence_async() { asm volatile("fence.proxy.async.shared::cta;" ::: "memory"); }
__device__ __forceinline__ void cluster_sync() {
    asm volatile("barrier.cluster.arrive.release.aligned;\nbarrier.cluster.wait.acquire.aligned;" ::: "memory");
}
__device__ __forceinline__ void ldsm4(uint32_t* r, uint32_t a) {
    asm volatile("ldmatrix.sync.aligned.m8n8.x4.shared.b16 {%0,%1,%2,%3}, [%4];"
                 : "=r"(r[0]), "=r"(r[1]), "=r"(r[2]), "=r"(r[3]) : "r"(a) : "memory");
}
__device__ __forceinline__ void ldsm4t(uint32_t* r, uint32_t a) {
    asm volatile("ldmatrix.sync.aligned.m8n8.x4.trans.shared.b16 {%0,%1,%2,%3}, [%4];"
                 : "=r"(r[0]), "=r"(r[1]), "=r"(r[2]), "=r"(r[3]) : "r"(a) : "memory");
}
__device__ __forceinline__ void stsm4(uint32_t a, uint32_t r0, uint32_t r1, uint32_t r2, uint32_t r3) {
    asm volatile("stmatrix.sync.aligned.m8n8.x4.shared.b16 [%0], {%1,%2,%3,%4};" :: "r"(a), "r"(r0), "r"(r1), "r"(r2), "r"(r3) : "memory");
}
__device__ __forceinline__ void stsm4t(uint32_t a, uint32_t r0, uint32_t r1, uint32_t r2, uint32_t r3) {
    asm volatile("stmatrix.sync.aligned.m8n8.x4.trans.shared.b16 [%0], {%1,%2,%3,%4};" :: "r"(a), "r"(r0), "r"(r1), "r"(r2), "r"(r3) : "memory");
}
__device__ __forceinline__ void stsm2(uint32_t a, uint32_t r0, uint32_t r1) {
    asm volatile("stmatrix.sync.aligned.m8n8.x2.shared.b16 [%0], {%1,%2};" :: "r"(a), "r"(r0), "r"(r1) : "memory");
}
__device__ __forceinline__ void stsm2t(uint32_t a, uint32_t r0, uint32_t r1) {
    asm volatile("stmatrix.sync.aligned.m8n8.x2.trans.shared.b16 [%0], {%1,%2};" :: "r"(a), "r"(r0), "r"(r1) : "memory");
}
__device__ __forceinline__ uint32_t movm(uint32_t a) {
    uint32_t d; asm volatile("movmatrix.sync.aligned.m8n8.trans.b16 %0, %1;" : "=r"(d) : "r"(a)); return d;
}
__device__ __forceinline__ void mma16(float* d, uint32_t a0, uint32_t a1, uint32_t a2, uint32_t a3, uint32_t b0, uint32_t b1) {
    asm volatile("mma.sync.aligned.m16n8k16.row.col.f32.bf16.bf16.f32 {%0,%1,%2,%3}, {%4,%5,%6,%7}, {%8,%9}, {%0,%1,%2,%3};"
                 : "+f"(d[0]), "+f"(d[1]), "+f"(d[2]), "+f"(d[3]) : "r"(a0), "r"(a1), "r"(a2), "r"(a3), "r"(b0), "r"(b1));
}
__device__ __forceinline__ void mma8(float* d, uint32_t a0, uint32_t a1, uint32_t b0) {
    asm volatile("mma.sync.aligned.m16n8k8.row.col.f32.bf16.bf16.f32 {%0,%1,%2,%3}, {%4,%5}, {%6}, {%0,%1,%2,%3};"
                 : "+f"(d[0]), "+f"(d[1]), "+f"(d[2]), "+f"(d[3]) : "r"(a0), "r"(a1), "r"(b0));
}
__device__ __forceinline__ uint32_t pack2(float lo, float hi) {
    uint32_t r; asm("cvt.rn.bf16x2.f32 %0, %1, %2;" : "=r"(r) : "f"(hi), "f"(lo)); return r;
}
__device__ __forceinline__ float bf_lo(uint32_t v) { return __uint_as_float(v << 16); }
__device__ __forceinline__ float bf_hi(uint32_t v) { return __uint_as_float(v & 0xFFFF0000u); }
__device__ __forceinline__ float ex2(float x) { float y; asm("ex2.approx.ftz.f32 %0, %1;" : "=f"(y) : "f"(x)); return y; }
__device__ __forceinline__ float rcp(float x) { float y; asm("rcp.approx.ftz.f32 %0, %1;" : "=f"(y) : "f"(x)); return y; }
__device__ __forceinline__ void sts4f(uint32_t a, float x, float y, float z, float w) {
    asm volatile("st.shared.v4.f32 [%0], {%1,%2,%3,%4};" :: "r"(a), "f"(x), "f"(y), "f"(z), "f"(w) : "memory");
}
__device__ __forceinline__ void sts4u(uint32_t a, uint4 v) {
    asm volatile("st.shared.v4.u32 [%0], {%1,%2,%3,%4};" :: "r"(a), "r"(v.x), "r"(v.y), "r"(v.z), "r"(v.w) : "memory");
}
__device__ __forceinline__ float4 lds4f(uint32_t a) {
    float4 v; asm volatile("ld.shared.v4.f32 {%0,%1,%2,%3}, [%4];" : "=f"(v.x), "=f"(v.y), "=f"(v.z), "=f"(v.w) : "r"(a) : "memory"); return v;
}
__device__ __forceinline__ float2 lds2f(uint32_t a) {
    float2 v; asm volatile("ld.shared.v2.f32 {%0,%1}, [%2];" : "=f"(v.x), "=f"(v.y) : "r"(a) : "memory"); return v;
}
__device__ __forceinline__ uint4 lds4u(uint32_t a) {
    uint4 v; asm volatile("ld.shared.v4.u32 {%0,%1,%2,%3}, [%4];" : "=r"(v.x), "=r"(v.y), "=r"(v.z), "=r"(v.w) : "r"(a) : "memory"); return v;
}
__device__ __forceinline__ uint2 lds2u(uint32_t a) {
    uint2 v; asm volatile("ld.shared.v2.u32 {%0,%1}, [%2];" : "=r"(v.x), "=r"(v.y) : "r"(a) : "memory"); return v;
}
__device__ __forceinline__ void st_async4(uint32_t a, uint32_t bar, uint32_t x, uint32_t y, uint32_t z, uint32_t w) {
    asm volatile("st.async.shared::cluster.mbarrier::complete_tx::bytes.v4.b32 [%0], {%1,%2,%3,%4}, [%5];"
                 :: "r"(a), "r"(x), "r"(y), "r"(z), "r"(w), "r"(bar) : "memory");
}
__device__ __forceinline__ void st_async2(uint32_t a, uint32_t bar, uint32_t x, uint32_t y) {
    asm volatile("st.async.shared::cluster.mbarrier::complete_tx::bytes.v2.b32 [%0], {%1,%2}, [%3];"
                 :: "r"(a), "r"(x), "r"(y), "r"(bar) : "memory");
}
__device__ __forceinline__ void st_async1(uint32_t a, uint32_t bar, uint32_t x) {
    asm volatile("st.async.shared::cluster.mbarrier::complete_tx::bytes.b32 [%0], %1, [%2];" :: "r"(a), "r"(x), "r"(bar) : "memory");
}
__device__ __forceinline__ uint4 ld_relaxed4(const uint4* p) {
    uint4 v;
    asm volatile("ld.relaxed.gpu.global.v4.u32 {%0,%1,%2,%3}, [%4];" : "=r"(v.x), "=r"(v.y), "=r"(v.z), "=r"(v.w) : "l"(p) : "memory");
    return v;
}
__device__ __forceinline__ void st_relaxed4(uint4* p, uint4 v) {
    asm volatile("st.relaxed.gpu.global.v4.u32 [%0], {%1,%2,%3,%4};" :: "l"(p), "r"(v.x), "r"(v.y), "r"(v.z), "r"(v.w) : "memory");
}
__device__ __forceinline__ void st_relaxed1(void* p, uint32_t v) {
    asm volatile("st.relaxed.gpu.global.u32 [%0], %1;" :: "l"(p), "r"(v) : "memory");
}
__device__ __forceinline__ uint32_t umax4(uint4 v) { return max(max(v.x, v.y), max(v.z, v.w)); }
__device__ __forceinline__ void wg_fence() { asm volatile("wgmma.fence.sync.aligned;" ::: "memory"); }
__device__ __forceinline__ void wg_commit() { asm volatile("wgmma.commit_group.sync.aligned;" ::: "memory"); }
template <int N> __device__ __forceinline__ void wg_wait() { asm volatile("wgmma.wait_group.sync.aligned %0;" :: "n"(N) : "memory"); }
template <int N> __device__ __forceinline__ void reg_fence(float* d) {
#pragma unroll
    for (int i = 0; i < N; i++) asm volatile("" : "+f"(d[i]) :: "memory");
}
#define ACC16(d) "+f"(d[0]), "+f"(d[1]), "+f"(d[2]), "+f"(d[3]), "+f"(d[4]), "+f"(d[5]), "+f"(d[6]), "+f"(d[7]), \
                 "+f"(d[8]), "+f"(d[9]), "+f"(d[10]), "+f"(d[11]), "+f"(d[12]), "+f"(d[13]), "+f"(d[14]), "+f"(d[15])
#define DESC_HI_SW128 "0x40000040"
#define OUT16(d) "=f"(d[0]), "=f"(d[1]), "=f"(d[2]), "=f"(d[3]), "=f"(d[4]), "=f"(d[5]), "=f"(d[6]), "=f"(d[7]), \
                 "=f"(d[8]), "=f"(d[9]), "=f"(d[10]), "=f"(d[11]), "=f"(d[12]), "=f"(d[13]), "=f"(d[14]), "=f"(d[15])
template <int ACCUM>
__device__ __forceinline__ void wg32_rs(float* d, const uint32_t* a, uint32_t db) {
    if (ACCUM)
        asm volatile("{\n.reg .b64 db;\nmov.b64 db, {%20, " DESC_HI_SW128 "};\n"
                     "wgmma.mma_async.sync.aligned.m64n32k16.f32.bf16.bf16 {%0,%1,%2,%3,%4,%5,%6,%7,%8,%9,%10,%11,%12,%13,%14,%15}, "
                     "{%16,%17,%18,%19}, db, 1, 1, 1, 0;\n}"
                     : ACC16(d) : "r"(a[0]), "r"(a[1]), "r"(a[2]), "r"(a[3]), "r"(db));
    else
        asm volatile("{\n.reg .b64 db;\nmov.b64 db, {%20, " DESC_HI_SW128 "};\n"
                     "wgmma.mma_async.sync.aligned.m64n32k16.f32.bf16.bf16 {%0,%1,%2,%3,%4,%5,%6,%7,%8,%9,%10,%11,%12,%13,%14,%15}, "
                     "{%16,%17,%18,%19}, db, 0, 1, 1, 0;\n}"
                     : OUT16(d) : "r"(a[0]), "r"(a[1]), "r"(a[2]), "r"(a[3]), "r"(db));
}
__device__ __forceinline__ void wg32_ss(float* d, uint32_t da, uint32_t db) {
    asm volatile("{\n.reg .b64 da, db;\nmov.b64 da, {%16, " DESC_HI_SW128 "};\nmov.b64 db, {%17, " DESC_HI_SW128 "};\n"
                 "wgmma.mma_async.sync.aligned.m64n32k16.f32.bf16.bf16 {%0,%1,%2,%3,%4,%5,%6,%7,%8,%9,%10,%11,%12,%13,%14,%15}, "
                 "da, db, 1, 1, 1, 1, 0;\n}"
                 : ACC16(d) : "r"(da), "r"(db));
}
template <int N>
__device__ __forceinline__ void wg8_chain(float* d, uint32_t da, uint32_t db) {
    wg_fence();
    asm volatile("{\n.reg .b64 da, db;\nmov.b64 da, {%4, " DESC_HI_SW128 "};\nmov.b64 db, {%5, 0x10};\n"
                 "wgmma.mma_async.sync.aligned.m64n8k16.f32.bf16.bf16 {%0,%1,%2,%3}, da, db, 0, 1, 1, 1, 0;\n}"
                 : "=f"(d[0]), "=f"(d[1]), "=f"(d[2]), "=f"(d[3]) : "r"(da), "r"(db));
#pragma unroll
    for (int i = 1; i < N; i++)
        asm volatile("{\n.reg .b64 da, db;\nmov.b64 da, {%4, " DESC_HI_SW128 "};\nmov.b64 db, {%5, 0x10};\n"
                     "wgmma.mma_async.sync.aligned.m64n8k16.f32.bf16.bf16 {%0,%1,%2,%3}, da, db, 1, 1, 1, 1, 0;\n}"
                     : "+f"(d[0]), "+f"(d[1]), "+f"(d[2]), "+f"(d[3]) : "r"(da + i * 128), "r"(db + i * 16));
    wg_commit();
    wg_wait<0>();
    reg_fence<4>(d);
}

__global__ void __launch_bounds__(256) ln_kernel(const __nv_bfloat16* __restrict__ x, const __nv_bfloat16* __restrict__ mem0) {
    const int lane = threadIdx.x & 31, row = blockIdx.x * 8 + (threadIdx.x >> 5);
    const uint4* src = reinterpret_cast<const uint4*>(x + (size_t)row * DM);
    uint4 v[4];
#pragma unroll
    for (int j = 0; j < 4; j++) v[j] = src[j * 32 + lane];
    const int gi = blockIdx.x * 256 + threadIdx.x;
    const uint4 poison = make_uint4(~0u, ~0u, ~0u, ~0u);
    if (gi < 1024) {
        uint4 m = reinterpret_cast<const uint4*>(mem0)[(gi & 7) * 128 + (gi >> 3)];
        if (m.x == ~0u) m.x = 0x7FFF7FFFu;
        if (m.y == ~0u) m.y = 0x7FFF7FFFu;
        if (m.z == ~0u) m.z = 0x7FFF7FFFu;
        if (m.w == ~0u) m.w = 0x7FFF7FFFu;
        g_xmem[0][gi] = m;
    } else if (gi < 4096) {
        (&g_xmem[0][0])[gi] = poison;
    } else if (gi < 4096 + 16384) {
        (&g_xo[0][0])[gi - 4096] = poison;
    } else if (gi < 4096 + 16384 + 48 * FSTR) {
        reinterpret_cast<uint4*>(&g_flag[0][0])[gi - 4096 - 16384] = poison;
    }
    float f[32];
#pragma unroll
    for (int j = 0; j < 4; j++) {
        f[j * 8 + 0] = bf_lo(v[j].x); f[j * 8 + 1] = bf_hi(v[j].x); f[j * 8 + 2] = bf_lo(v[j].y); f[j * 8 + 3] = bf_hi(v[j].y);
        f[j * 8 + 4] = bf_lo(v[j].z); f[j * 8 + 5] = bf_hi(v[j].z); f[j * 8 + 6] = bf_lo(v[j].w); f[j * 8 + 7] = bf_hi(v[j].w);
    }
    float s = 0.f;
#pragma unroll
    for (int i = 0; i < 32; i++) s += f[i];
#pragma unroll
    for (int o = 16; o; o >>= 1) s += __shfl_xor_sync(~0u, s, o);
    const float mean = s * (1.f / DM);
    float q = 0.f;
#pragma unroll
    for (int i = 0; i < 32; i++) { f[i] -= mean; q += f[i] * f[i]; }
#pragma unroll
    for (int o = 16; o; o >>= 1) q += __shfl_xor_sync(~0u, q, o);
    const float r = 1.f / sqrtf(q * (1.f / DM) + 1e-5f);
    uint4* dst = reinterpret_cast<uint4*>(g_xn + (size_t)row * DM);
    uint4* dst2 = g_xc + (row >> 5) * 4096 + (lane >> 3) * 256 + (row & 31) * 8 + ((lane & 7) ^ (row & 7));
#pragma unroll
    for (int j = 0; j < 4; j++) {
        const uint4 o = make_uint4(pack2(f[j * 8] * r, f[j * 8 + 1] * r), pack2(f[j * 8 + 2] * r, f[j * 8 + 3] * r),
                                   pack2(f[j * 8 + 4] * r, f[j * 8 + 5] * r), pack2(f[j * 8 + 6] * r, f[j * 8 + 7] * r));
        dst[j * 32 + lane] = o;
        dst2[(j & 1) * 2048 + (j >> 1) * 1024] = o;
    }
}

constexpr uint32_t C_WS = 0, C_WO = 65536, C_XN = 153600, C_MB = 186368, C_MISC = 202752, C_SMEM = 232448;
constexpr uint32_t C_BAR = C_MISC;
constexpr uint32_t C_RED0 = C_MISC + 256;
constexpr uint32_t C_RED1Q = C_RED0 + 2048, C_QX = C_RED1Q + 2048, C_KX = C_QX + 4096, C_QM = C_KX + 4096, C_KM = C_QM + 1024,
                   C_XSL = C_KM + 1024, C_OL = C_XSL + 5120;
constexpr uint32_t C_V = C_RED0 + 2048, C_PL = C_V + 20480, C_SL = C_PL + 4096, C_RED1V = C_WO + 42 * 2048;
static_assert(C_OL + 3072 <= C_SMEM && C_SL + 2560 <= C_SMEM, "smem overflow");
enum { B_W0 = 0, B_W1, B_W2, B_WS, B_WO, B_XF0, B_XF1, B_XF2, B_SC, B_P0, B_P1, B_XS, B_OL, B_MF0, B_MF1, B_OF, B_NUM };
constexpr uint32_t C_CAL = C_BAR + 192;
constexpr float SM_SCALE = 0.08838834764831845f * 1.4426950408889634f;

#define TSD(i) do {} while (0)
#define TS_PTR(w)
#define TSX(i, c)
#define TS(i)
#define NOFILL 0
#define DLY1 1500
#define DLY2 1750
#define VLEAD 6

#define VEARLY 6
__device__ __forceinline__ bool elect() {
    uint32_t r;
    asm volatile("{\n.reg .pred p;\nelect.sync _|p, 0xffffffff;\nselp.u32 %0, 1, 0, p;\n}" : "=r"(r));
    return r;
}
__device__ __forceinline__ int uni(int v) { return __shfl_sync(~0u, v, 0); }
__device__ __forceinline__ void calibrate(uint32_t cal, float keep) {
    const uint32_t t0 = gtick();
    uint32_t t, it = 0;
    do { t = gtick(); spin_guard(it); } while (t == t0);
    const uint32_t c = clk();
    const uint4 p = lds4u(cal);
    const float cpt = fminf(fmaxf(__fdividef((float)(c - p.y), (float)((t - p.x) & 0x7FFFFFF)), 16.f), 128.f);
    __syncwarp();
    sts4u(cal, make_uint4(t, c, __float_as_uint(keep > 0.f ? fmaf(keep, __uint_as_float(p.z) - cpt, cpt) : cpt), 0));
}
struct Stamps { uint32_t a, b, c; };
__device__ __forceinline__ Stamps load_stamps(const uint32_t* f, uint32_t l16) {
    const char* p = reinterpret_cast<const char*>(f) + (l16 >> 2) * FSTR;
    return Stamps{ld_relaxed1(p), ld_relaxed1(p + 128 * FSTR), ld_relaxed1(p + 256 * FSTR)};
}
__device__ __forceinline__ uint32_t latest_stamp(Stamps v, const uint32_t* f, uint32_t l16, int s, uint32_t cal) {
    const uint4 p = lds4u(cal);
    uint32_t it = 0;
    while (!__all_sync(~0u, (((v.a ^ s) | (v.b ^ s) | (v.c ^ s)) & 63) == 0)) { v = load_stamps(f, l16); spin_guard(it); }
    const uint32_t ref = p.x << 6;
    const int late = __reduce_max_sync(~0u, max(max((int)(v.a - ref), (int)(v.b - ref)), (int)(v.c - ref))) >> 6;
    return p.y + (int)((float)late * __uint_as_float(p.z));
}
__device__ __forceinline__ void wait_clock(uint32_t target) {
    uint32_t it = 0;
    while ((int)(clk() - target) < 0 && ++it < 4096) {}
}

template <int CHUNKS>
__device__ __forceinline__ bool refetch(uint32_t buf, const uint4* src, int w4, uint32_t l16, int barid) {
    uint32_t m = 0;
#pragma unroll 1
    for (uint32_t o = l16; o < CHUNKS * 16; o += 512) m = max(m, umax4(lds4u(buf + o)));
    if (!__any_sync(~0u, m == ~0u)) return false;
    bar_sync(barid, 128);
#pragma unroll 1
    for (uint32_t o = w4 * 512 + l16; o < CHUNKS * 16; o += 2048) {
        uint4 v;
        uint32_t it = 0;
        do { v = ld_relaxed4(src + (o >> 4)); spin_guard(it); } while (umax4(v) == ~0u);
        sts4u(buf + o, v);
    }
    fence_async();
    bar_sync(barid, 128);
    return true;
}

template <bool ISV>
__device__ __forceinline__ void chain_main(const CUtensorMap* tA, const CUtensorMap* tB, const CUtensorMap* tWo,
                                           const uint32_t sb, const int cl, const int rank) {
    const int tid = threadIdx.x;
    uint32_t l16_ = __shfl_sync(~0u, (tid & 31) * 16, tid & 31);
    const int warp = uni(tid >> 5), wg = warp >> 2, w4 = warp & 3;
    const int role = uni(rank % 3), head = 2 * cl + (rank >= 3);
    const uint32_t bar = sb + C_BAR;
    constexpr int ONK = ISV ? 42 : 43;
    const int ostart = uni(rank * 43 - (rank >= 3));

    uint32_t wk[24][4], wv[24][4];
    uint32_t a_adr, lane_b;
    {
        const int colA = head * 128 + (ISV ? 0 : role * 64), colB = head * 128 + (ISV ? 64 : role * 64);
        auto load_chunk = [&](uint32_t dst, int j, uint32_t b) {
            mbar_expect(b, 65536);
            tma2d(dst, tA, colA, j * 128, b);
            tma2d(dst + 16384, tB, colB, j * 128, b);
            tma2d(dst + 32768, tB, colB, 512 + j * 128, b);
            tma2d(dst + 49152, tA, colA, 512 + j * 128, b);
        };
        if (tid == 0)
            for (int j = 0; j < 3; j++) load_chunk(sb + j * 65536, j, bar + (B_W0 + j) * 8);
        if (warp == 4) calibrate(sb + C_CAL, 0.f);
        const int lane = tid & 31, kr = (lane & 7) + ((lane >> 4) << 3), rr = lane & 7;
        a_adr = __shfl_sync(~0u, sb + wg * 32768 + kr * 128 + (((w4 * 2 + ((lane >> 3) & 1)) ^ (kr & 7)) << 4), lane);
        if (ISV) {
            lane_b = sb + C_V + w4 * 2560 + rr * 80 + (lane >> 3) * 16;
        } else {
            lane_b = sb + C_QM + ((lane >> 4) + ((lane >> 3) & 1) * 4) * 128 + rr * 16;
        }
        lane_b = __shfl_sync(~0u, lane_b, lane);
#pragma unroll
        for (int j = 0; j < 3; j++) {
            mbar_wait(bar + (B_W0 + j) * 8, 0);
#pragma unroll
            for (int i = 0; i < 8; i++) {
                ldsm4t(wk[j * 8 + i], a_adr + j * 65536 + i * 2048);
                ldsm4t(wv[j * 8 + i], a_adr + j * 65536 + 16384 + i * 2048);
            }
            if (j != 1) {
                bar_sync(6, 256);
                if (j == 0) {
                    if (tid == 0) load_chunk(sb + C_WS, 3, bar + B_WS * 8);
                } else if (warp == 0) {
                    if (lane == 0) mbar_expect(bar + B_WO * 8, ONK * 2048);
                    __syncwarp();
                    for (int i = lane; i < ONK; i += 32) tma2d(sb + C_WO + i * 2048, tWo, cl * 64, (ostart + i) * 16, bar + B_WO * 8);
                }
            }
        }
        if (NOFILL) { for (uint32_t o = C_RED0 + tid * 16; o < C_SMEM; o += 4096) sts4u(sb + o, make_uint4(0, 0, 0, 0)); bar_sync(6, 256); }
        asm volatile("griddepcontrol.wait;" ::: "memory");
        asm volatile("griddepcontrol.launch_dependents;" ::: "memory");
        if (warp == 4) calibrate(sb + C_CAL, 0.f);
    }

    constexpr uint32_t RED1 = ISV ? C_RED1V : C_RED1Q;
    const uint32_t sbw = uni(sb + w4 * 512);
    const uint32_t red_out = uni(wg ? RED1 : C_RED0), red_in = uni(wg ? C_RED0 : RED1);
    const uint32_t mbw = uni(sb + C_MB + wg * 8192);
    const uint32_t xn_desc = uni((((sb + C_XN + wg * 16384) & 0x3FFFF) >> 4) | (1u << 16));
    const uint32_t ws_desc = uni((((sb + C_WS + wg * 32768) & 0x3FFFF) >> 4) | (1u << 16));
    const uint32_t sb_v = uni(mapa(sb, rank - role + 2));
    const uint32_t sb_x = uni(mapa(sb, rank - role + (warp >= 3)));
    const uint32_t sb_o = uni(mapa(sb, w4 + (w4 >> 1)));
    const uint32_t u_off = uni(ISV ? (head * 128 + w4 * 32) * (wg ? 2 : 16) : (cl * 4 + rank - (rank >= 3)) * 256 + (w4 & 1) * 128);
    const uint32_t v_row = uni(sb + C_V + (32 * (warp >> 1) + 4 * (warp & 1)) * 80);
    uint32_t* const my_flag = &g_flag[0][blockIdx.x * FSTR];
    auto load_tokens = [&](int seg, int khalf, uint32_t off, uint32_t bytes, int b) {
        if (!NOFILL && w4 == 3 && elect()) {
            mbar_expect(bar + b * 8, bytes);
            bulk_ld(sb + C_XN + wg * 16384 + off, g_xc + (seg * 4 + khalf * 2 + wg) * 1024 + off / 16, bytes, bar + b * 8);
        }
    };
    auto tokens_a_late = [&](int seg) { load_tokens(seg, 1, wg * 8192, 16384 - wg * 8192, B_XF0 + 2 * wg); };
    if (wg == 1) load_tokens(0, 1, 0, 8192, B_XF1);
    tokens_a_late(0);
    uint32_t pf[4][4];
    auto prefetch = [&]() {
#pragma unroll
        for (int i = 0; i < 4; i++) ldsm4t(pf[i], a_adr + C_WS + (i & 1) * 16384 + (i >> 1) * 2048);
    };
    mbar_wait(bar + B_WS * 8, 0);
    prefetch();

    int s = -1;
#pragma unroll 1
    for (;; s = uni(s + 1)) {
        asm volatile("" : "+r"(l16_), "+r"(lane_b), "+r"(a_adr));
        const uint32_t l16 = l16_;
        const int lane = l16 >> 4;
        TS_PTR(wg);
        TS(0);
        auto token_softmax = [&]() {
            if (!NOFILL && warp >= 6) {
                const int hi = warp - 6;
                const uint32_t src = sb + C_XSL + l16 + hi * 8;
                const int d0 = 16 * role + 8 * hi + (lane >> 2) - 2 * (lane & 3);
                mbar_wait(bar + B_XS * 8, s & 1);
                float e[10];
                float m = -INFINITY;
#pragma unroll
                for (int i = 0; i < 5; i++) {
                    __syncwarp();
                    const float2 a = lds2f(src + i * 512), b = lds2f(src + 2560 + i * 512);
                    e[2 * i] = (i == 0 || d0 >= 8 * (i - 1)) ? a.x + b.x : -INFINITY;
                    e[2 * i + 1] = (i == 0 || d0 > 8 * (i - 1)) ? a.y + b.y : -INFINITY;
                    m = fmaxf(m, fmaxf(e[2 * i], e[2 * i + 1]));
                }
                m = fmaxf(m, __shfl_xor_sync(~0u, m, 1));
                m = fmaxf(m, __shfl_xor_sync(~0u, m, 2));
                m *= -SM_SCALE;
                float l = 0.f;
#pragma unroll
                for (int i = 0; i < 10; i++) { e[i] = ex2(fmaf(e[i], SM_SCALE, m)); l += e[i]; }
                l += __shfl_xor_sync(~0u, l, 1);
                l += __shfl_xor_sync(~0u, l, 2);
                l = rcp(l);
                const uint32_t pd = sb_v + C_PL + (s & 1) * 2048 + role * 768 + hi * 4, pb = sb_v + C_BAR + (B_P0 + (s & 1)) * 8;
                st_async1(pd + (l16 >> 1), pb, pack2(e[0] * l, e[1] * l));
                st_async1(pd + 256 + l16, pb, pack2(e[2] * l, e[3] * l));
                st_async1(pd + 264 + l16, pb, pack2(e[4] * l, e[5] * l));
                if (role) {
                    st_async1(pd + 768 + l16, pb, pack2(e[6] * l, e[7] * l));
                    st_async1(pd + 776 + l16, pb, pack2(e[8] * l, e[9] * l));
                }
                if (hi == 0 && elect()) mbar_expect(bar + B_XS * 8, 3072 + role * 2048);
            }
        };
        if (s >= 0) {
            float ck[4], cv[4];
            while (true) {
                uint32_t b[2][4];
                mbar_wait(bar + (B_MF0 + wg) * 8, s & 1);
                TS(1);
                ldsm4(b[0], mbw + l16 + 12 * 512);
#pragma unroll
                for (int i = 0; i < 4; i++) ck[i] = cv[i] = 0.f;
#pragma unroll
                for (int kp = 0; kp < 16; kp++) {
                    const int grp = kp / 5, ph = kp % 5, nx = kp + 1;
                    if (nx < 16) ldsm4(b[nx & 1], mbw + l16 + ((nx % 5) ? (nx / 5) * 4 + (nx % 5) - 1 : 12 + nx / 5) * 512);
                    const uint32_t* bb = b[kp & 1];
                    if (ph) {
                        const int q = (grp * 4 + ph - 1) * 2, i = ph - 1;
                        ldsm4t(pf[i], a_adr + C_WS + (i & 1) * 16384 + (grp * 2 + 2 + (i >> 1)) * 2048);
                        mma16(cv, wv[q][0], wv[q][1], wv[q][2], wv[q][3], bb[0], bb[1]);
                        mma16(ck, wk[q][0], wk[q][1], wk[q][2], wk[q][3], bb[0], bb[1]);
                        mma16(cv, wv[q + 1][0], wv[q + 1][1], wv[q + 1][2], wv[q + 1][3], bb[2], bb[3]);
                        mma16(ck, wk[q + 1][0], wk[q + 1][1], wk[q + 1][2], wk[q + 1][3], bb[2], bb[3]);
                    } else {
                        mma16(cv, pf[1][0], pf[1][1], pf[1][2], pf[1][3], bb[0], bb[1]);
                        mma16(ck, pf[0][0], pf[0][1], pf[0][2], pf[0][3], bb[0], bb[1]);
                        mma16(cv, pf[3][0], pf[3][1], pf[3][2], pf[3][3], bb[2], bb[3]);
                        mma16(ck, pf[2][0], pf[2][1], pf[2][2], pf[2][3], bb[2], bb[3]);
                    }
                }
                sts4f(sbw + red_out + l16, cv[0], cv[1], cv[2], cv[3]);
                if (!any_nan(cv[0], cv[1])) break;
                if (!refetch<512>(mbw, &g_xmem[s & 3][wg * 512], w4, l16, 1 + wg)) break;
                prefetch();
            }
            TS(2);
            auto stamp = [&]() {
                if (warp == 7) {
                    const uint32_t dep = lds2u(sb + C_CAL + 8).y;
                    const uint32_t v = ((gtick_dep(dep) - (ISV ? VLEAD : 0)) << 6) | s;
                    if (elect()) st_relaxed1(my_flag, v);
                }
                if (s < NSEG - 1) tokens_a_late(s + 1);
            };
            if (!ISV) {
                const uint32_t lane_a = sb + C_KX + ((l16 & 384) << 2) + (l16 & 112);
                auto finish = [&]() {
                    bar_sync(6, 256);
                    const float4 r = lds4f(sbw + red_in + l16);
                    stsm2t(sb + C_QM + warp * 256 + (l16 & 255), pack2(ck[0] + r.x, ck[1] + r.y), pack2(ck[2] + r.z, ck[3] + r.w));
                    bar_sync(6, 256);
                    TSX(3, warp == 0);
                };
                if (warp < 2) {
                    uint32_t k0[2][4], k1[2][4], q0[4], q1[4];
                    const uint32_t kl = lane_a + warp * 256, dst = sb_v + C_SL + role * 1280 + warp * 512 + l16;
                    ldsm4(k0[0], kl); ldsm4(k0[1], kl + 2048);
                    ldsm4(k1[0], kl + 128); ldsm4(k1[1], kl + 128 + 2048);
                    finish();
                    ldsm4(q0, lane_b); ldsm4(q1, lane_b + 256);
                    float s0[4] = {0.f, 0.f, 0.f, 0.f}, s1[4] = {0.f, 0.f, 0.f, 0.f}, s2[4] = {0.f, 0.f, 0.f, 0.f}, s3[4] = {0.f, 0.f, 0.f, 0.f};
                    mma16(s0, q0[0], q0[1], q0[2], q0[3], k0[0][0], k0[0][1]);
                    mma16(s1, q0[0], q0[1], q0[2], q0[3], k0[1][0], k0[1][1]);
                    mma16(s2, q0[0], q0[1], q0[2], q0[3], k1[0][0], k1[0][1]);
                    mma16(s3, q0[0], q0[1], q0[2], q0[3], k1[1][0], k1[1][1]);
                    mma16(s0, q1[0], q1[1], q1[2], q1[3], k0[0][2], k0[0][3]);
                    mma16(s1, q1[0], q1[1], q1[2], q1[3], k0[1][2], k0[1][3]);
                    mma16(s2, q1[0], q1[1], q1[2], q1[3], k1[0][2], k1[0][3]);
                    mma16(s3, q1[0], q1[1], q1[2], q1[3], k1[1][2], k1[1][3]);
                    st_async4(dst, sb_v + C_BAR + B_SC * 8, __float_as_uint(s0[0] + s1[2]), __float_as_uint(s0[1] + s1[3]),
                                  __float_as_uint(s2[0] + s3[2]), __float_as_uint(s2[1] + s3[3]));
                } else if (warp == 2) {
                    uint32_t q0[4], q1[4], m0[4], m1[4];
                    const uint32_t dst = sb_v + C_SL + role * 1280 + 1024 + (l16 >> 1);
                    finish();
                    ldsm4(q0, lane_b); ldsm4(m0, sb + C_KM + l16); ldsm4(m1, sb + C_KM + 512 + l16); ldsm4(q1, lane_b + 256);
                    float s0[4] = {0.f, 0.f, 0.f, 0.f}, s1[4] = {0.f, 0.f, 0.f, 0.f};
                    mma16(s0, q0[0], q0[1], q0[2], q0[3], m0[0], m0[1]);
                    mma16(s1, q0[0], q0[1], q0[2], q0[3], m1[0], m1[1]);
                    mma16(s0, q1[0], q1[1], q1[2], q1[3], m0[2], m0[3]);
                    mma16(s1, q1[0], q1[1], q1[2], q1[3], m1[2], m1[3]);
                    st_async2(dst, sb_v + C_BAR + B_SC * 8, __float_as_uint(s0[0] + s1[2]), __float_as_uint(s0[1] + s1[3]));
                } else {
                    finish();
                    stamp();
                }
                TSX(4, warp == 0);
                if (!NOFILL) {
                    const int mh = warp >= 3, ti = warp - 3 * mh;
                    const uint32_t ka = ti ? lane_a + (ti - 1) * 128 : sb + C_KM + l16;
                    const uint32_t qx = sb + C_QX + mh * 256 + l16 + (l16 & 256);
                    uint32_t k[2][4], q[4][4];
                    ldsm4(k[0], ka); ldsm4(k[1], ka + (ti ? 2048 : 512));
#pragma unroll
                    for (int i = 0; i < 4; i++) ldsm4(q[i], qx + i * 1024);
                    float s0[4] = {0.f, 0.f, 0.f, 0.f};
#pragma unroll
                    for (int i = 0; i < 4; i++) mma16(s0, q[i][0], q[i][1], q[i][2], q[i][3], k[i >> 1][(i & 1) * 2], k[i >> 1][(i & 1) * 2 + 1]);
                    bar_sync(6, 256);
                    st_async4(sb_x + C_XSL + role * 2560 + ti * 512 + l16, sb_x + C_BAR + B_XS * 8,
                              __float_as_uint(s0[0]), __float_as_uint(s0[1]), __float_as_uint(s0[2]), __float_as_uint(s0[3]));
                }
                if (s == NSEG - 1) { token_softmax(); break; }
            } else {
                const uint32_t d = v_row + (s & 1) * 10240 + 64 + (l16 & 96) * 20 + ((l16 & 16) + ((l16 & 128) >> 2)) * 5;
                bar_sync(6, 256);
                const float4 r = lds4f(sbw + red_in + l16);
                stsm2(d, pack2(ck[0] + r.x, ck[1] + r.y), pack2(ck[2] + r.z, ck[3] + r.w));
                bar_sync(6, 256);
                stamp();
                TSX(3, warp == 0);
            }
        }
        if (ISV) {
            auto load_values = [&](uint32_t (*vx)[4], uint32_t* vm, int ss) {
#pragma unroll
                for (int j = 0; j < 4; j++) ldsm4(vx[j], lane_b + (ss & 1) * 10240 + j * 640);
                ldsm4(vm, sb + C_V + (ss & 1) * 10240 + w4 * 2560 + 64 + l16 * 5);
            };
            if (wg == 0) {
                if (s >= 0 && s < NSEG - 1) {
                    uint32_t vx[4][4], vm[4];
                    load_values(vx, vm, s);
                    const uint32_t oo = u_off + ((l16 & 48) << 3) + ((l16 >> 2) & 112);
                    char* dst = reinterpret_cast<char*>(&g_xo[s & 3][0]) + oo;
                    st_relaxed4(reinterpret_cast<uint4*>(reinterpret_cast<char*>(&g_xo[(s + 2) & 3][0]) + oo), make_uint4(~0u, ~0u, ~0u, ~0u));
                    mbar_wait(bar + B_SC * 8, s & 1);
                    TS(4);
                    const float4 a0 = lds4f(sb + C_SL + l16), b0 = lds4f(sb + C_SL + 1280 + l16);
                    const float4 a1 = lds4f(sb + C_SL + 512 + l16), b1 = lds4f(sb + C_SL + 1280 + 512 + l16);
                    const float2 a2 = lds2f(sb + C_SL + 1024 + (l16 >> 1)), b2 = lds2f(sb + C_SL + 1280 + 1024 + (l16 >> 1));
                    const float e[10] = {a0.x + b0.x, a0.y + b0.y, a0.z + b0.z, a0.w + b0.w, a1.x + b1.x, a1.y + b1.y, a1.z + b1.z, a1.w + b1.w,
                                         a2.x + b2.x, a2.y + b2.y};
                    float m = fmaxf(fmaxf(fmaxf(e[0], e[1]), fmaxf(e[2], e[3])), fmaxf(fmaxf(e[4], e[5]), fmaxf(e[6], e[7])));
                    m = fmaxf(m, fmaxf(e[8], e[9]));
                    m = fmaxf(fmaxf(m, __shfl_xor_sync(~0u, m, 1)), fmaxf(__shfl_xor_sync(~0u, m, 2), __shfl_xor_sync(~0u, m, 3)));
                    m *= -SM_SCALE;
                    float x[10];
#pragma unroll
                    for (int i = 0; i < 10; i++) x[i] = ex2(fmaf(e[i], SM_SCALE, m));
                    float o[4][4];
                    const uint32_t p0 = pack2(x[0], x[1]), p1 = pack2(x[2], x[3]), j0 = __float_as_uint(x[1]), j1 = __float_as_uint(x[3]);
#pragma unroll
                    for (int j = 0; j < 4; j++) { o[j][0] = o[j][1] = o[j][2] = o[j][3] = 0.f; mma16(o[j], p0, j0, p1, j1, vx[j][0], vx[j][1]); }
                    const uint32_t p2 = pack2(x[4], x[5]), p3 = pack2(x[6], x[7]), j2 = __float_as_uint(x[5]), j3 = __float_as_uint(x[7]);
#pragma unroll
                    for (int j = 0; j < 4; j++) mma16(o[j], p2, j2, p3, j3, vx[j][2], vx[j][3]);
                    const uint32_t p4 = pack2(x[8], x[9]), j4 = __float_as_uint(x[9]);
                    float l = (((x[0] + x[1]) + (x[2] + x[3])) + ((x[4] + x[5]) + (x[6] + x[7]))) + (x[8] + x[9]);
                    l = (l + __shfl_xor_sync(~0u, l, 1)) + (__shfl_xor_sync(~0u, l, 2) + __shfl_xor_sync(~0u, l, 3));
#pragma unroll
                    for (int j = 0; j < 4; j++) mma8(o[j], p4, j4, vm[j]);
                    l = rcp(l);
                    st_relaxed4(reinterpret_cast<uint4*>(dst), make_uint4(pack2(o[0][0] * l, o[0][1] * l), pack2(o[1][0] * l, o[1][1] * l),
                                                                          pack2(o[2][0] * l, o[2][1] * l), pack2(o[3][0] * l, o[3][1] * l)));
                    if (w4 == 0 && elect()) mbar_expect(bar + B_SC * 8, 2560);
                }
            } else if (s >= 1 && !NOFILL) {
                int ss = s - 1;
#pragma unroll 1
                do {
                    uint32_t vx[4][4], vm[4];
                    TSD(6);
                    load_values(vx, vm, ss);
                    const uint32_t pb = bar + (B_P0 + (ss & 1)) * 8, pl = sb + C_PL + (ss & 1) * 2048;
                    char* orow = reinterpret_cast<char*>(g_ox) + (ss * (32 * HD * 2) + u_off + (l16 >> 6) * (HD * 2) + (l16 & 48));
                    mbar_wait(pb, (ss >> 1) & 1);
                    TSD(7);
                    float o[4][4];
#pragma unroll
                    for (int mh = 0; mh < 2; mh++) {
                        __syncwarp();
                        const uint2 pm = lds2u(pl + mh * 768 + (l16 >> 1));
                        const uint4 p0 = lds4u(pl + mh * 768 + 256 + l16);
#pragma unroll
                        for (int j = 0; j < 4; j++) { o[j][0] = o[j][1] = o[j][2] = o[j][3] = 0.f; mma8(o[j], pm.x, pm.y, vm[j]); }
#pragma unroll
                        for (int j = 0; j < 4; j++) mma16(o[j], p0.x, p0.y, p0.z, p0.w, vx[j][0], vx[j][1]);
                        if (mh) {
                            const uint4 p1 = lds4u(pl + 1536 + l16);
#pragma unroll
                            for (int j = 0; j < 4; j++) mma16(o[j], p1.x, p1.y, p1.z, p1.w, vx[j][2], vx[j][3]);
                        }
                        *reinterpret_cast<uint4*>(orow + mh * (16 * HD * 2)) =
                            make_uint4(pack2(o[0][0], o[0][1]), pack2(o[1][0], o[1][1]), pack2(o[2][0], o[2][1]), pack2(o[3][0], o[3][1]));
                        *reinterpret_cast<uint4*>(orow + mh * (16 * HD * 2) + 8 * HD * 2) =
                            make_uint4(pack2(o[0][2], o[0][3]), pack2(o[1][2], o[1][3]), pack2(o[2][2], o[2][3]), pack2(o[3][2], o[3][3]));
                        if (mh) TSD(9); else TSD(8);
                    }
                    if (w4 == 0 && elect()) mbar_expect(pb, 2048);
                    if (ss != NSEG - 2) break;
                    ss = uni(ss + 1);
                } while (true);
            }
            if (s == NSEG - 1) { mbar_wait(bar + B_SC * 8, s & 1); break; }
            if (wg == 0) bar_arrive(3, 256);
        }
        TS(5);
        float xk[16], xv[16];
        {
            constexpr int NE = ISV ? VEARLY : 8;
            if (!NOFILL) {
                mbar_wait(bar + (B_XF0 + wg) * 8, 0);
                if (wg == 0) bar_sync(7, 256);
                TS(6);
                wg_fence();
                wg32_rs<0>(xk, wk[16], xn_desc);
                wg32_rs<0>(xv, wv[16], xn_desc);
#pragma unroll
                for (int i = 1; i < NE; i++) {
                    wg32_rs<1>(xk, wk[16 + i], xn_desc + (i >> 2) * 256 + (i & 3) * 2);
                    wg32_rs<1>(xv, wv[16 + i], xn_desc + (i >> 2) * 256 + (i & 3) * 2);
                }
                wg_commit();
            }
            Stamps st = {63u, 63u, 63u};
            if (wg == 1) {
                if (NOFILL) wait_clock(clk() + 400);
                if (w4 == 0) st = load_stamps(g_flag[0], l16);
                if (ISV) bar_sync(3, 256);
                if (!NOFILL) mbar_wait(bar + B_XF2 * 8, (s + 1) & 1);
            }
            if (!NOFILL) {
                wg_fence();
#pragma unroll
                for (int i = NE; i < 8; i++) {
                    wg32_rs<1>(xk, wk[16 + i], xn_desc + (i >> 2) * 256 + (i & 3) * 2);
                    wg32_rs<1>(xv, wv[16 + i], xn_desc + (i >> 2) * 256 + (i & 3) * 2);
                }
#pragma unroll
                for (int i = 0; i < 8; i++) {
                    wg32_ss(xk, ws_desc + i * 128, xn_desc + (2 + (i >> 2)) * 256 + (i & 3) * 2);
                    wg32_ss(xv, ws_desc + 1024 + i * 128, xn_desc + (2 + (i >> 2)) * 256 + (i & 3) * 2);
                }
                wg_commit();
                if (wg == 1) bar_arrive(7, 256);
            }
            if (warp == 4 && s >= 0) {
                const uint32_t target = latest_stamp(st, g_flag[0], l16, s, sb + C_CAL) + DLY1;
                const uint4* src = &g_xo[s & 3][ostart * 16];
                TS(10);
                if (elect()) {
                    mbar_expect(bar + B_OF * 8, ONK * 256);
                    wait_clock(target);
                    bulk_ld(sb + C_MB, src, ONK * 256, bar + B_OF * 8);
                }
                __syncwarp();
                TS(8);
            }
            if (!NOFILL) {
                wg_wait<0>();
                reg_fence<16>(xk); reg_fence<16>(xv);
                if (wg == 1) {
                    if (w4 == 3) bar_sync(2, 128); else bar_arrive(2, 128);
                    load_tokens(s + 1, 0, 0, 16384, B_XF1);
                }
            }
            TS(7);
        }
        if (s >= 0) {
            if (wg == 0) {
                const uint32_t dst = sb_o + C_OL + rank * 512 + l16;
                float co[4];
                mbar_wait(bar + B_OF * 8, s & 1);
                bar_arrive(4, 160);
                TS(8);
                while (true) {
                    wg8_chain<ONK>(co, (((sb + C_WO) & 0x3FFFF) >> 4) | (1u << 16), (((sb + C_MB) & 0x3FFFF) >> 4) | (8u << 16));
                    if (!any_nan(co[0], co[1])) break;
                    if (!refetch<ONK * 16>(sb + C_MB, &g_xo[s & 3][ostart * 16], w4, l16, 1)) break;
                }
                st_async4(dst, sb_o + C_BAR + B_OL * 8, __float_as_uint(co[0]), __float_as_uint(co[1]), __float_as_uint(co[2]), __float_as_uint(co[3]));
                TS(9);
            } else if (w4 == 0) {
                bar_sync(4, 160);
                const uint32_t dep = lds2u(sb + C_CAL + 8).y;
                const uint32_t v = (gtick_dep(dep) << 6) | s;
                if (elect()) st_relaxed1(my_flag + 96 * FSTR, v);
                calibrate(sb + C_CAL, 0.75f);
            } else if (!ISV) {
                token_softmax();
                TSX(9, w4 == 2);
            }
        } else {
            mbar_wait(bar + B_WO * 8, 0);
        }
        Stamps st = {63u, 63u, 63u};
        if (wg == 0) {
            if (w4 == 3) bar_sync(5, 256); else bar_arrive(5, 256);
            load_tokens(s + 1, 0, 0, 16384, B_XF0);
            if (!ISV && w4 < 2 && s >= 0) {
                const uint32_t off = u_off + (l16 >> 2), src = sb + C_OL + l16 + w4 * 8;
                char* dst = reinterpret_cast<char*>(&g_xmem[(s + 1) & 3][0]) + off;
                mbar_wait(bar + B_OL * 8, s & 1);
                const float2 a = lds2f(src), b = lds2f(src + 512), c = lds2f(src + 1024), d = lds2f(src + 1536), e = lds2f(src + 2048), f = lds2f(src + 2560);
                st_relaxed1(dst, movm(pack2((a.x + b.x) + (c.x + d.x) + (e.x + f.x), (a.y + b.y) + (c.y + d.y) + (e.y + f.y))));
                TS(10);
                st_relaxed1(reinterpret_cast<char*>(&g_xmem[(s + 3) & 3][0]) + off, ~0u);
                if (w4 == 0 && elect()) mbar_expect(bar + B_OL * 8, 3072);
            }
        } else {
            bar_sync(5, 256);
            if (w4 == 0) st = load_stamps(g_flag[1], l16);
        }
        TS(11);
        if (!NOFILL) {
            mbar_wait(bar + (B_XF0 + wg) * 8, 1);
            if (wg == 0) bar_sync(7, 256);
            TS(12);
            wg_fence();
#pragma unroll
            for (int i = 0; i < 16; i++) {
                wg32_rs<1>(xv, wv[i], xn_desc + (i >> 2) * 256 + (i & 3) * 2);
                wg32_rs<1>(xk, wk[i], xn_desc + (i >> 2) * 256 + (i & 3) * 2);
                if (i == 7) wg_commit();
            }
            wg_commit();
            if (wg == 1) bar_arrive(7, 256);
            wg_wait<1>();
            if (wg == 0) bar_sync(8, 256);
            wg_wait<0>();
            reg_fence<16>(xk); reg_fence<16>(xv);
            if (wg == 1) bar_sync(2, 128);
#pragma unroll
            for (int j = 0; j < 4; j++) sts4f(sbw + C_XN + wg * 24576 + l16 + j * 2048, xv[4 * j], xv[4 * j + 1], xv[4 * j + 2], xv[4 * j + 3]);
            bar_arrive(9 - wg, 256);
        }
        TS(13);
        auto finish_tokens = [&]() {
            if (NOFILL) return;
            uint32_t lo[4], hi[4];
#pragma unroll
            for (int j = 0; j < 4; j++) {
                const float4 r = lds4f(sbw + C_XN + (wg ^ 1) * 24576 + l16 + j * 2048);
                lo[j] = pack2(xk[4 * j] + r.x, xk[4 * j + 1] + r.y);
                hi[j] = pack2(xk[4 * j + 2] + r.z, xk[4 * j + 3] + r.w);
            }
            if (!ISV) {
                const uint32_t d = sb + C_QX + warp * 1024 + l16;
                stsm4t(d, lo[0], lo[1], lo[2], lo[3]);
                stsm4t(d + 512, hi[0], hi[1], hi[2], hi[3]);
            } else {
                uint32_t lf = l16;
                asm volatile("" : "+r"(lf));
                const uint32_t d = v_row + ((s + 1) & 1) * 10240 + (lf & 96) * 20 + (lf & 16) * 5 + ((lf >> 3) & 48);
                stsm4(d, lo[0], lo[1], lo[2], lo[3]);
                stsm4(d + 160, hi[0], hi[1], hi[2], hi[3]);
            }
        };
        if (wg == 1) {
            if (s < NSEG - 2) load_tokens(s + 2, 1, 0, 8192, B_XF1);
            prefetch();
            if (w4 == 0) {
                uint32_t target = 0;
                if (s >= 0) target = latest_stamp(st, g_flag[1], l16, s, sb + C_CAL) + DLY2;
                const uint4* src = &g_xmem[(s + 1) & 3][0];
                TS(3);
                if (elect()) {
                    mbar_expect(bar + B_MF0 * 8, 8192);
                    mbar_expect(bar + B_MF1 * 8, 8192);
                    if (s >= 0) wait_clock(target);
                    bulk_ld(sb + C_MB, src, 8192, bar + B_MF0 * 8);
                    bulk_ld(sb + C_MB + 8192, src + 512, 8192, bar + B_MF1 * 8);
                }
                __syncwarp();
                TS(4);
            }
            if (!NOFILL) bar_sync(9, 256);
            finish_tokens();
            if (!ISV) bar_arrive(10, 256);
        } else {
            finish_tokens();
            prefetch();
            if (!ISV) bar_sync(10, 256);
        }
    }
}

__global__ void __cluster_dims__(6, 1, 1) __launch_bounds__(256, 1)
chain_kernel(const __grid_constant__ CUtensorMap tq, const __grid_constant__ CUtensorMap tk, const __grid_constant__ CUtensorMap tv,
             const __grid_constant__ CUtensorMap two) {
    extern __shared__ __align__(1024) uint8_t smem[];
    const uint32_t sb = smem_u32(smem);
    const int rank = blockIdx.x % 6, cl = blockIdx.x / 6, role = rank % 3;
    if (threadIdx.x == 0) {
        const uint32_t bar = sb + C_BAR;
        for (int i = 0; i < B_NUM; i++) mbar_init(bar + i * 8, 1);
        if (role == 2) {
            mbar_expect(bar + B_SC * 8, 2560);
            mbar_expect(bar + B_P0 * 8, 2048);
            mbar_expect(bar + B_P1 * 8, 2048);
        } else {
            mbar_expect(bar + B_XS * 8, role ? 5120 : 3072);
            mbar_expect(bar + B_OL * 8, 3072);
        }
        asm volatile("fence.mbarrier_init.release.cluster;" ::: "memory");
        fence_async();
    }
    __syncthreads();
    cluster_sync();
    if (role == 2) chain_main<true>(&tv, &tv, &two, sb, cl, rank);
    else chain_main<false>(&tq, &tk, &two, sb, cl, rank);
    __syncwarp();
    cluster_sync();
}

constexpr int G_STAGES = 4;
constexpr uint32_t G_STAGE = 49152, G_EPI = G_STAGES * G_STAGE, G_BAR = G_EPI + 32768, G_SMEM = G_BAR + 256;

__device__ __forceinline__ void wg256(float* d, uint32_t da, uint32_t db, uint32_t accum) {
    asm volatile("{\n.reg .b64 da, db;\n.reg .pred p;\nsetp.ne.u32 p, %130, 0;\nmov.b64 da, {%128, " DESC_HI_SW128 "};\nmov.b64 db, {%129, " DESC_HI_SW128 "};\n"
                 "wgmma.mma_async.sync.aligned.m64n256k16.f32.bf16.bf16 {"
                 "%0,%1,%2,%3,%4,%5,%6,%7,%8,%9,%10,%11,%12,%13,%14,%15,%16,%17,%18,%19,%20,%21,%22,%23,%24,%25,%26,%27,%28,%29,%30,%31,"
                 "%32,%33,%34,%35,%36,%37,%38,%39,%40,%41,%42,%43,%44,%45,%46,%47,%48,%49,%50,%51,%52,%53,%54,%55,%56,%57,%58,%59,%60,%61,%62,%63,"
                 "%64,%65,%66,%67,%68,%69,%70,%71,%72,%73,%74,%75,%76,%77,%78,%79,%80,%81,%82,%83,%84,%85,%86,%87,%88,%89,%90,%91,%92,%93,%94,%95,"
                 "%96,%97,%98,%99,%100,%101,%102,%103,%104,%105,%106,%107,%108,%109,%110,%111,%112,%113,%114,%115,%116,%117,%118,%119,%120,%121,%122,%123,%124,%125,%126,%127"
                 "}, da, db, p, 1, 1, 0, 1;\n}"
                 : ACC16(d), ACC16((d + 16)), ACC16((d + 32)), ACC16((d + 48)), ACC16((d + 64)), ACC16((d + 80)), ACC16((d + 96)), ACC16((d + 112))
                 : "r"(da), "r"(db), "r"(accum));
}
__device__ __forceinline__ float sigmoidf_(float v) { return rcp(1.f + ex2(-1.4426950408889634f * v)); }

template <int MODE>
__global__ void __cluster_dims__(2, 1, 1) __launch_bounds__(384, 1)
gemm_kernel(const __grid_constant__ CUtensorMap tA, const __grid_constant__ CUtensorMap tB0, const __grid_constant__ CUtensorMap tB1,
            const __grid_constant__ CUtensorMap tOut, const __grid_constant__ CUtensorMap tX, const __grid_constant__ CUtensorMap tY) {
    constexpr int KB = MODE == 0 ? DM / 64 : (MODE == 1 ? FF / 64 : HD / 64);
    constexpr int NT = MODE == 0 ? FF / 128 : DM / 256;
    constexpr int NTILES = NT * 8;
    extern __shared__ __align__(1024) uint8_t smem[];
    const uint32_t sb = smem_u32(smem);
    const uint32_t full = sb + G_BAR, empty = full + 64;
    const int tid = threadIdx.x, lane = tid & 31;
    const int wg = __shfl_sync(~0u, tid >> 7, 0);
    const int rank = blockIdx.x & 1, pair = blockIdx.x >> 1, npair = gridDim.x >> 1;
    if (tid == 0) {
        for (int i = 0; i < G_STAGES; i++) { mbar_init(full + i * 8, 1); mbar_init(empty + i * 8, 16); }
        asm volatile("fence.mbarrier_init.release.cluster;" ::: "memory");
        fence_async();
    }
    __syncthreads();
    cluster_sync();
    if (wg == 0) {
        asm volatile("setmaxnreg.dec.sync.aligned.u32 40;");
        if (tid == 0) {
            uint32_t st = 0, ph = 1;
            for (int tile = pair; tile < NTILES; tile += npair) {
                const int mp = tile & 7, nt = tile >> 3, row0 = (mp * 2 + rank) * 128;
                const CUtensorMap* tB = (MODE == 0 && rank) ? &tB1 : &tB0;
                const int bcol = MODE == 0 ? nt * 128 : nt * 256 + rank * 128;
                for (int kb = 0; kb < KB; kb++) {
                    mbar_wait(empty + st * 8, ph);
                    const uint32_t base = sb + st * G_STAGE;
                    mbar_expect(full + st * 8, G_STAGE);
                    tma2d(base, &tA, kb * 64, row0, full + st * 8);
                    tma2d_mc(base + 16384 + rank * 16384, tB, bcol, kb * 64, full + st * 8, 3);
                    tma2d_mc(base + 16384 + rank * 16384 + 8192, tB, bcol + 64, kb * 64, full + st * 8, 3);
                    if (++st == G_STAGES) { st = 0; ph ^= 1; }
                }
                if (MODE == 2) {
                    for (int q = 0; q < 4; q++) {
                        mbar_wait(empty + st * 8, ph);
                        const uint32_t base = sb + st * G_STAGE;
                        mbar_expect(full + st * 8, 32768);
                        tma2d(base, &tX, nt * 256 + q * 64, row0, full + st * 8);
                        tma2d(base + 16384, &tY, nt * 256 + q * 64, row0, full + st * 8);
                        if (++st == G_STAGES) { st = 0; ph ^= 1; }
                    }
                }
            }
        }
        __syncwarp();
        cluster_sync();
    } else {
        asm volatile("setmaxnreg.inc.sync.aligned.u32 232;");
        const int cw = wg - 1, w4 = (tid >> 5) & 3;
        const uint32_t empty_dst = mapa(empty, lane & 1);
        const uint32_t epi = sb + G_EPI + cw * 16384;
        const int er = w4 * 16 + (lane & 15), ec = lane >> 4;
        uint32_t st = 0, ph = 0;
        float acc[128];
        for (int tile = pair; tile < NTILES; tile += npair) {
            const int mp = tile & 7, nt = tile >> 3, row0 = (mp * 2 + rank) * 128 + cw * 64;
            uint32_t prev = 0;
#pragma unroll 1
            for (int kb = 0; kb < KB; kb++) {
                mbar_wait(full + st * 8, ph);
                const uint32_t base = sb + st * G_STAGE;
                const uint32_t da = (((base + cw * 8192) & 0x3FFFF) >> 4) | (1u << 16);
                const uint32_t db = (((base + 16384) & 0x3FFFF) >> 4) | (512u << 16);
                wg_fence();
#pragma unroll
                for (int k = 0; k < 4; k++) wg256(acc, da + k * 2, db + k * 128, (kb | k) != 0);
                wg_commit();
                if (kb > 0) {
                    wg_wait<1>();
                    if (lane < 2) mbar_arrive_cluster(empty_dst + prev * 8);
                }
                prev = st;
                if (++st == G_STAGES) { st = 0; ph ^= 1; }
            }
            wg_wait<0>();
            reg_fence<128>(acc);
            if (lane < 2) mbar_arrive_cluster(empty_dst + prev * 8);
#pragma unroll
            for (int hp = 0; hp < (MODE == 0 ? 1 : 2); hp++) {
                uint32_t o[32];
#pragma unroll
                for (int bx = 0; bx < 2; bx++) {
                    uint32_t xa = 0;
                    if (MODE == 2) {
                        mbar_wait(full + st * 8, ph);
                        xa = sb + st * G_STAGE + (cw * 64 + er) * 128;
                    }
#pragma unroll
                    for (int j = 0; j < 4; j++) {
                        const int a0 = hp * 64 + bx * 32 + j * 8;
                        uint32_t* oo = o + bx * 16 + j * 4;
                        if (MODE == 0) {
#pragma unroll
                            for (int i = 0; i < 4; i++)
                                oo[i] = pack2(sigmoidf_(acc[a0 + 2 * i]) * acc[64 + a0 + 2 * i], sigmoidf_(acc[a0 + 2 * i + 1]) * acc[64 + a0 + 2 * i + 1]);
                        } else if (MODE == 1) {
#pragma unroll
                            for (int i = 0; i < 4; i++)
                                oo[i] = pack2(sigmoidf_(acc[a0 + 2 * i]) * acc[a0 + 2 * i], sigmoidf_(acc[a0 + 2 * i + 1]) * acc[a0 + 2 * i + 1]);
                        } else {
                            uint32_t xv[4], yv[4];
                            const uint32_t ad = xa + (((2 * j + ec) ^ (er & 7)) << 4);
                            ldsm4(xv, ad); ldsm4(yv, ad + 16384);
#pragma unroll
                            for (int i = 0; i < 4; i++)
                                oo[i] = pack2(fmaf(acc[a0 + 2 * i], bf_lo(yv[i]), bf_lo(xv[i])), fmaf(acc[a0 + 2 * i + 1], bf_hi(yv[i]), bf_hi(xv[i])));
                        }
                    }
                    if (MODE == 2) {
                        __syncwarp();
                        if (lane < 2) mbar_arrive_cluster(empty_dst + st * 8);
                        if (++st == G_STAGES) { st = 0; ph ^= 1; }
                    }
                }
                if ((tid & 127) == 0) asm volatile("cp.async.bulk.wait_group.read 0;" ::: "memory");
                bar_sync(1 + cw, 128);
#pragma unroll
                for (int bx = 0; bx < 2; bx++)
#pragma unroll
                    for (int j = 0; j < 4; j++) {
                        const uint32_t* oo = o + bx * 16 + j * 4;
                        stsm4(epi + bx * 8192 + er * 128 + (((2 * j + ec) ^ (er & 7)) << 4), oo[0], oo[1], oo[2], oo[3]);
                    }
                fence_async();
                bar_sync(1 + cw, 128);
                if ((tid & 127) == 0) {
                    const int col = MODE == 0 ? nt * 128 : nt * 256 + hp * 128;
                    tma2d_store(&tOut, col, row0, epi);
                    tma2d_store(&tOut, col + 64, row0, epi + 8192);
                    asm volatile("cp.async.bulk.commit_group;" ::: "memory");
                }
            }
        }
        if ((tid & 127) == 0) asm volatile("cp.async.bulk.wait_group 0;" ::: "memory");
        __syncwarp();
        cluster_sync();
    }
}

typedef CUresult (*EncodeFn)(CUtensorMap*, CUtensorMapDataType, cuuint32_t, void*, const cuuint64_t*, const cuuint64_t*, const cuuint32_t*,
                             const cuuint32_t*, CUtensorMapInterleave, CUtensorMapSwizzle, CUtensorMapL2promotion, CUtensorMapFloatOOBfill);

CUtensorMap make_map(EncodeFn enc, const void* p, int rows, int cols, int box_rows) {
    CUtensorMap m;
    cuuint64_t dims[2] = {(cuuint64_t)cols, (cuuint64_t)rows}, strides[1] = {(cuuint64_t)cols * 2};
    cuuint32_t box[2] = {64, (cuuint32_t)box_rows}, es[2] = {1, 1};
    enc(&m, CU_TENSOR_MAP_DATA_TYPE_BFLOAT16, 2, const_cast<void*>(p), dims, strides, box, es, CU_TENSOR_MAP_INTERLEAVE_NONE,
        CU_TENSOR_MAP_SWIZZLE_128B, CU_TENSOR_MAP_L2_PROMOTION_L2_128B, CU_TENSOR_MAP_FLOAT_OOB_FILL_NONE);
    return m;
}

}

extern "C" void kernel_launch(void* const* d_in, const int* in_sizes, int n_in, void* d_out, int out_size) {
    const __nv_bfloat16* x = (const __nv_bfloat16*)d_in[0];
    const __nv_bfloat16* mem0 = (const __nv_bfloat16*)d_in[1];
    void* fn = nullptr;
    cudaDriverEntryPointQueryResult qr;
    cudaGetDriverEntryPoint("cuTensorMapEncodeTiled", &fn, cudaEnableDefault, &qr);
    EncodeFn enc = (EncodeFn)fn;
    void *xn, *ox, *h, *y;
    cudaGetSymbolAddress(&xn, g_xn); cudaGetSymbolAddress(&ox, g_ox); cudaGetSymbolAddress(&h, g_h); cudaGetSymbolAddress(&y, g_y);

    const CUtensorMap tq = make_map(enc, d_in[2], DM, HD, 128), tk = make_map(enc, d_in[3], DM, HD, 128), tv = make_map(enc, d_in[4], DM, HD, 128);
    const CUtensorMap two16 = make_map(enc, d_in[5], HD, DM, 16);
    const CUtensorMap txn128 = make_map(enc, xn, SEQ, DM, 128), tg = make_map(enc, d_in[8], DM, FF, 64), tu = make_map(enc, d_in[9], DM, FF, 64);
    const CUtensorMap th64 = make_map(enc, h, SEQ, FF, 64), th128 = make_map(enc, h, SEQ, FF, 128), td = make_map(enc, d_in[10], FF, DM, 64);
    const CUtensorMap ty64 = make_map(enc, y, SEQ, DM, 64), ty128 = make_map(enc, y, SEQ, DM, 128), tx128 = make_map(enc, x, SEQ, DM, 128);
    const CUtensorMap tox = make_map(enc, ox, SEQ, HD, 128), two64 = make_map(enc, d_in[5], HD, DM, 64), tout = make_map(enc, d_out, SEQ, DM, 64);

    cudaFuncSetAttribute(chain_kernel, cudaFuncAttributeMaxDynamicSharedMemorySize, C_SMEM);
    cudaFuncSetAttribute(gemm_kernel<0>, cudaFuncAttributeMaxDynamicSharedMemorySize, G_SMEM);
    cudaFuncSetAttribute(gemm_kernel<1>, cudaFuncAttributeMaxDynamicSharedMemorySize, G_SMEM);
    cudaFuncSetAttribute(gemm_kernel<2>, cudaFuncAttributeMaxDynamicSharedMemorySize, G_SMEM);

    cudaStream_t st = cudaStreamPerThread;
    ln_kernel<<<SEQ / 8, 256, 0, st>>>(x, mem0);
    chain_kernel<<<96, 256, C_SMEM, st>>>(tq, tk, tv, two16);
    gemm_kernel<0><<<132, 384, G_SMEM, st>>>(txn128, tg, tu, th64, th64, th64);
    gemm_kernel<1><<<64, 384, G_SMEM, st>>>(th128, td, td, ty64, ty64, ty64);
    gemm_kernel<2><<<64, 384, G_SMEM, st>>>(tox, two64, two64, tout, tx128, ty128);
}
```

```cpp
#include <cuda_runtime.h>
#include <cuda_bf16.h>
#include <cuda.h>
#include <stdint.h>
#include <type_traits>

namespace {

constexpr int SEQ = 2048, DM = 1024, HD = 4096, FF = 3584, NSEG = 64;

__device__ __align__(1024) __nv_bfloat16 g_xn[SEQ * DM];
__device__ __align__(1024) uint4 g_xc[SEQ * DM / 8];
__device__ __align__(1024) __nv_bfloat16 g_ox[SEQ * HD];
__device__ __align__(1024) __nv_bfloat16 g_h[SEQ * FF];
__device__ __align__(1024) __nv_bfloat16 g_y[SEQ * DM];
__device__ __align__(1024) uint4 g_xmem[4][1024];
__device__ __align__(1024) uint4 g_xo[4][4096];
#define FSTR 8
__device__ __align__(1024) uint32_t g_flag[2][96 * FSTR];

__device__ __forceinline__ uint32_t smem_u32(const void* p) { return (uint32_t)__cvta_generic_to_shared(p); }
__device__ __forceinline__ uint32_t mapa(uint32_t a, uint32_t r) {
    uint32_t o; asm("mapa.shared::cluster.u32 %0, %1, %2;" : "=r"(o) : "r"(a), "r"(r)); return o;
}
__device__ __forceinline__ void mbar_init(uint32_t a, uint32_t cnt) {
    asm volatile("mbarrier.init.shared.b64 [%0], %1;" :: "r"(a), "r"(cnt) : "memory");
}
__device__ __forceinline__ void mbar_expect(uint32_t a, uint32_t bytes) {
    asm volatile("mbarrier.arrive.expect_tx.shared.b64 _, [%0], %1;" :: "r"(a), "r"(bytes) : "memory");
}
__device__ __forceinline__ void mbar_arrive_cluster(uint32_t a) {
    asm volatile("mbarrier.arrive.shared::cluster.b64 _, [%0];" :: "r"(a) : "memory");
}
__device__ __forceinline__ void spin_guard(uint32_t& it) {
    asm volatile("{\n.reg .pred p;\nadd.u32 %0, %0, 1;\nsetp.gt.u32 p, %0, 0x400000;\n@p st.shared.u32 [%0], %0;\n}" : "+r"(it));
}
__device__ __forceinline__ void mbar_wait(uint32_t a, uint32_t par) {
    asm volatile("{\n.reg .pred p;\n.reg .u32 i;\nmov.u32 i, 0;\n"
                 "WL:\nmbarrier.try_wait.parity.shared::cta.b64 p, [%0], %1;\n@p bra WD;\n"
                 "add.u32 i, i, 1;\nsetp.gt.u32 p, i, 0x400000;\n@p st.shared.u32 [i], i;\nbra WL;\nWD:\n}" :: "r"(a), "r"(par) : "memory");
}
__device__ __forceinline__ void mbar_arrive(uint32_t a) { asm volatile("mbarrier.arrive.shared.b64 _, [%0];" :: "r"(a) : "memory"); }
__device__ __forceinline__ void tma2d(uint32_t dst, const CUtensorMap* m, int c0, int c1, uint32_t bar) {
    asm volatile("cp.async.bulk.tensor.2d.shared::cluster.global.mbarrier::complete_tx::bytes [%0], [%1, {%3, %4}], [%2];"
                 :: "r"(dst), "l"(m), "r"(bar), "r"(c0), "r"(c1) : "memory");
}
__device__ __forceinline__ void tma2d_mc(uint32_t dst, const CUtensorMap* m, int c0, int c1, uint32_t bar, uint16_t mask) {
    asm volatile("cp.async.bulk.tensor.2d.shared::cluster.global.mbarrier::complete_tx::bytes.multicast::cluster [%0], [%1, {%3, %4}], [%2], %5;"
                 :: "r"(dst), "l"(m), "r"(bar), "r"(c0), "r"(c1), "h"(mask) : "memory");
}
__device__ __forceinline__ void bulk_mc(uint32_t dst, const void* src, uint32_t bytes, uint32_t bar, uint16_t mask) {
    asm volatile("cp.async.bulk.shared::cluster.global.mbarrier::complete_tx::bytes.multicast::cluster [%0], [%1], %2, [%3], %4;"
                 :: "r"(dst), "l"(src), "r"(bytes), "r"(bar), "h"(mask) : "memory");
}
__device__ __forceinline__ void bulk_ld(uint32_t dst, const void* src, uint32_t bytes, uint32_t bar) {
    asm volatile("cp.async.bulk.shared::cluster.global.mbarrier::complete_tx::bytes [%0], [%1], %2, [%3];"
                 :: "r"(dst), "l"(src), "r"(bytes), "r"(bar) : "memory");
}
__device__ __forceinline__ uint32_t gtick() { uint32_t c; asm volatile("mov.u32 %0, %%globaltimer_lo;" : "=r"(c)); return c >> 5; }
__device__ __forceinline__ uint32_t gtick_dep(uint32_t zero) {
    uint32_t c;
    asm volatile("{\n.reg .pred p;\nsetp.eq.u32 p, %1, 0;\nmov.u32 %0, 0;\n@p mov.u32 %0, %%globaltimer_lo;\n}" : "=r"(c) : "r"(zero));
    return c >> 5;
}
__device__ __forceinline__ uint32_t ld_relaxed1(const void* p) {
    uint32_t v; asm volatile("ld.relaxed.gpu.global.u32 %0, [%1];" : "=r"(v) : "l"(p) : "memory"); return v;
}
__device__ __forceinline__ bool any_nan(float a, float b) {
    uint32_t r;
    asm volatile("{\n.reg .pred p;\nsetp.nan.f32 p, %1, %2;\nvote.sync.any.pred p, p, 0xffffffff;\nselp.u32 %0, 1, 0, p;\n}" : "=r"(r) : "f"(a), "f"(b));
    return r;
}
__device__ __forceinline__ void bar_arrive(int id, int n) { asm volatile("bar.arrive %0, %1;" :: "r"(id), "r"(n) : "memory"); }
__device__ __forceinline__ uint32_t clk() { uint32_t c; asm volatile("mov.u32 %0, %%clock;" : "=r"(c)); return c; }
__device__ __forceinline__ void tma2d_store(const CUtensorMap* m, int c0, int c1, uint32_t src) {
    asm volatile("cp.async.bulk.tensor.2d.global.shared::cta.bulk_group [%0, {%1, %2}], [%3];"
                 :: "l"(m), "r"(c0), "r"(c1), "r"(src) : "memory");
}
__device__ __forceinline__ void bar_sync(int id, int n) { asm volatile("bar.sync %0, %1;" :: "r"(id), "r"(n) : "memory"); }
__device__ __forceinline__ void fence_async() { asm volatile("fence.proxy.async.shared::cta;" ::: "memory"); }
__device__ __forceinline__ void cluster_sync() {
    asm volatile("barrier.cluster.arrive.release.aligned;\nbarrier.cluster.wait.acquire.aligned;" ::: "memory");
}
__device__ __forceinline__ void ldsm4(uint32_t* r, uint32_t a) {
    asm volatile("ldmatrix.sync.aligned.m8n8.x4.shared.b16 {%0,%1,%2,%3}, [%4];"
                 : "=r"(r[0]), "=r"(r[1]), "=r"(r[2]), "=r"(r[3]) : "r"(a) : "memory");
}
__device__ __forceinline__ void ldsm4t(uint32_t* r, uint32_t a) {
    asm volatile("ldmatrix.sync.aligned.m8n8.x4.trans.shared.b16 {%0,%1,%2,%3}, [%4];"
                 : "=r"(r[0]), "=r"(r[1]), "=r"(r[2]), "=r"(r[3]) : "r"(a) : "memory");
}
__device__ __forceinline__ void stsm4(uint32_t a, uint32_t r0, uint32_t r1, uint32_t r2, uint32_t r3) {
    asm volatile("stmatrix.sync.aligned.m8n8.x4.shared.b16 [%0], {%1,%2,%3,%4};" :: "r"(a), "r"(r0), "r"(r1), "r"(r2), "r"(r3) : "memory");
}
__device__ __forceinline__ void stsm4t(uint32_t a, uint32_t r0, uint32_t r1, uint32_t r2, uint32_t r3) {
    asm volatile("stmatrix.sync.aligned.m8n8.x4.trans.shared.b16 [%0], {%1,%2,%3,%4};" :: "r"(a), "r"(r0), "r"(r1), "r"(r2), "r"(r3) : "memory");
}
__device__ __forceinline__ void stsm2(uint32_t a, uint32_t r0, uint32_t r1) {
    asm volatile("stmatrix.sync.aligned.m8n8.x2.shared.b16 [%0], {%1,%2};" :: "r"(a), "r"(r0), "r"(r1) : "memory");
}
__device__ __forceinline__ void stsm2t(uint32_t a, uint32_t r0, uint32_t r1) {
    asm volatile("stmatrix.sync.aligned.m8n8.x2.trans.shared.b16 [%0], {%1,%2};" :: "r"(a), "r"(r0), "r"(r1) : "memory");
}
__device__ __forceinline__ uint32_t movm(uint32_t a) {
    uint32_t d; asm volatile("movmatrix.sync.aligned.m8n8.trans.b16 %0, %1;" : "=r"(d) : "r"(a)); return d;
}
__device__ __forceinline__ void mma16(float* d, uint32_t a0, uint32_t a1, uint32_t a2, uint32_t a3, uint32_t b0, uint32_t b1) {
    asm volatile("mma.sync.aligned.m16n8k16.row.col.f32.bf16.bf16.f32 {%0,%1,%2,%3}, {%4,%5,%6,%7}, {%8,%9}, {%0,%1,%2,%3};"
                 : "+f"(d[0]), "+f"(d[1]), "+f"(d[2]), "+f"(d[3]) : "r"(a0), "r"(a1), "r"(a2), "r"(a3), "r"(b0), "r"(b1));
}
__device__ __forceinline__ void mma8(float* d, uint32_t a0, uint32_t a1, uint32_t b0) {
    asm volatile("mma.sync.aligned.m16n8k8.row.col.f32.bf16.bf16.f32 {%0,%1,%2,%3}, {%4,%5}, {%6}, {%0,%1,%2,%3};"
                 : "+f"(d[0]), "+f"(d[1]), "+f"(d[2]), "+f"(d[3]) : "r"(a0), "r"(a1), "r"(b0));
}
__device__ __forceinline__ uint32_t pack2(float lo, float hi) {
    uint32_t r; asm("cvt.rn.bf16x2.f32 %0, %1, %2;" : "=r"(r) : "f"(hi), "f"(lo)); return r;
}
__device__ __forceinline__ float bf_lo(uint32_t v) { return __uint_as_float(v << 16); }
__device__ __forceinline__ float bf_hi(uint32_t v) { return __uint_as_float(v & 0xFFFF0000u); }
__device__ __forceinline__ float ex2(float x) { float y; asm("ex2.approx.ftz.f32 %0, %1;" : "=f"(y) : "f"(x)); return y; }
__device__ __forceinline__ float rcp(float x) { float y; asm("rcp.approx.ftz.f32 %0, %1;" : "=f"(y) : "f"(x)); return y; }
__device__ __forceinline__ void sts4f(uint32_t a, float x, float y, float z, float w) {
    asm volatile("st.shared.v4.f32 [%0], {%1,%2,%3,%4};" :: "r"(a), "f"(x), "f"(y), "f"(z), "f"(w) : "memory");
}
__device__ __forceinline__ void sts4u(uint32_t a, uint4 v) {
    asm volatile("st.shared.v4.u32 [%0], {%1,%2,%3,%4};" :: "r"(a), "r"(v.x), "r"(v.y), "r"(v.z), "r"(v.w) : "memory");
}
__device__ __forceinline__ float4 lds4f(uint32_t a) {
    float4 v; asm volatile("ld.shared.v4.f32 {%0,%1,%2,%3}, [%4];" : "=f"(v.x), "=f"(v.y), "=f"(v.z), "=f"(v.w) : "r"(a) : "memory"); return v;
}
__device__ __forceinline__ float2 lds2f(uint32_t a) {
    float2 v; asm volatile("ld.shared.v2.f32 {%0,%1}, [%2];" : "=f"(v.x), "=f"(v.y) : "r"(a) : "memory"); return v;
}
__device__ __forceinline__ uint4 lds4u(uint32_t a) {
    uint4 v; asm volatile("ld.shared.v4.u32 {%0,%1,%2,%3}, [%4];" : "=r"(v.x), "=r"(v.y), "=r"(v.z), "=r"(v.w) : "r"(a) : "memory"); return v;
}
__device__ __forceinline__ uint32_t lds1u(uint32_t a) {
    uint32_t v; asm volatile("ld.shared.u32 %0, [%1];" : "=r"(v) : "r"(a) : "memory"); return v;
}
__device__ __forceinline__ uint2 lds2u(uint32_t a) {
    uint2 v; asm volatile("ld.shared.v2.u32 {%0,%1}, [%2];" : "=r"(v.x), "=r"(v.y) : "r"(a) : "memory"); return v;
}
__device__ __forceinline__ void st_async4(uint32_t a, uint32_t bar, uint32_t x, uint32_t y, uint32_t z, uint32_t w) {
    asm volatile("st.async.shared::cluster.mbarrier::complete_tx::bytes.v4.b32 [%0], {%1,%2,%3,%4}, [%5];"
                 :: "r"(a), "r"(x), "r"(y), "r"(z), "r"(w), "r"(bar) : "memory");
}
__device__ __forceinline__ void st_async2(uint32_t a, uint32_t bar, uint32_t x, uint32_t y) {
    asm volatile("st.async.shared::cluster.mbarrier::complete_tx::bytes.v2.b32 [%0], {%1,%2}, [%3];"
                 :: "r"(a), "r"(x), "r"(y), "r"(bar) : "memory");
}
__device__ __forceinline__ void st_async1(uint32_t a, uint32_t bar, uint32_t x) {
    asm volatile("st.async.shared::cluster.mbarrier::complete_tx::bytes.b32 [%0], %1, [%2];" :: "r"(a), "r"(x), "r"(bar) : "memory");
}
__device__ __forceinline__ uint4 ld_relaxed4(const uint4* p) {
    uint4 v;
    asm volatile("ld.relaxed.gpu.global.v4.u32 {%0,%1,%2,%3}, [%4];" : "=r"(v.x), "=r"(v.y), "=r"(v.z), "=r"(v.w) : "l"(p) : "memory");
    return v;
}
__device__ __forceinline__ void st_relaxed4(uint4* p, uint4 v) {
    asm volatile("st.relaxed.gpu.global.v4.u32 [%0], {%1,%2,%3,%4};" :: "l"(p), "r"(v.x), "r"(v.y), "r"(v.z), "r"(v.w) : "memory");
}
__device__ __forceinline__ void st_relaxed1(void* p, uint32_t v) {
    asm volatile("st.relaxed.gpu.global.u32 [%0], %1;" :: "l"(p), "r"(v) : "memory");
}
__device__ __forceinline__ uint32_t umax4(uint4 v) { return max(max(v.x, v.y), max(v.z, v.w)); }
__device__ __forceinline__ void wg_fence() { asm volatile("wgmma.fence.sync.aligned;" ::: "memory"); }
__device__ __forceinline__ void wg_commit() { asm volatile("wgmma.commit_group.sync.aligned;" ::: "memory"); }
template <int N> __device__ __forceinline__ void wg_wait() { asm volatile("wgmma.wait_group.sync.aligned %0;" :: "n"(N) : "memory"); }
template <int N> __device__ __forceinline__ void reg_fence(float* d) {
#pragma unroll
    for (int i = 0; i < N; i++) asm volatile("" : "+f"(d[i]) :: "memory");
}
#define ACC16(d) "+f"(d[0]), "+f"(d[1]), "+f"(d[2]), "+f"(d[3]), "+f"(d[4]), "+f"(d[5]), "+f"(d[6]), "+f"(d[7]), \
                 "+f"(d[8]), "+f"(d[9]), "+f"(d[10]), "+f"(d[11]), "+f"(d[12]), "+f"(d[13]), "+f"(d[14]), "+f"(d[15])
#define DESC_HI_SW128 "0x40000040"
#define OUT16(d) "=f"(d[0]), "=f"(d[1]), "=f"(d[2]), "=f"(d[3]), "=f"(d[4]), "=f"(d[5]), "=f"(d[6]), "=f"(d[7]), \
                 "=f"(d[8]), "=f"(d[9]), "=f"(d[10]), "=f"(d[11]), "=f"(d[12]), "=f"(d[13]), "=f"(d[14]), "=f"(d[15])
template <int ACCUM, int KS>
__device__ __forceinline__ void wg32_rs(float* d, const uint32_t* a, uint32_t db) {
    if (ACCUM)
        asm volatile("{\n.reg .b64 db;\n.reg .b32 tb;\nadd.u32 tb, %20, %21;\nmov.b64 db, {tb, " DESC_HI_SW128 "};\n"
                     "wgmma.mma_async.sync.aligned.m64n32k16.f32.bf16.bf16 {%0,%1,%2,%3,%4,%5,%6,%7,%8,%9,%10,%11,%12,%13,%14,%15}, "
                     "{%16,%17,%18,%19}, db, 1, 1, 1, 0;\n}"
                     : ACC16(d) : "r"(a[0]), "r"(a[1]), "r"(a[2]), "r"(a[3]), "r"(db), "n"((KS >> 2) * 256 + (KS & 3) * 2));
    else
        asm volatile("{\n.reg .b64 db;\n.reg .b32 tb;\nadd.u32 tb, %20, %21;\nmov.b64 db, {tb, " DESC_HI_SW128 "};\n"
                     "wgmma.mma_async.sync.aligned.m64n32k16.f32.bf16.bf16 {%0,%1,%2,%3,%4,%5,%6,%7,%8,%9,%10,%11,%12,%13,%14,%15}, "
                     "{%16,%17,%18,%19}, db, 0, 1, 1, 0;\n}"
                     : OUT16(d) : "r"(a[0]), "r"(a[1]), "r"(a[2]), "r"(a[3]), "r"(db), "n"((KS >> 2) * 256 + (KS & 3) * 2));
}
template <int AOFF, int KS>
__device__ __forceinline__ void wg32_ss(float* d, uint32_t da, uint32_t db) {
    asm volatile("{\n.reg .b64 da, db;\n.reg .b32 ta, tb;\nadd.u32 ta, %16, %18;\nadd.u32 tb, %17, %19;\n"
                 "mov.b64 da, {ta, " DESC_HI_SW128 "};\nmov.b64 db, {tb, " DESC_HI_SW128 "};\n"
                 "wgmma.mma_async.sync.aligned.m64n32k16.f32.bf16.bf16 {%0,%1,%2,%3,%4,%5,%6,%7,%8,%9,%10,%11,%12,%13,%14,%15}, "
                 "da, db, 1, 1, 1, 1, 0;\n}"
                 : ACC16(d) : "r"(da), "r"(db), "n"(AOFF), "n"((KS >> 2) * 256 + (KS & 3) * 2));
}
template <int I>
__device__ __forceinline__ void wg8_ss(float* d, uint32_t da, uint32_t db) {
    if (I == 0)
        asm volatile("{\n.reg .b64 da, db;\nmov.b64 da, {%4, " DESC_HI_SW128 "};\nmov.b64 db, {%5, 0x10};\n"
                     "wgmma.mma_async.sync.aligned.m64n8k16.f32.bf16.bf16 {%0,%1,%2,%3}, da, db, 0, 1, 1, 1, 0;\n}"
                     : "=f"(d[0]), "=f"(d[1]), "=f"(d[2]), "=f"(d[3]) : "r"(da), "r"(db));
    else
        asm volatile("{\n.reg .b64 da, db;\n.reg .b32 ta, tb;\nadd.u32 ta, %4, %6;\nadd.u32 tb, %5, %7;\n"
                     "mov.b64 da, {ta, " DESC_HI_SW128 "};\nmov.b64 db, {tb, 0x10};\n"
                     "wgmma.mma_async.sync.aligned.m64n8k16.f32.bf16.bf16 {%0,%1,%2,%3}, da, db, 1, 1, 1, 1, 0;\n}"
                     : "+f"(d[0]), "+f"(d[1]), "+f"(d[2]), "+f"(d[3]) : "r"(da), "r"(db), "n"(I * 128), "n"(I * 16));
}
template <int I0, int I1, class F>
__device__ __forceinline__ void static_for(F&& f) {
    if constexpr (I0 < I1) { f(std::integral_constant<int, I0>{}); static_for<I0 + 1, I1>(f); }
}
template <int I0, int I1>
__device__ __forceinline__ void wg8_chain(float* d, uint32_t da, uint32_t db) {
    wg_fence();
    static_for<I0, I1>([&](auto i) { wg8_ss<i.value>(d, da, db); });
    wg_commit();
}

__global__ void __launch_bounds__(256) ln_kernel(const __nv_bfloat16* __restrict__ x, const __nv_bfloat16* __restrict__ mem0) {
    const int lane = threadIdx.x & 31, row = blockIdx.x * 8 + (threadIdx.x >> 5);
    const uint4* src = reinterpret_cast<const uint4*>(x + (size_t)row * DM);
    uint4 v[4];
#pragma unroll
    for (int j = 0; j < 4; j++) v[j] = src[j * 32 + lane];
    const int gi = blockIdx.x * 256 + threadIdx.x;
    const uint4 poison = make_uint4(~0u, ~0u, ~0u, ~0u);
    if (gi < 1024) {
        uint4 m = reinterpret_cast<const uint4*>(mem0)[(gi & 7) * 128 + (gi >> 3)];
        if (m.x == ~0u) m.x = 0x7FFF7FFFu;
        if (m.y == ~0u) m.y = 0x7FFF7FFFu;
        if (m.z == ~0u) m.z = 0x7FFF7FFFu;
        if (m.w == ~0u) m.w = 0x7FFF7FFFu;
        g_xmem[0][gi] = m;
    } else if (gi < 4096) {
        (&g_xmem[0][0])[gi] = poison;
    } else if (gi < 4096 + 16384) {
        (&g_xo[0][0])[gi - 4096] = poison;
    } else if (gi < 4096 + 16384 + 48 * FSTR) {
        reinterpret_cast<uint4*>(&g_flag[0][0])[gi - 4096 - 16384] = poison;
    }
    float f[32];
#pragma unroll
    for (int j = 0; j < 4; j++) {
        f[j * 8 + 0] = bf_lo(v[j].x); f[j * 8 + 1] = bf_hi(v[j].x); f[j * 8 + 2] = bf_lo(v[j].y); f[j * 8 + 3] = bf_hi(v[j].y);
        f[j * 8 + 4] = bf_lo(v[j].z); f[j * 8 + 5] = bf_hi(v[j].z); f[j * 8 + 6] = bf_lo(v[j].w); f[j * 8 + 7] = bf_hi(v[j].w);
    }
    float s = 0.f;
#pragma unroll
    for (int i = 0; i < 32; i++) s += f[i];
#pragma unroll
    for (int o = 16; o; o >>= 1) s += __shfl_xor_sync(~0u, s, o);
    const float mean = s * (1.f / DM);
    float q = 0.f;
#pragma unroll
    for (int i = 0; i < 32; i++) { f[i] -= mean; q += f[i] * f[i]; }
#pragma unroll
    for (int o = 16; o; o >>= 1) q += __shfl_xor_sync(~0u, q, o);
    const float r = 1.f / sqrtf(q * (1.f / DM) + 1e-5f);
    uint4* dst = reinterpret_cast<uint4*>(g_xn + (size_t)row * DM);
    uint4* dst2 = g_xc + (row >> 5) * 4096 + (lane >> 3) * 256 + (row & 31) * 8 + ((lane & 7) ^ (row & 7));
#pragma unroll
    for (int j = 0; j < 4; j++) {
        const uint4 o = make_uint4(pack2(f[j * 8] * r, f[j * 8 + 1] * r), pack2(f[j * 8 + 2] * r, f[j * 8 + 3] * r),
                                   pack2(f[j * 8 + 4] * r, f[j * 8 + 5] * r), pack2(f[j * 8 + 6] * r, f[j * 8 + 7] * r));
        dst[j * 32 + lane] = o;
        dst2[(j & 1) * 2048 + (j >> 1) * 1024] = o;
    }
}

constexpr uint32_t C_WS = 0, C_WO = 65536, C_XN = 153600, C_MB = 186368, C_MISC = 202752, C_SMEM = 232448;
constexpr uint32_t C_BAR = C_MISC;
constexpr uint32_t C_RED0 = C_MISC + 256;
constexpr uint32_t C_RED1Q = C_RED0 + 2048, C_QX = C_RED1Q + 2048, C_KX = C_QX + 4096, C_QM = C_KX + 4096, C_KM = C_QM + 1024,
                   C_XSL = C_KM + 1024, C_OL = C_XSL + 5120;
constexpr uint32_t C_V = C_RED0 + 2048, C_PL = C_V + 20480, C_SL = C_PL + 4096, C_RED1V = C_WO + 42 * 2048;
static_assert(C_OL + 3072 <= C_SMEM && C_SL + 2560 <= C_SMEM, "smem overflow");
enum { B_W0 = 0, B_W1, B_W2, B_WS, B_WO, B_XF0, B_XF1, B_XF2, B_SC, B_P0, B_P1, B_XS, B_OL, B_MF0, B_MF1, B_OF, B_RT0, B_RT1, B_NUM };
constexpr uint32_t C_CAL = C_BAR + 192;
constexpr float SM_SCALE = 0.08838834764831845f * 1.4426950408889634f;

#define TSD(i) do {} while (0)
#define TS_PTR(w)
#define TSX(i, c)
#define TS(i)
#define NOFILL 0
#define DLY1 1000
#define DLY2 1500
#define VLEAD 3

#define VEARLY 6
__device__ __forceinline__ bool elect() {
    uint32_t r;
    asm volatile("{\n.reg .pred p;\nelect.sync _|p, 0xffffffff;\nselp.u32 %0, 1, 0, p;\n}" : "=r"(r));
    return r;
}
__device__ __forceinline__ int uni(int v) { return __shfl_sync(~0u, v, 0); }
__device__ __forceinline__ void calibrate(uint32_t cal, float keep) {
    const uint32_t t0 = gtick();
    uint32_t t, it = 0;
    do { t = gtick(); spin_guard(it); } while (t == t0);
    const uint32_t c = clk();
    const uint4 p = lds4u(cal);
    const float cpt = fminf(fmaxf(__fdividef((float)(c - p.y), (float)((t - p.x) & 0x7FFFFFF)), 16.f), 128.f);
    __syncwarp();
    sts4u(cal, make_uint4(t, c, __float_as_uint(keep > 0.f ? fmaf(keep, __uint_as_float(p.z) - cpt, cpt) : cpt), 0));
}
struct Stamps { uint32_t a, b, c; };
__device__ __forceinline__ Stamps load_stamps(const uint32_t* f, uint32_t l16) {
    const char* p = reinterpret_cast<const char*>(f) + (l16 >> 2) * FSTR;
    return Stamps{ld_relaxed1(p), ld_relaxed1(p + 128 * FSTR), ld_relaxed1(p + 256 * FSTR)};
}
__device__ __forceinline__ uint32_t latest_stamp(Stamps v, const uint32_t* f, uint32_t l16, int s, uint32_t cal) {
    const uint4 p = lds4u(cal);
    uint32_t it = 0;
    while (!__all_sync(~0u, (((v.a ^ s) | (v.b ^ s) | (v.c ^ s)) & 63) == 0)) { v = load_stamps(f, l16); spin_guard(it); }
    const uint32_t ref = p.x << 6;
    const int late = __reduce_max_sync(~0u, max(max((int)(v.a - ref), (int)(v.b - ref)), (int)(v.c - ref))) >> 6;
    return p.y + (int)((float)late * __uint_as_float(p.z));
}
__device__ __forceinline__ void wait_clock(uint32_t target) {
    uint32_t it = 0;
    while ((int)(clk() - target) < 0 && ++it < 4096) {}
}

template <int BYTES>
__device__ __forceinline__ bool incomplete(uint32_t buf, uint32_t l16) {
    uint32_t m = 0;
#pragma unroll 1
    for (int o = 0; o < BYTES; o += 256) m = max(m, umax4(lds4u(buf + o + (l16 & 255))));
    return __any_sync(~0u, m == ~0u);
}
__device__ __forceinline__ void refetch(uint32_t buf, const uint4* src, uint32_t bytes, uint32_t b, int w4, int barid, uint32_t& tries) {
    spin_guard(tries);
    bar_sync(barid, 128);
    if (w4 == 0 && elect()) { mbar_expect(b, bytes); bulk_ld(buf, src, bytes, b); }
    __syncwarp();
    mbar_wait(b, 0);
    bar_sync(barid, 128);
    if (w4 == 0 && elect()) mbar_arrive(b);
    __syncwarp();
}

template <bool ISV>
__device__ __forceinline__ void chain_main(const CUtensorMap* tA, const CUtensorMap* tB, const CUtensorMap* tWo,
                                           const uint32_t sb, const int cl, const int rank) {
    const int tid = threadIdx.x;
    uint32_t l16_ = __shfl_sync(~0u, (tid & 31) * 16, tid & 31);
    const int warp = uni(tid >> 5), wg = warp >> 2, w4 = warp & 3;
    const int role = uni(rank % 3), head = 2 * cl + (rank >= 3);
    const uint32_t bar = sb + C_BAR;
    constexpr int ONK = ISV ? 42 : 43;
    const int ostart = uni(rank * 43 - (rank >= 3));

    uint32_t wk[24][4], wv[24][4];
    uint32_t a_adr, lane_b;
    {
        const int colA = head * 128 + (ISV ? 0 : role * 64), colB = head * 128 + (ISV ? 64 : role * 64);
        auto load_chunk = [&](uint32_t dst, int j, uint32_t b) {
            mbar_expect(b, 65536);
            tma2d(dst, tA, colA, j * 128, b);
            tma2d(dst + 16384, tB, colB, j * 128, b);
            tma2d(dst + 32768, tB, colB, 512 + j * 128, b);
            tma2d(dst + 49152, tA, colA, 512 + j * 128, b);
        };
        if (tid == 0)
            for (int j = 0; j < 3; j++) load_chunk(sb + j * 65536, j, bar + (B_W0 + j) * 8);
        if (warp == 4) calibrate(sb + C_CAL, 0.f);
        const int lane = tid & 31, kr = (lane & 7) + ((lane >> 4) << 3), rr = lane & 7;
        a_adr = __shfl_sync(~0u, sb + wg * 32768 + kr * 128 + (((w4 * 2 + ((lane >> 3) & 1)) ^ (kr & 7)) << 4), lane);
        if (ISV) {
            lane_b = sb + C_V + w4 * 2560 + rr * 80 + (lane >> 3) * 16;
        } else {
            lane_b = sb + C_QM + ((lane >> 4) + ((lane >> 3) & 1) * 4) * 128 + rr * 16;
        }
        lane_b = __shfl_sync(~0u, lane_b, lane);
#pragma unroll
        for (int j = 0; j < 3; j++) {
            mbar_wait(bar + (B_W0 + j) * 8, 0);
#pragma unroll
            for (int i = 0; i < 8; i++) {
                ldsm4t(wk[j * 8 + i], a_adr + j * 65536 + i * 2048);
                ldsm4t(wv[j * 8 + i], a_adr + j * 65536 + 16384 + i * 2048);
            }
            if (j != 1) {
                bar_sync(6, 256);
                if (j == 0) {
                    if (tid == 0) load_chunk(sb + C_WS, 3, bar + B_WS * 8);
                } else if (warp == 0) {
                    if (lane == 0) mbar_expect(bar + B_WO * 8, ONK * 2048);
                    __syncwarp();
                    for (int i = lane; i < ONK; i += 32) tma2d(sb + C_WO + i * 2048, tWo, cl * 64, (ostart + i) * 16, bar + B_WO * 8);
                }
            }
        }
        if (NOFILL) { for (uint32_t o = C_RED0 + tid * 16; o < C_SMEM; o += 4096) sts4u(sb + o, make_uint4(0, 0, 0, 0)); bar_sync(6, 256); }
        asm volatile("griddepcontrol.wait;" ::: "memory");
        asm volatile("griddepcontrol.launch_dependents;" ::: "memory");
        if (warp == 4) calibrate(sb + C_CAL, 0.f);
    }

    constexpr uint32_t RED1 = ISV ? C_RED1V : C_RED1Q;
    const uint32_t sbw = uni(sb + w4 * 512);
    const uint32_t red_out = uni(wg ? RED1 : C_RED0), red_in = uni(wg ? C_RED0 : RED1);
    const uint32_t mbw = uni(sb + C_MB + wg * 8192);
    const uint32_t xn_desc = uni((((sb + C_XN + wg * 16384) & 0x3FFFF) >> 4) | (1u << 16));
    const uint32_t ws_desc = uni((((sb + C_WS + wg * 32768) & 0x3FFFF) >> 4) | (1u << 16));
    const uint32_t sb_v = uni(mapa(sb, rank - role + 2));
    const uint32_t sb_x = uni(mapa(sb, rank - role + (warp >= 3)));
    const uint32_t sb_o = uni(mapa(sb, w4 + (w4 >> 1)));
    const uint32_t u_off = uni(ISV ? (head * 128 + w4 * 32) * 16 : (cl * 4 + rank - (rank >= 3)) * 256 + (w4 & 1) * 128);
    const uint32_t v_row = uni(sb + C_V + (32 * (warp >> 1) + 4 * (warp & 1)) * 80);
    uint32_t* const my_flag = &g_flag[0][blockIdx.x * FSTR];
    auto load_tokens = [&](int seg, int khalf, uint32_t off, uint32_t bytes, int b) {
        if (!NOFILL && w4 == 3 && elect()) {
            mbar_expect(bar + b * 8, bytes);
            bulk_ld(sb + C_XN + wg * 16384 + off, g_xc + (seg * 4 + khalf * 2 + wg) * 1024 + off / 16, bytes, bar + b * 8);
        }
    };
    auto tokens_a_late = [&](int seg) { load_tokens(seg, 1, wg * 8192, 16384 - wg * 8192, B_XF0 + 2 * wg); };
    if (wg == 1) load_tokens(0, 1, 0, 8192, B_XF1);
    tokens_a_late(0);
    uint32_t pf[4][4];
    auto prefetch = [&]() {
#pragma unroll
        for (int i = 0; i < 4; i++) ldsm4t(pf[i], a_adr + C_WS + (i & 1) * 16384 + (i >> 1) * 2048);
    };
    mbar_wait(bar + B_WS * 8, 0);
    prefetch();

    int s = -1;
#pragma unroll 1
    for (;; s = uni(s + 1)) {
        asm volatile("" : "+r"(l16_), "+r"(lane_b), "+r"(a_adr));
        const uint32_t l16 = l16_;
        const int lane = l16 >> 4;
        TS_PTR(wg);
        TS(0);
            auto stamp = [&]() {
                if (warp == 7) {
                    const uint32_t dep = lds2u(sb + C_CAL + 8).y;
                    const uint32_t v = ((gtick_dep(dep) - (ISV ? VLEAD : 0)) << 6) | s;
                    if (elect()) st_relaxed1(my_flag, v);
                }
                if (s < NSEG - 1) tokens_a_late(s + 1);
            };
        auto token_softmax = [&]() {
            if (!NOFILL && warp >= 6) {
                const int hi = warp - 6;
                const uint32_t src = sb + C_XSL + l16 + hi * 8;
                const int d0 = 16 * role + 8 * hi + (lane >> 2) - 2 * (lane & 3);
                mbar_wait(bar + B_XS * 8, s & 1);
                float e[10];
                float m = -INFINITY;
#pragma unroll
                for (int i = 0; i < 5; i++) {
                    __syncwarp();
                    const float2 a = lds2f(src + i * 512), b = lds2f(src + 2560 + i * 512);
                    e[2 * i] = (i == 0 || d0 >= 8 * (i - 1)) ? a.x + b.x : -INFINITY;
                    e[2 * i + 1] = (i == 0 || d0 > 8 * (i - 1)) ? a.y + b.y : -INFINITY;
                    m = fmaxf(m, fmaxf(e[2 * i], e[2 * i + 1]));
                }
                m = fmaxf(m, __shfl_xor_sync(~0u, m, 1));
                m = fmaxf(m, __shfl_xor_sync(~0u, m, 2));
                m *= -SM_SCALE;
                float l = 0.f;
#pragma unroll
                for (int i = 0; i < 10; i++) { e[i] = ex2(fmaf(e[i], SM_SCALE, m)); l += e[i]; }
                l += __shfl_xor_sync(~0u, l, 1);
                l += __shfl_xor_sync(~0u, l, 2);
                l = rcp(l);
                const uint32_t pd = sb_v + C_PL + (s & 1) * 2048 + role * 768 + hi * 4, pb = sb_v + C_BAR + (B_P0 + (s & 1)) * 8;
                st_async1(pd + (l16 >> 1), pb, pack2(e[0] * l, e[1] * l));
                st_async1(pd + 256 + l16, pb, pack2(e[2] * l, e[3] * l));
                st_async1(pd + 264 + l16, pb, pack2(e[4] * l, e[5] * l));
                if (role) {
                    st_async1(pd + 768 + l16, pb, pack2(e[6] * l, e[7] * l));
                    st_async1(pd + 776 + l16, pb, pack2(e[8] * l, e[9] * l));
                }
                if (hi == 0 && elect()) mbar_expect(bar + B_XS * 8, 3072 + role * 2048);
            }
        };
        if (s >= 0) {
            float ck[4], cv[4];
            uint32_t tries = 0;
            const uint32_t can = mbw + l16 * 8 + (l16 >> 2);
            mbar_wait(bar + (B_MF0 + wg) * 8, s & 1);
            TS(1);
            while (true) {
                uint32_t b[2][4];
                ldsm4(b[0], mbw + l16 + 12 * 512);
                const uint32_t c0 = lds1u(can), c1 = lds1u(can + 4096);
                bool bad = false;
#pragma unroll
                for (int i = 0; i < 4; i++) ck[i] = cv[i] = 0.f;
#pragma unroll
                for (int kp = 0; kp < 16; kp++) {
                    const int grp = kp / 5, ph = kp % 5, nx = kp + 1;
                    if (nx < 16) ldsm4(b[nx & 1], mbw + l16 + ((nx % 5) ? (nx / 5) * 4 + (nx % 5) - 1 : 12 + nx / 5) * 512);
                    const uint32_t* bb = b[kp & 1];
                    if (ph) {
                        const int q = (grp * 4 + ph - 1) * 2, i = ph - 1;
                        ldsm4t(pf[i], a_adr + C_WS + (i & 1) * 16384 + (grp * 2 + 2 + (i >> 1)) * 2048);
                        mma16(cv, wv[q][0], wv[q][1], wv[q][2], wv[q][3], bb[0], bb[1]);
                        mma16(ck, wk[q][0], wk[q][1], wk[q][2], wk[q][3], bb[0], bb[1]);
                        mma16(cv, wv[q + 1][0], wv[q + 1][1], wv[q + 1][2], wv[q + 1][3], bb[2], bb[3]);
                        mma16(ck, wk[q + 1][0], wk[q + 1][1], wk[q + 1][2], wk[q + 1][3], bb[2], bb[3]);
                    } else {
                        mma16(cv, pf[1][0], pf[1][1], pf[1][2], pf[1][3], bb[0], bb[1]);
                        mma16(ck, pf[0][0], pf[0][1], pf[0][2], pf[0][3], bb[0], bb[1]);
                        mma16(cv, pf[3][0], pf[3][1], pf[3][2], pf[3][3], bb[2], bb[3]);
                        mma16(ck, pf[2][0], pf[2][1], pf[2][2], pf[2][3], bb[2], bb[3]);
                    }
                    if (kp == 0) {
                        bad = __any_sync(~0u, max(c0, c1) == ~0u);
                        if (bad) break;
                    }
                }
                if (!bad) {
                    sts4f(sbw + red_out + l16, cv[0], cv[1], cv[2], cv[3]);
                    if (!any_nan(cv[0], cv[1])) break;
                    if (!incomplete<8192>(mbw, l16)) break;
                }
                refetch(mbw, &g_xmem[s & 3][wg * 512], 8192, bar + (B_RT0 + wg) * 8, w4, 1 + wg, tries);
                prefetch();
            }
            TS(2);
            if (!ISV) {
                const uint32_t lane_a = sb + C_KX + ((l16 & 384) << 2) + (l16 & 112);
                auto finish = [&]() {
                    bar_sync(6, 256);
                    const float4 r = lds4f(sbw + red_in + l16);
                    stsm2t(sb + C_QM + warp * 256 + (l16 & 255), pack2(ck[0] + r.x, ck[1] + r.y), pack2(ck[2] + r.z, ck[3] + r.w));
                    bar_sync(6, 256);
                    TSX(3, warp == 0);
                };
                if (warp < 2) {
                    uint32_t k0[2][4], k1[2][4], q0[4], q1[4];
                    const uint32_t kl = lane_a + warp * 256, dst = sb_v + C_SL + role * 1280 + warp * 512 + l16;
                    ldsm4(k0[0], kl); ldsm4(k0[1], kl + 2048);
                    ldsm4(k1[0], kl + 128); ldsm4(k1[1], kl + 128 + 2048);
                    finish();
                    ldsm4(q0, lane_b); ldsm4(q1, lane_b + 256);
                    float s0[4] = {0.f, 0.f, 0.f, 0.f}, s1[4] = {0.f, 0.f, 0.f, 0.f}, s2[4] = {0.f, 0.f, 0.f, 0.f}, s3[4] = {0.f, 0.f, 0.f, 0.f};
                    mma16(s0, q0[0], q0[1], q0[2], q0[3], k0[0][0], k0[0][1]);
                    mma16(s1, q0[0], q0[1], q0[2], q0[3], k0[1][0], k0[1][1]);
                    mma16(s2, q0[0], q0[1], q0[2], q0[3], k1[0][0], k1[0][1]);
                    mma16(s3, q0[0], q0[1], q0[2], q0[3], k1[1][0], k1[1][1]);
                    mma16(s0, q1[0], q1[1], q1[2], q1[3], k0[0][2], k0[0][3]);
                    mma16(s1, q1[0], q1[1], q1[2], q1[3], k0[1][2], k0[1][3]);
                    mma16(s2, q1[0], q1[1], q1[2], q1[3], k1[0][2], k1[0][3]);
                    mma16(s3, q1[0], q1[1], q1[2], q1[3], k1[1][2], k1[1][3]);
                    st_async4(dst, sb_v + C_BAR + B_SC * 8, __float_as_uint(s0[0] + s1[2]), __float_as_uint(s0[1] + s1[3]),
                                  __float_as_uint(s2[0] + s3[2]), __float_as_uint(s2[1] + s3[3]));
                } else if (warp == 2) {
                    uint32_t q0[4], q1[4], m0[4], m1[4];
                    const uint32_t dst = sb_v + C_SL + role * 1280 + 1024 + (l16 >> 1);
                    finish();
                    ldsm4(q0, lane_b); ldsm4(m0, sb + C_KM + l16); ldsm4(m1, sb + C_KM + 512 + l16); ldsm4(q1, lane_b + 256);
                    float s0[4] = {0.f, 0.f, 0.f, 0.f}, s1[4] = {0.f, 0.f, 0.f, 0.f};
                    mma16(s0, q0[0], q0[1], q0[2], q0[3], m0[0], m0[1]);
                    mma16(s1, q0[0], q0[1], q0[2], q0[3], m1[0], m1[1]);
                    mma16(s0, q1[0], q1[1], q1[2], q1[3], m0[2], m0[3]);
                    mma16(s1, q1[0], q1[1], q1[2], q1[3], m1[2], m1[3]);
                    st_async2(dst, sb_v + C_BAR + B_SC * 8, __float_as_uint(s0[0] + s1[2]), __float_as_uint(s0[1] + s1[3]));
                } else {
                    finish();
                    stamp();
                }
                TSX(4, warp == 0);
                if (!NOFILL) {
                    const int mh = warp >= 3, ti = warp - 3 * mh;
                    const uint32_t ka = ti ? lane_a + (ti - 1) * 128 : sb + C_KM + l16;
                    const uint32_t qx = sb + C_QX + mh * 256 + l16 + (l16 & 256);
                    uint32_t k[2][4], q[4][4];
                    ldsm4(k[0], ka); ldsm4(k[1], ka + (ti ? 2048 : 512));
#pragma unroll
                    for (int i = 0; i < 4; i++) ldsm4(q[i], qx + i * 1024);
                    float s0[4] = {0.f, 0.f, 0.f, 0.f};
#pragma unroll
                    for (int i = 0; i < 4; i++) mma16(s0, q[i][0], q[i][1], q[i][2], q[i][3], k[i >> 1][(i & 1) * 2], k[i >> 1][(i & 1) * 2 + 1]);
                    bar_sync(6, 256);
                    st_async4(sb_x + C_XSL + role * 2560 + ti * 512 + l16, sb_x + C_BAR + B_XS * 8,
                              __float_as_uint(s0[0]), __float_as_uint(s0[1]), __float_as_uint(s0[2]), __float_as_uint(s0[3]));
                }
                if (s == NSEG - 1) { token_softmax(); break; }
            } else {
                const uint32_t d = v_row + (s & 1) * 10240 + 64 + (l16 & 96) * 20 + ((l16 & 16) + ((l16 & 128) >> 2)) * 5;
                bar_sync(6, 256);
                const float4 r = lds4f(sbw + red_in + l16);
                stsm2(d, pack2(ck[0] + r.x, ck[1] + r.y), pack2(ck[2] + r.z, ck[3] + r.w));
                if (wg == 0) bar_arrive(11, 256);
                else bar_arrive(6, 256);
                TSX(3, warp == 0);
            }
        }
        if (ISV) {
            auto load_values = [&](uint32_t (*vx)[4], uint32_t* vm, int ss) {
#pragma unroll
                for (int j = 0; j < 4; j++) ldsm4(vx[j], lane_b + (ss & 1) * 10240 + j * 640);
                ldsm4(vm, sb + C_V + (ss & 1) * 10240 + w4 * 2560 + 64 + l16 * 5);
            };
            auto token_output = [&](int ss) {
                uint32_t vx[4][4], vm[4];
                TSD(6);
                load_values(vx, vm, ss);
                const uint32_t pb = bar + (B_P0 + (ss & 1)) * 8, pl = sb + C_PL + (ss & 1) * 2048 + wg * 768;
                char* orow = reinterpret_cast<char*>(g_ox) + ((ss * 2 + wg) * (16 * HD * 2) + (u_off >> 3) + (l16 >> 6) * (HD * 2) + (l16 & 48));
                mbar_wait(pb, (ss >> 1) & 1);
                float o[4][4];
                const uint2 pm = lds2u(pl + (l16 >> 1));
                const uint4 p0 = lds4u(pl + 256 + l16), p1 = lds4u(pl + 768 + l16);
#pragma unroll
                for (int j = 0; j < 4; j++) { o[j][0] = o[j][1] = o[j][2] = o[j][3] = 0.f; mma8(o[j], pm.x, pm.y, vm[j]); }
#pragma unroll
                for (int j = 0; j < 4; j++) mma16(o[j], p0.x, p0.y, p0.z, p0.w, vx[j][0], vx[j][1]);
                if (wg) {
#pragma unroll
                    for (int j = 0; j < 4; j++) mma16(o[j], p1.x, p1.y, p1.z, p1.w, vx[j][2], vx[j][3]);
                }
                *reinterpret_cast<uint4*>(orow) =
                    make_uint4(pack2(o[0][0], o[0][1]), pack2(o[1][0], o[1][1]), pack2(o[2][0], o[2][1]), pack2(o[3][0], o[3][1]));
                *reinterpret_cast<uint4*>(orow + 8 * HD * 2) =
                    make_uint4(pack2(o[0][2], o[0][3]), pack2(o[1][2], o[1][3]), pack2(o[2][2], o[2][3]), pack2(o[3][2], o[3][3]));
                if (warp == 5 && elect()) mbar_expect(pb, 2048);
                TSD(7);
            };
            if (s >= 1 && !NOFILL) token_output(s - 1);
            if (s >= 0) {
                if (wg == 0) bar_sync(6, 256);
                else bar_sync(11, 256);
                stamp();
            }
            if (s == NSEG - 1) {
                if (!NOFILL) token_output(s);
                mbar_wait(bar + B_SC * 8, s & 1);
                break;
            }
            if (wg == 0) {
                if (s >= 0) {
                    uint32_t vx[4][4], vm[4];
                    load_values(vx, vm, s);
                    const uint32_t oo = u_off + ((l16 & 48) << 3) + ((l16 >> 2) & 112);
                    char* dst = reinterpret_cast<char*>(&g_xo[s & 3][0]) + oo;
                    st_relaxed4(reinterpret_cast<uint4*>(reinterpret_cast<char*>(&g_xo[(s + 2) & 3][0]) + oo), make_uint4(~0u, ~0u, ~0u, ~0u));
                    mbar_wait(bar + B_SC * 8, s & 1);
                    TS(4);
                    const float4 a0 = lds4f(sb + C_SL + l16), b0 = lds4f(sb + C_SL + 1280 + l16);
                    const float4 a1 = lds4f(sb + C_SL + 512 + l16), b1 = lds4f(sb + C_SL + 1280 + 512 + l16);
                    const float2 a2 = lds2f(sb + C_SL + 1024 + (l16 >> 1)), b2 = lds2f(sb + C_SL + 1280 + 1024 + (l16 >> 1));
                    const float e[10] = {a0.x + b0.x, a0.y + b0.y, a0.z + b0.z, a0.w + b0.w, a1.x + b1.x, a1.y + b1.y, a1.z + b1.z, a1.w + b1.w,
                                         a2.x + b2.x, a2.y + b2.y};
                    float m = fmaxf(fmaxf(fmaxf(e[0], e[1]), fmaxf(e[2], e[3])), fmaxf(fmaxf(e[4], e[5]), fmaxf(e[6], e[7])));
                    m = fmaxf(m, fmaxf(e[8], e[9]));
                    m = fmaxf(fmaxf(m, __shfl_xor_sync(~0u, m, 1)), fmaxf(__shfl_xor_sync(~0u, m, 2), __shfl_xor_sync(~0u, m, 3)));
                    m *= -SM_SCALE;
                    float x[10];
#pragma unroll
                    for (int i = 0; i < 10; i++) x[i] = ex2(fmaf(e[i], SM_SCALE, m));
                    float o[4][4];
                    const uint32_t p0 = pack2(x[0], x[1]), p1 = pack2(x[2], x[3]), j0 = __float_as_uint(x[1]), j1 = __float_as_uint(x[3]);
#pragma unroll
                    for (int j = 0; j < 4; j++) { o[j][0] = o[j][1] = o[j][2] = o[j][3] = 0.f; mma16(o[j], p0, j0, p1, j1, vx[j][0], vx[j][1]); }
                    const uint32_t p2 = pack2(x[4], x[5]), p3 = pack2(x[6], x[7]), j2 = __float_as_uint(x[5]), j3 = __float_as_uint(x[7]);
#pragma unroll
                    for (int j = 0; j < 4; j++) mma16(o[j], p2, j2, p3, j3, vx[j][2], vx[j][3]);
                    const uint32_t p4 = pack2(x[8], x[9]), j4 = __float_as_uint(x[9]);
                    float l = (((x[0] + x[1]) + (x[2] + x[3])) + ((x[4] + x[5]) + (x[6] + x[7]))) + (x[8] + x[9]);
                    l = (l + __shfl_xor_sync(~0u, l, 1)) + (__shfl_xor_sync(~0u, l, 2) + __shfl_xor_sync(~0u, l, 3));
#pragma unroll
                    for (int j = 0; j < 4; j++) mma8(o[j], p4, j4, vm[j]);
                    l = rcp(l);
                    st_relaxed4(reinterpret_cast<uint4*>(dst), make_uint4(pack2(o[0][0] * l, o[0][1] * l), pack2(o[1][0] * l, o[1][1] * l),
                                                                          pack2(o[2][0] * l, o[2][1] * l), pack2(o[3][0] * l, o[3][1] * l)));
                    if (w4 == 0 && elect()) mbar_expect(bar + B_SC * 8, 2560);
                }
                bar_arrive(3, 256);
            }
        }
        TS(5);
        float xk[16], xv[16];
        {
            constexpr int NE = ISV ? VEARLY : 8;
            if (!NOFILL) {
                mbar_wait(bar + (B_XF0 + wg) * 8, 0);
                if (wg == 0) bar_sync(7, 256);
                TS(6);
                wg_fence();
                static_for<0, NE>([&](auto i) {
                    wg32_rs<i.value != 0, i.value>(xk, wk[16 + i.value], xn_desc);
                    wg32_rs<i.value != 0, i.value>(xv, wv[16 + i.value], xn_desc);
                });
                wg_commit();
            }
            Stamps st = {63u, 63u, 63u};
            if (wg == 1) {
                if (NOFILL) wait_clock(clk() + 400);
                if (w4 == 0) st = load_stamps(g_flag[0], l16);
                if (ISV) bar_sync(3, 256);
                if (!NOFILL) mbar_wait(bar + B_XF2 * 8, (s + 1) & 1);
            }
            if (!NOFILL) {
                wg_fence();
                static_for<NE, 8>([&](auto i) {
                    wg32_rs<1, i.value>(xk, wk[16 + i.value], xn_desc);
                    wg32_rs<1, i.value>(xv, wv[16 + i.value], xn_desc);
                });
                static_for<0, 8>([&](auto i) {
                    wg32_ss<i.value * 128, 8 + i.value>(xk, ws_desc, xn_desc);
                    wg32_ss<1024 + i.value * 128, 8 + i.value>(xv, ws_desc, xn_desc);
                });
                wg_commit();
                if (wg == 1) bar_arrive(7, 256);
            }
            uint32_t target = 0;
            if (warp == 4 && s >= 0) {
                target = latest_stamp(st, g_flag[0], l16, s, sb + C_CAL) + DLY1;
                if (elect()) mbar_expect(bar + B_OF * 8, ONK * 256);
                TS(10);
            }
            if (!NOFILL) {
                wg_wait<0>();
                reg_fence<16>(xk); reg_fence<16>(xv);
                if (wg == 1) {
                    if (w4 == 3) bar_sync(2, 128); else bar_arrive(2, 128);
                    load_tokens(s + 1, 0, 0, 16384, B_XF1);
                }
            }
            TS(7);
            if (warp == 4 && s >= 0) {
                const uint4* src = &g_xo[s & 3][ostart * 16];
                wait_clock(target);
                if (elect()) bulk_ld(sb + C_MB, src, ONK * 256, bar + B_OF * 8);
                TS(8);
            }
        }
        if (s >= 0) {
            if (wg == 0) {
                const uint32_t dst = sb_o + C_OL + rank * 512 + l16;
                float co[4];
                const uint32_t can = sb + C_MB + l16 * 8 + (l16 >> 2), can2 = can + (lane < ONK * 2 - 64 ? 8192 : 0);
                const uint32_t da = (((sb + C_WO) & 0x3FFFF) >> 4) | (1u << 16), db = (((sb + C_MB) & 0x3FFFF) >> 4) | (8u << 16);
                uint32_t tries = 0;
                bool stamped = false;
                mbar_wait(bar + B_OF * 8, s & 1);
                TS(8);
                while (true) {
                    const uint32_t c0 = lds1u(can), c1 = lds1u(can + 4096), c2 = lds1u(can2);
                    wg8_chain<0, 6>(co, da, db);
                    if (!__any_sync(~0u, max(max(c0, c1), c2) == ~0u)) {
                        if (!stamped) bar_arrive(4, 160);
                        stamped = true;
                        wg8_chain<6, ONK>(co, da, db);
                        wg_wait<0>();
                        reg_fence<4>(co);
                        if (!any_nan(co[0], co[1])) break;
                        if (!incomplete<ONK * 256>(sb + C_MB, l16)) break;
                    }
                    wg_wait<0>();
                    refetch(sb + C_MB, &g_xo[s & 3][ostart * 16], ONK * 256, bar + B_RT0 * 8, w4, 1, tries);
                }
                st_async4(dst, sb_o + C_BAR + B_OL * 8, __float_as_uint(co[0]), __float_as_uint(co[1]), __float_as_uint(co[2]), __float_as_uint(co[3]));
                TS(9);
            } else if (w4 == 0) {
                bar_sync(4, 160);
                const uint32_t dep = lds2u(sb + C_CAL + 8).y;
                const uint32_t v = (gtick_dep(dep) << 6) | s;
                if (elect()) st_relaxed1(my_flag + 96 * FSTR, v);
                calibrate(sb + C_CAL, 0.75f);
            } else if (!ISV) {
                token_softmax();
                TSX(9, w4 == 2);
            }
        } else {
            mbar_wait(bar + B_WO * 8, 0);
        }
        Stamps st = {63u, 63u, 63u};
        if (wg == 0) {
            if (w4 == 3) bar_sync(5, 256); else bar_arrive(5, 256);
            load_tokens(s + 1, 0, 0, 16384, B_XF0);
            if (!ISV && w4 < 2 && s >= 0) {
                const uint32_t off = u_off + (l16 >> 2), src = sb + C_OL + l16 + w4 * 8;
                char* dst = reinterpret_cast<char*>(&g_xmem[(s + 1) & 3][0]) + off;
                mbar_wait(bar + B_OL * 8, s & 1);
                const float2 a = lds2f(src), b = lds2f(src + 512), c = lds2f(src + 1024), d = lds2f(src + 1536), e = lds2f(src + 2048), f = lds2f(src + 2560);
                st_relaxed1(dst, movm(pack2((a.x + b.x) + (c.x + d.x) + (e.x + f.x), (a.y + b.y) + (c.y + d.y) + (e.y + f.y))));
                TS(10);
                st_relaxed1(reinterpret_cast<char*>(&g_xmem[(s + 3) & 3][0]) + off, ~0u);
                if (w4 == 0 && elect()) mbar_expect(bar + B_OL * 8, 3072);
            }
        } else {
            bar_sync(5, 256);
            if (w4 == 0) st = load_stamps(g_flag[1], l16);
        }
        TS(11);
        if (!NOFILL) {
            mbar_wait(bar + (B_XF0 + wg) * 8, 1);
            if (wg == 0) bar_sync(7, 256);
            TS(12);
        }
        const uint32_t slot = sbw + C_XN + 24576 + l16;
        auto store_tokens = [&](const float4* r) {
            uint32_t lo[4], hi[4];
#pragma unroll
            for (int j = 0; j < 4; j++) {
                lo[j] = pack2(xk[4 * j] + r[j].x, xk[4 * j + 1] + r[j].y);
                hi[j] = pack2(xk[4 * j + 2] + r[j].z, xk[4 * j + 3] + r[j].w);
            }
            if (!ISV) {
                const uint32_t d = sb + C_QX + warp * 1024 + l16;
                stsm4t(d, lo[0], lo[1], lo[2], lo[3]);
                stsm4t(d + 512, hi[0], hi[1], hi[2], hi[3]);
            } else {
                uint32_t lf = l16;
                asm volatile("" : "+r"(lf));
                const uint32_t d = v_row + ((s + 1) & 1) * 10240 + (lf & 96) * 20 + (lf & 16) * 5 + ((lf >> 3) & 48);
                stsm4(d, lo[0], lo[1], lo[2], lo[3]);
                stsm4(d + 160, hi[0], hi[1], hi[2], hi[3]);
            }
        };
        if (wg == 1) {
            if (!NOFILL) {
                wg_fence();
                static_for<0, 16>([&](auto i) {
                    wg32_rs<1, i.value>(xv, wv[i.value], xn_desc);
                    wg32_rs<1, i.value>(xk, wk[i.value], xn_desc);
                });
                wg_commit();
                bar_arrive(7, 256);
                wg_wait<0>();
                reg_fence<16>(xk); reg_fence<16>(xv);
                bar_sync(2, 128);
#pragma unroll
                for (int j = 0; j < 4; j++) sts4f(slot + j * 2048, xv[4 * j], xv[4 * j + 1], xv[4 * j + 2], xv[4 * j + 3]);
                bar_arrive(8, 256);
                if (s < NSEG - 2) load_tokens(s + 2, 1, 0, 8192, B_XF1);
            }
            TS(13);
            if (w4 == 0) {
                uint32_t target = 0;
                if (s >= 0) target = latest_stamp(st, g_flag[1], l16, s, sb + C_CAL) + DLY2;
                const uint4* src = &g_xmem[(s + 1) & 3][0];
                if (elect()) {
                    mbar_expect(bar + B_MF0 * 8, 8192);
                    mbar_expect(bar + B_MF1 * 8, 8192);
                }
                TS(3);
                if (s >= 0) wait_clock(target);
                if (elect()) {
                    bulk_ld(sb + C_MB, src, 8192, bar + B_MF0 * 8);
                    bulk_ld(sb + C_MB + 8192, src + 512, 8192, bar + B_MF1 * 8);
                }
                TS(4);
            }
            if (!NOFILL) {
                bar_sync(9, 256);
                float4 r[4];
#pragma unroll
                for (int j = 0; j < 4; j++) r[j] = lds4f(slot + j * 2048);
                store_tokens(r);
            }
            if (!ISV) bar_arrive(10, 256);
            prefetch();
        } else {
            if (!NOFILL) {
                wg_fence();
                static_for<0, 16>([&](auto i) { wg32_rs<1, i.value>(xv, wv[i.value], xn_desc); });
                wg_commit();
                static_for<0, 6>([&](auto i) { wg32_rs<1, i.value>(xk, wk[i.value], xn_desc); });
                wg_commit();
                bar_sync(8, 256);
                float4 r[4];
#pragma unroll
                for (int j = 0; j < 4; j++) r[j] = lds4f(slot + j * 2048);
                wg_wait<1>();
                reg_fence<16>(xv);
#pragma unroll
                for (int j = 0; j < 4; j++) sts4f(slot + j * 2048, xv[4 * j], xv[4 * j + 1], xv[4 * j + 2], xv[4 * j + 3]);
                bar_arrive(9, 256);
                static_for<6, 16>([&](auto i) { wg32_rs<1, i.value>(xk, wk[i.value], xn_desc); });
                wg_commit();
                prefetch();
                wg_wait<0>();
                reg_fence<16>(xk);
                TS(13);
                store_tokens(r);
            } else {
                prefetch();
            }
            if (!ISV) bar_sync(10, 256);
        }
    }
}

__global__ void __cluster_dims__(6, 1, 1) __launch_bounds__(256, 1)
chain_kernel(const __grid_constant__ CUtensorMap tq, const __grid_constant__ CUtensorMap tk, const __grid_constant__ CUtensorMap tv,
             const __grid_constant__ CUtensorMap two) {
    extern __shared__ __align__(1024) uint8_t smem[];
    const uint32_t sb = smem_u32(smem);
    const int rank = blockIdx.x % 6, cl = blockIdx.x / 6, role = rank % 3;
    if (threadIdx.x == 0) {
        const uint32_t bar = sb + C_BAR;
        for (int i = 0; i < B_NUM; i++) mbar_init(bar + i * 8, 1);
        if (role == 2) {
            mbar_expect(bar + B_SC * 8, 2560);
            mbar_expect(bar + B_P0 * 8, 2048);
            mbar_expect(bar + B_P1 * 8, 2048);
        } else {
            mbar_expect(bar + B_XS * 8, role ? 5120 : 3072);
            mbar_expect(bar + B_OL * 8, 3072);
        }
        asm volatile("fence.mbarrier_init.release.cluster;" ::: "memory");
        fence_async();
    }
    __syncthreads();
    cluster_sync();
    if (role == 2) chain_main<true>(&tv, &tv, &two, sb, cl, rank);
    else chain_main<false>(&tq, &tk, &two, sb, cl, rank);
    __syncwarp();
    cluster_sync();
}

constexpr int G_STAGES = 4;
constexpr uint32_t G_STAGE = 49152, G_EPI = G_STAGES * G_STAGE, G_BAR = G_EPI + 32768, G_SMEM = G_BAR + 256;

__device__ __forceinline__ void wg256(float* d, uint32_t da, uint32_t db, uint32_t accum) {
    asm volatile("{\n.reg .b64 da, db;\n.reg .pred p;\nsetp.ne.u32 p, %130, 0;\nmov.b64 da, {%128, " DESC_HI_SW128 "};\nmov.b64 db, {%129, " DESC_HI_SW128 "};\n"
                 "wgmma.mma_async.sync.aligned.m64n256k16.f32.bf16.bf16 {"
                 "%0,%1,%2,%3,%4,%5,%6,%7,%8,%9,%10,%11,%12,%13,%14,%15,%16,%17,%18,%19,%20,%21,%22,%23,%24,%25,%26,%27,%28,%29,%30,%31,"
                 "%32,%33,%34,%35,%36,%37,%38,%39,%40,%41,%42,%43,%44,%45,%46,%47,%48,%49,%50,%51,%52,%53,%54,%55,%56,%57,%58,%59,%60,%61,%62,%63,"
                 "%64,%65,%66,%67,%68,%69,%70,%71,%72,%73,%74,%75,%76,%77,%78,%79,%80,%81,%82,%83,%84,%85,%86,%87,%88,%89,%90,%91,%92,%93,%94,%95,"
                 "%96,%97,%98,%99,%100,%101,%102,%103,%104,%105,%106,%107,%108,%109,%110,%111,%112,%113,%114,%115,%116,%117,%118,%119,%120,%121,%122,%123,%124,%125,%126,%127"
                 "}, da, db, p, 1, 1, 0, 1;\n}"
                 : ACC16(d), ACC16((d + 16)), ACC16((d + 32)), ACC16((d + 48)), ACC16((d + 64)), ACC16((d + 80)), ACC16((d + 96)), ACC16((d + 112))
                 : "r"(da), "r"(db), "r"(accum));
}
__device__ __forceinline__ float sigmoidf_(float v) { return rcp(1.f + ex2(-1.4426950408889634f * v)); }

template <int MODE>
__global__ void __cluster_dims__(2, 1, 1) __launch_bounds__(384, 1)
gemm_kernel(const __grid_constant__ CUtensorMap tA, const __grid_constant__ CUtensorMap tB0, const __grid_constant__ CUtensorMap tB1,
            const __grid_constant__ CUtensorMap tOut, const __grid_constant__ CUtensorMap tX, const __grid_constant__ CUtensorMap tY) {
    constexpr int KB = MODE == 0 ? DM / 64 : (MODE == 1 ? FF / 64 : HD / 64);
    constexpr int NT = MODE == 0 ? FF / 128 : DM / 256;
    constexpr int NTILES = NT * 8;
    extern __shared__ __align__(1024) uint8_t smem[];
    const uint32_t sb = smem_u32(smem);
    const uint32_t full = sb + G_BAR, empty = full + 64;
    const int tid = threadIdx.x, lane = tid & 31;
    const int wg = __shfl_sync(~0u, tid >> 7, 0);
    const int rank = blockIdx.x & 1, pair = blockIdx.x >> 1, npair = gridDim.x >> 1;
    if (tid == 0) {
        for (int i = 0; i < G_STAGES; i++) { mbar_init(full + i * 8, 1); mbar_init(empty + i * 8, 16); }
        asm volatile("fence.mbarrier_init.release.cluster;" ::: "memory");
        fence_async();
    }
    __syncthreads();
    cluster_sync();
    if (wg == 0) {
        asm volatile("setmaxnreg.dec.sync.aligned.u32 40;");
        if (tid == 0) {
            uint32_t st = 0, ph = 1;
            for (int tile = pair; tile < NTILES; tile += npair) {
                const int mp = tile & 7, nt = tile >> 3, row0 = (mp * 2 + rank) * 128;
                const CUtensorMap* tB = (MODE == 0 && rank) ? &tB1 : &tB0;
                const int bcol = MODE == 0 ? nt * 128 : nt * 256 + rank * 128;
                for (int kb = 0; kb < KB; kb++) {
                    mbar_wait(empty + st * 8, ph);
                    const uint32_t base = sb + st * G_STAGE;
                    mbar_expect(full + st * 8, G_STAGE);
                    tma2d(base, &tA, kb * 64, row0, full + st * 8);
                    tma2d_mc(base + 16384 + rank * 16384, tB, bcol, kb * 64, full + st * 8, 3);
                    tma2d_mc(base + 16384 + rank * 16384 + 8192, tB, bcol + 64, kb * 64, full + st * 8, 3);
                    if (++st == G_STAGES) { st = 0; ph ^= 1; }
                }
                if (MODE == 2) {
                    for (int q = 0; q < 4; q++) {
                        mbar_wait(empty + st * 8, ph);
                        const uint32_t base = sb + st * G_STAGE;
                        mbar_expect(full + st * 8, 32768);
                        tma2d(base, &tX, nt * 256 + q * 64, row0, full + st * 8);
                        tma2d(base + 16384, &tY, nt * 256 + q * 64, row0, full + st * 8);
                        if (++st == G_STAGES) { st = 0; ph ^= 1; }
                    }
                }
            }
        }
        __syncwarp();
        cluster_sync();
    } else {
        asm volatile("setmaxnreg.inc.sync.aligned.u32 232;");
        const int cw = wg - 1, w4 = (tid >> 5) & 3;
        const uint32_t empty_dst = mapa(empty, lane & 1);
        const uint32_t epi = sb + G_EPI + cw * 16384;
        const int er = w4 * 16 + (lane & 15), ec = lane >> 4;
        uint32_t st = 0, ph = 0;
        float acc[128];
        for (int tile = pair; tile < NTILES; tile += npair) {
            const int mp = tile & 7, nt = tile >> 3, row0 = (mp * 2 + rank) * 128 + cw * 64;
            uint32_t prev = 0;
#pragma unroll 1
            for (int kb = 0; kb < KB; kb++) {
                mbar_wait(full + st * 8, ph);
                const uint32_t base = sb + st * G_STAGE;
                const uint32_t da = (((base + cw * 8192) & 0x3FFFF) >> 4) | (1u << 16);
                const uint32_t db = (((base + 16384) & 0x3FFFF) >> 4) | (512u << 16);
                wg_fence();
#pragma unroll
                for (int k = 0; k < 4; k++) wg256(acc, da + k * 2, db + k * 128, (kb | k) != 0);
                wg_commit();
                if (kb > 0) {
                    wg_wait<1>();
                    if (lane < 2) mbar_arrive_cluster(empty_dst + prev * 8);
                }
                prev = st;
                if (++st == G_STAGES) { st = 0; ph ^= 1; }
            }
            wg_wait<0>();
            reg_fence<128>(acc);
            if (lane < 2) mbar_arrive_cluster(empty_dst + prev * 8);
#pragma unroll
            for (int hp = 0; hp < (MODE == 0 ? 1 : 2); hp++) {
                uint32_t o[32];
#pragma unroll
                for (int bx = 0; bx < 2; bx++) {
                    uint32_t xa = 0;
                    if (MODE == 2) {
                        mbar_wait(full + st * 8, ph);
                        xa = sb + st * G_STAGE + (cw * 64 + er) * 128;
                    }
#pragma unroll
                    for (int j = 0; j < 4; j++) {
                        const int a0 = hp * 64 + bx * 32 + j * 8;
                        uint32_t* oo = o + bx * 16 + j * 4;
                        if (MODE == 0) {
#pragma unroll
                            for (int i = 0; i < 4; i++)
                                oo[i] = pack2(sigmoidf_(acc[a0 + 2 * i]) * acc[64 + a0 + 2 * i], sigmoidf_(acc[a0 + 2 * i + 1]) * acc[64 + a0 + 2 * i + 1]);
                        } else if (MODE == 1) {
#pragma unroll
                            for (int i = 0; i < 4; i++)
                                oo[i] = pack2(sigmoidf_(acc[a0 + 2 * i]) * acc[a0 + 2 * i], sigmoidf_(acc[a0 + 2 * i + 1]) * acc[a0 + 2 * i + 1]);
                        } else {
                            uint32_t xv[4], yv[4];
                            const uint32_t ad = xa + (((2 * j + ec) ^ (er & 7)) << 4);
                            ldsm4(xv, ad); ldsm4(yv, ad + 16384);
#pragma unroll
                            for (int i = 0; i < 4; i++)
                                oo[i] = pack2(fmaf(acc[a0 + 2 * i], bf_lo(yv[i]), bf_lo(xv[i])), fmaf(acc[a0 + 2 * i + 1], bf_hi(yv[i]), bf_hi(xv[i])));
                        }
                    }
                    if (MODE == 2) {
                        __syncwarp();
                        if (lane < 2) mbar_arrive_cluster(empty_dst + st * 8);
                        if (++st == G_STAGES) { st = 0; ph ^= 1; }
                    }
                }
                if ((tid & 127) == 0) asm volatile("cp.async.bulk.wait_group.read 0;" ::: "memory");
                bar_sync(1 + cw, 128);
#pragma unroll
                for (int bx = 0; bx < 2; bx++)
#pragma unroll
                    for (int j = 0; j < 4; j++) {
                        const uint32_t* oo = o + bx * 16 + j * 4;
                        stsm4(epi + bx * 8192 + er * 128 + (((2 * j + ec) ^ (er & 7)) << 4), oo[0], oo[1], oo[2], oo[3]);
                    }
                fence_async();
                bar_sync(1 + cw, 128);
                if ((tid & 127) == 0) {
                    const int col = MODE == 0 ? nt * 128 : nt * 256 + hp * 128;
                    tma2d_store(&tOut, col, row0, epi);
                    tma2d_store(&tOut, col + 64, row0, epi + 8192);
                    asm volatile("cp.async.bulk.commit_group;" ::: "memory");
                }
            }
        }
        if ((tid & 127) == 0) asm volatile("cp.async.bulk.wait_group 0;" ::: "memory");
        __syncwarp();
        cluster_sync();
    }
}

typedef CUresult (*EncodeFn)(CUtensorMap*, CUtensorMapDataType, cuuint32_t, void*, const cuuint64_t*, const cuuint64_t*, const cuuint32_t*,
                             const cuuint32_t*, CUtensorMapInterleave, CUtensorMapSwizzle, CUtensorMapL2promotion, CUtensorMapFloatOOBfill);

CUtensorMap make_map(EncodeFn enc, const void* p, int rows, int cols, int box_rows) {
    CUtensorMap m;
    cuuint64_t dims[2] = {(cuuint64_t)cols, (cuuint64_t)rows}, strides[1] = {(cuuint64_t)cols * 2};
    cuuint32_t box[2] = {64, (cuuint32_t)box_rows}, es[2] = {1, 1};
    enc(&m, CU_TENSOR_MAP_DATA_TYPE_BFLOAT16, 2, const_cast<void*>(p), dims, strides, box, es, CU_TENSOR_MAP_INTERLEAVE_NONE,
        CU_TENSOR_MAP_SWIZZLE_128B, CU_TENSOR_MAP_L2_PROMOTION_L2_128B, CU_TENSOR_MAP_FLOAT_OOB_FILL_NONE);
    return m;
}

}

extern "C" void kernel_launch(void* const* d_in, const int* in_sizes, int n_in, void* d_out, int out_size) {
    const __nv_bfloat16* x = (const __nv_bfloat16*)d_in[0];
    const __nv_bfloat16* mem0 = (const __nv_bfloat16*)d_in[1];
    void* fn = nullptr;
    cudaDriverEntryPointQueryResult qr;
    cudaGetDriverEntryPoint("cuTensorMapEncodeTiled", &fn, cudaEnableDefault, &qr);
    EncodeFn enc = (EncodeFn)fn;
    void *xn, *ox, *h, *y;
    cudaGetSymbolAddress(&xn, g_xn); cudaGetSymbolAddress(&ox, g_ox); cudaGetSymbolAddress(&h, g_h); cudaGetSymbolAddress(&y, g_y);

    const CUtensorMap tq = make_map(enc, d_in[2], DM, HD, 128), tk = make_map(enc, d_in[3], DM, HD, 128), tv = make_map(enc, d_in[4], DM, HD, 128);
    const CUtensorMap two16 = make_map(enc, d_in[5], HD, DM, 16);
    const CUtensorMap txn128 = make_map(enc, xn, SEQ, DM, 128), tg = make_map(enc, d_in[8], DM, FF, 64), tu = make_map(enc, d_in[9], DM, FF, 64);
    const CUtensorMap th64 = make_map(enc, h, SEQ, FF, 64), th128 = make_map(enc, h, SEQ, FF, 128), td = make_map(enc, d_in[10], FF, DM, 64);
    const CUtensorMap ty64 = make_map(enc, y, SEQ, DM, 64), ty128 = make_map(enc, y, SEQ, DM, 128), tx128 = make_map(enc, x, SEQ, DM, 128);
    const CUtensorMap tox = make_map(enc, ox, SEQ, HD, 128), two64 = make_map(enc, d_in[5], HD, DM, 64), tout = make_map(enc, d_out, SEQ, DM, 64);

    cudaFuncSetAttribute(chain_kernel, cudaFuncAttributeMaxDynamicSharedMemorySize, C_SMEM);
    cudaFuncSetAttribute(gemm_kernel<0>, cudaFuncAttributeMaxDynamicSharedMemorySize, G_SMEM);
    cudaFuncSetAttribute(gemm_kernel<1>, cudaFuncAttributeMaxDynamicSharedMemorySize, G_SMEM);
    cudaFuncSetAttribute(gemm_kernel<2>, cudaFuncAttributeMaxDynamicSharedMemorySize, G_SMEM);

    cudaStream_t st = cudaStreamPerThread;
    ln_kernel<<<SEQ / 8, 256, 0, st>>>(x, mem0);
    chain_kernel<<<96, 256, C_SMEM, st>>>(tq, tk, tv, two16);
    gemm_kernel<0><<<132, 384, G_SMEM, st>>>(txn128, tg, tu, th64, th64, th64);
    gemm_kernel<1><<<64, 384, G_SMEM, st>>>(th128, td, td, ty64, ty64, ty64);
    gemm_kernel<2><<<64, 384, G_SMEM, st>>>(tox, two64, two64, tout, tx128, ty128);
}
```

```cpp
#include <cuda_runtime.h>
#include <cuda_bf16.h>
#include <cuda.h>
#include <stdint.h>
#include <type_traits>

namespace {

constexpr int SEQ = 2048, DM = 1024, HD = 4096, FF = 3584, NSEG = 64;

__device__ __align__(1024) __nv_bfloat16 g_xn[SEQ * DM];
__device__ __align__(1024) uint4 g_xc[SEQ * DM / 8];
__device__ __align__(1024) __nv_bfloat16 g_ox[SEQ * HD];
__device__ __align__(1024) __nv_bfloat16 g_h[SEQ * FF];
__device__ __align__(1024) __nv_bfloat16 g_y[SEQ * DM];
__device__ __align__(1024) uint4 g_xmem[4][1024];
__device__ __align__(1024) uint4 g_xo[4][4096];
#define FSTR 8
__device__ __align__(1024) uint32_t g_flag[2][96 * FSTR];

__device__ __forceinline__ uint32_t smem_u32(const void* p) { return (uint32_t)__cvta_generic_to_shared(p); }
__device__ __forceinline__ uint32_t mapa(uint32_t a, uint32_t r) {
    uint32_t o; asm("mapa.shared::cluster.u32 %0, %1, %2;" : "=r"(o) : "r"(a), "r"(r)); return o;
}
__device__ __forceinline__ void mbar_init(uint32_t a, uint32_t cnt) {
    asm volatile("mbarrier.init.shared.b64 [%0], %1;" :: "r"(a), "r"(cnt) : "memory");
}
__device__ __forceinline__ void mbar_expect(uint32_t a, uint32_t bytes) {
    asm volatile("mbarrier.arrive.expect_tx.shared.b64 _, [%0], %1;" :: "r"(a), "r"(bytes) : "memory");
}
__device__ __forceinline__ void mbar_arrive_cluster(uint32_t a) {
    asm volatile("mbarrier.arrive.shared::cluster.b64 _, [%0];" :: "r"(a) : "memory");
}
__device__ __forceinline__ void spin_guard(uint32_t& it) {
    asm volatile("{\n.reg .pred p;\nadd.u32 %0, %0, 1;\nsetp.gt.u32 p, %0, 0x400000;\n@p st.shared.u32 [%0], %0;\n}" : "+r"(it));
}
__device__ __forceinline__ void mbar_wait(uint32_t a, uint32_t par) {
    asm volatile("{\n.reg .pred p;\n.reg .u32 i;\nmov.u32 i, 0;\n"
                 "WL:\nadd.u32 i, i, 1;\nsetp.gt.u32 p, i, 0x400000;\n@p st.shared.u32 [i], i;\n"
                 "mbarrier.try_wait.parity.shared::cta.b64 p, [%0], %1;\n@!p bra WL;\n}" :: "r"(a), "r"(par) : "memory");
}
__device__ __forceinline__ void mbar_arrive(uint32_t a) { asm volatile("mbarrier.arrive.shared.b64 _, [%0];" :: "r"(a) : "memory"); }
__device__ __forceinline__ void tma2d(uint32_t dst, const CUtensorMap* m, int c0, int c1, uint32_t bar) {
    asm volatile("cp.async.bulk.tensor.2d.shared::cluster.global.mbarrier::complete_tx::bytes [%0], [%1, {%3, %4}], [%2];"
                 :: "r"(dst), "l"(m), "r"(bar), "r"(c0), "r"(c1) : "memory");
}
__device__ __forceinline__ void tma2d_mc(uint32_t dst, const CUtensorMap* m, int c0, int c1, uint32_t bar, uint16_t mask) {
    asm volatile("cp.async.bulk.tensor.2d.shared::cluster.global.mbarrier::complete_tx::bytes.multicast::cluster [%0], [%1, {%3, %4}], [%2], %5;"
                 :: "r"(dst), "l"(m), "r"(bar), "r"(c0), "r"(c1), "h"(mask) : "memory");
}
__device__ __forceinline__ void bulk_mc(uint32_t dst, const void* src, uint32_t bytes, uint32_t bar, uint16_t mask) {
    asm volatile("cp.async.bulk.shared::cluster.global.mbarrier::complete_tx::bytes.multicast::cluster [%0], [%1], %2, [%3], %4;"
                 :: "r"(dst), "l"(src), "r"(bytes), "r"(bar), "h"(mask) : "memory");
}
__device__ __forceinline__ void bulk_ld(uint32_t dst, const void* src, uint32_t bytes, uint32_t bar) {
    asm volatile("cp.async.bulk.shared::cluster.global.mbarrier::complete_tx::bytes [%0], [%1], %2, [%3];"
                 :: "r"(dst), "l"(src), "r"(bytes), "r"(bar) : "memory");
}
__device__ __forceinline__ uint32_t gtick() { uint32_t c; asm volatile("mov.u32 %0, %%globaltimer_lo;" : "=r"(c)); return c >> 5; }
__device__ __forceinline__ uint32_t gtick_dep(uint32_t zero) {
    uint32_t c;
    asm volatile("{\n.reg .pred p;\nsetp.eq.u32 p, %1, 0;\nmov.u32 %0, 0;\n@p mov.u32 %0, %%globaltimer_lo;\n}" : "=r"(c) : "r"(zero));
    return c >> 5;
}
__device__ __forceinline__ uint32_t ld_relaxed1(const void* p) {
    uint32_t v; asm volatile("ld.relaxed.gpu.global.u32 %0, [%1];" : "=r"(v) : "l"(p) : "memory"); return v;
}
__device__ __forceinline__ bool any_nan(float a, float b) {
    uint32_t r;
    asm volatile("{\n.reg .pred p;\nsetp.nan.f32 p, %1, %2;\nvote.sync.any.pred p, p, 0xffffffff;\nselp.u32 %0, 1, 0, p;\n}" : "=r"(r) : "f"(a), "f"(b));
    return r;
}
__device__ __forceinline__ bool bar_sync_unless_nan(float a, float b) {
    uint32_t r;
    asm volatile("{\n.reg .pred p;\nsetp.nan.f32 p, %1, %2;\nvote.sync.any.pred p, p, 0xffffffff;\n@!p bar.sync 6, 256;\nselp.u32 %0, 1, 0, p;\n}"
                 : "=r"(r) : "f"(a), "f"(b) : "memory");
    return r;
}
__device__ __forceinline__ bool st_async4_unless_nan(uint32_t a, uint32_t bar, const float* v) {
    uint32_t r;
    asm volatile("{\n.reg .pred p;\nsetp.nan.f32 p, %3, %4;\nvote.sync.any.pred p, p, 0xffffffff;\n"
                 "@!p st.async.shared::cluster.mbarrier::complete_tx::bytes.v4.f32 [%1], {%3,%4,%5,%6}, [%2];\nselp.u32 %0, 1, 0, p;\n}"
                 : "=r"(r) : "r"(a), "r"(bar), "f"(v[0]), "f"(v[1]), "f"(v[2]), "f"(v[3]) : "memory");
    return r;
}
__device__ __forceinline__ void bar_arrive(int id, int n) { asm volatile("bar.arrive %0, %1;" :: "r"(id), "r"(n) : "memory"); }
__device__ __forceinline__ uint32_t clk() { uint32_t c; asm volatile("mov.u32 %0, %%clock;" : "=r"(c)); return c; }
__device__ __forceinline__ void tma2d_store(const CUtensorMap* m, int c0, int c1, uint32_t src) {
    asm volatile("cp.async.bulk.tensor.2d.global.shared::cta.bulk_group [%0, {%1, %2}], [%3];"
                 :: "l"(m), "r"(c0), "r"(c1), "r"(src) : "memory");
}
__device__ __forceinline__ void bar_sync(int id, int n) { asm volatile("bar.sync %0, %1;" :: "r"(id), "r"(n) : "memory"); }
__device__ __forceinline__ void fence_async() { asm volatile("fence.proxy.async.shared::cta;" ::: "memory"); }
__device__ __forceinline__ void cluster_sync() {
    asm volatile("barrier.cluster.arrive.release.aligned;\nbarrier.cluster.wait.acquire.aligned;" ::: "memory");
}
__device__ __forceinline__ void ldsm4(uint32_t* r, uint32_t a) {
    asm volatile("ldmatrix.sync.aligned.m8n8.x4.shared.b16 {%0,%1,%2,%3}, [%4];"
                 : "=r"(r[0]), "=r"(r[1]), "=r"(r[2]), "=r"(r[3]) : "r"(a) : "memory");
}
__device__ __forceinline__ void ldsm4t(uint32_t* r, uint32_t a) {
    asm volatile("ldmatrix.sync.aligned.m8n8.x4.trans.shared.b16 {%0,%1,%2,%3}, [%4];"
                 : "=r"(r[0]), "=r"(r[1]), "=r"(r[2]), "=r"(r[3]) : "r"(a) : "memory");
}
__device__ __forceinline__ void stsm4(uint32_t a, uint32_t r0, uint32_t r1, uint32_t r2, uint32_t r3) {
    asm volatile("stmatrix.sync.aligned.m8n8.x4.shared.b16 [%0], {%1,%2,%3,%4};" :: "r"(a), "r"(r0), "r"(r1), "r"(r2), "r"(r3) : "memory");
}
__device__ __forceinline__ void stsm4t(uint32_t a, uint32_t r0, uint32_t r1, uint32_t r2, uint32_t r3) {
    asm volatile("stmatrix.sync.aligned.m8n8.x4.trans.shared.b16 [%0], {%1,%2,%3,%4};" :: "r"(a), "r"(r0), "r"(r1), "r"(r2), "r"(r3) : "memory");
}
__device__ __forceinline__ void stsm2(uint32_t a, uint32_t r0, uint32_t r1) {
    asm volatile("stmatrix.sync.aligned.m8n8.x2.shared.b16 [%0], {%1,%2};" :: "r"(a), "r"(r0), "r"(r1) : "memory");
}
__device__ __forceinline__ void stsm2t(uint32_t a, uint32_t r0, uint32_t r1) {
    asm volatile("stmatrix.sync.aligned.m8n8.x2.trans.shared.b16 [%0], {%1,%2};" :: "r"(a), "r"(r0), "r"(r1) : "memory");
}
__device__ __forceinline__ uint32_t movm(uint32_t a) {
    uint32_t d; asm volatile("movmatrix.sync.aligned.m8n8.trans.b16 %0, %1;" : "=r"(d) : "r"(a)); return d;
}
__device__ __forceinline__ void mma16(float* d, uint32_t a0, uint32_t a1, uint32_t a2, uint32_t a3, uint32_t b0, uint32_t b1) {
    asm volatile("mma.sync.aligned.m16n8k16.row.col.f32.bf16.bf16.f32 {%0,%1,%2,%3}, {%4,%5,%6,%7}, {%8,%9}, {%0,%1,%2,%3};"
                 : "+f"(d[0]), "+f"(d[1]), "+f"(d[2]), "+f"(d[3]) : "r"(a0), "r"(a1), "r"(a2), "r"(a3), "r"(b0), "r"(b1));
}
__device__ __forceinline__ void mma8(float* d, uint32_t a0, uint32_t a1, uint32_t b0) {
    asm volatile("mma.sync.aligned.m16n8k8.row.col.f32.bf16.bf16.f32 {%0,%1,%2,%3}, {%4,%5}, {%6}, {%0,%1,%2,%3};"
                 : "+f"(d[0]), "+f"(d[1]), "+f"(d[2]), "+f"(d[3]) : "r"(a0), "r"(a1), "r"(b0));
}
__device__ __forceinline__ uint32_t pack2(float lo, float hi) {
    uint32_t r; asm("cvt.rn.bf16x2.f32 %0, %1, %2;" : "=r"(r) : "f"(hi), "f"(lo)); return r;
}
__device__ __forceinline__ float bf_lo(uint32_t v) { return __uint_as_float(v << 16); }
__device__ __forceinline__ float bf_hi(uint32_t v) { return __uint_as_float(v & 0xFFFF0000u); }
__device__ __forceinline__ float ex2(float x) { float y; asm("ex2.approx.ftz.f32 %0, %1;" : "=f"(y) : "f"(x)); return y; }
__device__ __forceinline__ float rcp(float x) { float y; asm("rcp.approx.ftz.f32 %0, %1;" : "=f"(y) : "f"(x)); return y; }
__device__ __forceinline__ void sts4f(uint32_t a, float x, float y, float z, float w) {
    asm volatile("st.shared.v4.f32 [%0], {%1,%2,%3,%4};" :: "r"(a), "f"(x), "f"(y), "f"(z), "f"(w) : "memory");
}
__device__ __forceinline__ void sts4u(uint32_t a, uint4 v) {
    asm volatile("st.shared.v4.u32 [%0], {%1,%2,%3,%4};" :: "r"(a), "r"(v.x), "r"(v.y), "r"(v.z), "r"(v.w) : "memory");
}
__device__ __forceinline__ float4 lds4f(uint32_t a) {
    float4 v; asm volatile("ld.shared.v4.f32 {%0,%1,%2,%3}, [%4];" : "=f"(v.x), "=f"(v.y), "=f"(v.z), "=f"(v.w) : "r"(a) : "memory"); return v;
}
__device__ __forceinline__ float2 lds2f(uint32_t a) {
    float2 v; asm volatile("ld.shared.v2.f32 {%0,%1}, [%2];" : "=f"(v.x), "=f"(v.y) : "r"(a) : "memory"); return v;
}
__device__ __forceinline__ uint4 lds4u(uint32_t a) {
    uint4 v; asm volatile("ld.shared.v4.u32 {%0,%1,%2,%3}, [%4];" : "=r"(v.x), "=r"(v.y), "=r"(v.z), "=r"(v.w) : "r"(a) : "memory"); return v;
}
__device__ __forceinline__ uint32_t lds1u(uint32_t a) {
    uint32_t v; asm volatile("ld.shared.u32 %0, [%1];" : "=r"(v) : "r"(a) : "memory"); return v;
}
__device__ __forceinline__ uint2 lds2u(uint32_t a) {
    uint2 v; asm volatile("ld.shared.v2.u32 {%0,%1}, [%2];" : "=r"(v.x), "=r"(v.y) : "r"(a) : "memory"); return v;
}
__device__ __forceinline__ void st_async4(uint32_t a, uint32_t bar, uint32_t x, uint32_t y, uint32_t z, uint32_t w) {
    asm volatile("st.async.shared::cluster.mbarrier::complete_tx::bytes.v4.b32 [%0], {%1,%2,%3,%4}, [%5];"
                 :: "r"(a), "r"(x), "r"(y), "r"(z), "r"(w), "r"(bar) : "memory");
}
__device__ __forceinline__ void st_async2(uint32_t a, uint32_t bar, uint32_t x, uint32_t y) {
    asm volatile("st.async.shared::cluster.mbarrier::complete_tx::bytes.v2.b32 [%0], {%1,%2}, [%3];"
                 :: "r"(a), "r"(x), "r"(y), "r"(bar) : "memory");
}
__device__ __forceinline__ void st_async1(uint32_t a, uint32_t bar, uint32_t x) {
    asm volatile("st.async.shared::cluster.mbarrier::complete_tx::bytes.b32 [%0], %1, [%2];" :: "r"(a), "r"(x), "r"(bar) : "memory");
}
__device__ __forceinline__ uint4 ld_relaxed4(const uint4* p) {
    uint4 v;
    asm volatile("ld.relaxed.gpu.global.v4.u32 {%0,%1,%2,%3}, [%4];" : "=r"(v.x), "=r"(v.y), "=r"(v.z), "=r"(v.w) : "l"(p) : "memory");
    return v;
}
__device__ __forceinline__ void st_relaxed4(uint4* p, uint4 v) {
    asm volatile("st.relaxed.gpu.global.v4.u32 [%0], {%1,%2,%3,%4};" :: "l"(p), "r"(v.x), "r"(v.y), "r"(v.z), "r"(v.w) : "memory");
}
__device__ __forceinline__ void st_pred4(void* p, uint4 v, bool on) {
    asm volatile("{\n.reg .pred p;\nsetp.ne.u32 p, %5, 0;\n@p st.global.v4.u32 [%0], {%1,%2,%3,%4};\n}"
                 :: "l"(p), "r"(v.x), "r"(v.y), "r"(v.z), "r"(v.w), "r"((uint32_t)on) : "memory");
}
__device__ __forceinline__ void st_relaxed1(void* p, uint32_t v) {
    asm volatile("st.relaxed.gpu.global.u32 [%0], %1;" :: "l"(p), "r"(v) : "memory");
}
__device__ __forceinline__ uint32_t umax4(uint4 v) { return max(max(v.x, v.y), max(v.z, v.w)); }
__device__ __forceinline__ void wg_fence() { asm volatile("wgmma.fence.sync.aligned;" ::: "memory"); }
__device__ __forceinline__ void wg_commit() { asm volatile("wgmma.commit_group.sync.aligned;" ::: "memory"); }
template <int N> __device__ __forceinline__ void wg_wait() { asm volatile("wgmma.wait_group.sync.aligned %0;" :: "n"(N) : "memory"); }
template <int N> __device__ __forceinline__ void reg_fence(float* d) {
#pragma unroll
    for (int i = 0; i < N; i++) asm volatile("" : "+f"(d[i]) :: "memory");
}
#define ACC16(d) "+f"(d[0]), "+f"(d[1]), "+f"(d[2]), "+f"(d[3]), "+f"(d[4]), "+f"(d[5]), "+f"(d[6]), "+f"(d[7]), \
                 "+f"(d[8]), "+f"(d[9]), "+f"(d[10]), "+f"(d[11]), "+f"(d[12]), "+f"(d[13]), "+f"(d[14]), "+f"(d[15])
#define DESC_HI_SW128 "0x40000040"
#define OUT16(d) "=f"(d[0]), "=f"(d[1]), "=f"(d[2]), "=f"(d[3]), "=f"(d[4]), "=f"(d[5]), "=f"(d[6]), "=f"(d[7]), \
                 "=f"(d[8]), "=f"(d[9]), "=f"(d[10]), "=f"(d[11]), "=f"(d[12]), "=f"(d[13]), "=f"(d[14]), "=f"(d[15])
template <int ACCUM, int BOFF>
__device__ __forceinline__ void wg32_rs(float* d, const uint32_t* a, uint64_t dsw) {
    if (ACCUM)
        asm volatile("{\n.reg .b64 db;\nadd.s64 db, %20, %21;\n"
                     "wgmma.mma_async.sync.aligned.m64n32k16.f32.bf16.bf16 {%0,%1,%2,%3,%4,%5,%6,%7,%8,%9,%10,%11,%12,%13,%14,%15}, "
                     "{%16,%17,%18,%19}, db, 1, 1, 1, 0;\n}"
                     : ACC16(d) : "r"(a[0]), "r"(a[1]), "r"(a[2]), "r"(a[3]), "l"(dsw), "n"(BOFF));
    else
        asm volatile("{\n.reg .b64 db;\nadd.s64 db, %20, %21;\n"
                     "wgmma.mma_async.sync.aligned.m64n32k16.f32.bf16.bf16 {%0,%1,%2,%3,%4,%5,%6,%7,%8,%9,%10,%11,%12,%13,%14,%15}, "
                     "{%16,%17,%18,%19}, db, 0, 1, 1, 0;\n}"
                     : OUT16(d) : "r"(a[0]), "r"(a[1]), "r"(a[2]), "r"(a[3]), "l"(dsw), "n"(BOFF));
}
template <int AOFF, int BOFF>
__device__ __forceinline__ void wg32_ss(float* d, uint64_t dsw) {
    asm volatile("{\n.reg .b64 da, db;\nadd.s64 da, %16, %17;\nadd.s64 db, %16, %18;\n"
                 "wgmma.mma_async.sync.aligned.m64n32k16.f32.bf16.bf16 {%0,%1,%2,%3,%4,%5,%6,%7,%8,%9,%10,%11,%12,%13,%14,%15}, "
                 "da, db, 1, 1, 1, 1, 0;\n}"
                 : ACC16(d) : "l"(dsw), "n"(AOFF), "n"(BOFF));
}
template <int ACCUM, int AOFF, int BOFF>
__device__ __forceinline__ void wg8_ss(float* d, uint64_t dsw, uint64_t dns) {
    if (!ACCUM)
        asm volatile("{\n.reg .b64 da, db;\nadd.s64 da, %4, %6;\nadd.s64 db, %5, %7;\n"
                     "wgmma.mma_async.sync.aligned.m64n8k16.f32.bf16.bf16 {%0,%1,%2,%3}, da, db, 0, 1, 1, 1, 0;\n}"
                     : "=f"(d[0]), "=f"(d[1]), "=f"(d[2]), "=f"(d[3]) : "l"(dsw), "l"(dns), "n"(AOFF), "n"(BOFF));
    else
        asm volatile("{\n.reg .b64 da, db;\nadd.s64 da, %4, %6;\nadd.s64 db, %5, %7;\n"
                     "wgmma.mma_async.sync.aligned.m64n8k16.f32.bf16.bf16 {%0,%1,%2,%3}, da, db, 1, 1, 1, 1, 0;\n}"
                     : "+f"(d[0]), "+f"(d[1]), "+f"(d[2]), "+f"(d[3]) : "l"(dsw), "l"(dns), "n"(AOFF), "n"(BOFF));
}
template <int I0, int I1, class F>
__device__ __forceinline__ void static_for(F&& f) {
    if constexpr (I0 < I1) { f(std::integral_constant<int, I0>{}); static_for<I0 + 1, I1>(f); }
}
template <int I0, int I1, int AOFF, int BOFF>
__device__ __forceinline__ void wg8_chain(float* d, uint64_t dsw, uint64_t dns) {
    wg_fence();
    static_for<I0, I1>([&](auto i) { wg8_ss<i.value != 0, AOFF + i.value * 128, BOFF + i.value * 16>(d, dsw, dns); });
    wg_commit();
}

__global__ void __launch_bounds__(256) ln_kernel(const __nv_bfloat16* __restrict__ x, const __nv_bfloat16* __restrict__ mem0) {
    const int lane = threadIdx.x & 31, row = blockIdx.x * 8 + (threadIdx.x >> 5);
    const uint4* src = reinterpret_cast<const uint4*>(x + (size_t)row * DM);
    uint4 v[4];
#pragma unroll
    for (int j = 0; j < 4; j++) v[j] = src[j * 32 + lane];
    const int gi = blockIdx.x * 256 + threadIdx.x;
    const uint4 poison = make_uint4(~0u, ~0u, ~0u, ~0u);
    if (gi < 1024) {
        uint4 m = reinterpret_cast<const uint4*>(mem0)[(gi & 7) * 128 + (gi >> 3)];
        if (m.x == ~0u) m.x = 0x7FFF7FFFu;
        if (m.y == ~0u) m.y = 0x7FFF7FFFu;
        if (m.z == ~0u) m.z = 0x7FFF7FFFu;
        if (m.w == ~0u) m.w = 0x7FFF7FFFu;
        g_xmem[0][gi] = m;
    } else if (gi < 4096) {
        (&g_xmem[0][0])[gi] = poison;
    } else if (gi < 4096 + 16384) {
        (&g_xo[0][0])[gi - 4096] = poison;
    } else if (gi < 4096 + 16384 + 48 * FSTR) {
        reinterpret_cast<uint4*>(&g_flag[0][0])[gi - 4096 - 16384] = poison;
    }
    float f[32];
#pragma unroll
    for (int j = 0; j < 4; j++) {
        f[j * 8 + 0] = bf_lo(v[j].x); f[j * 8 + 1] = bf_hi(v[j].x); f[j * 8 + 2] = bf_lo(v[j].y); f[j * 8 + 3] = bf_hi(v[j].y);
        f[j * 8 + 4] = bf_lo(v[j].z); f[j * 8 + 5] = bf_hi(v[j].z); f[j * 8 + 6] = bf_lo(v[j].w); f[j * 8 + 7] = bf_hi(v[j].w);
    }
    float s = 0.f;
#pragma unroll
    for (int i = 0; i < 32; i++) s += f[i];
#pragma unroll
    for (int o = 16; o; o >>= 1) s += __shfl_xor_sync(~0u, s, o);
    const float mean = s * (1.f / DM);
    float q = 0.f;
#pragma unroll
    for (int i = 0; i < 32; i++) { f[i] -= mean; q += f[i] * f[i]; }
#pragma unroll
    for (int o = 16; o; o >>= 1) q += __shfl_xor_sync(~0u, q, o);
    const float r = 1.f / sqrtf(q * (1.f / DM) + 1e-5f);
    uint4* dst = reinterpret_cast<uint4*>(g_xn + (size_t)row * DM);
    uint4* dst2 = g_xc + (row >> 5) * 4096 + (lane >> 3) * 256 + (row & 31) * 8 + ((lane & 7) ^ (row & 7));
#pragma unroll
    for (int j = 0; j < 4; j++) {
        const uint4 o = make_uint4(pack2(f[j * 8] * r, f[j * 8 + 1] * r), pack2(f[j * 8 + 2] * r, f[j * 8 + 3] * r),
                                   pack2(f[j * 8 + 4] * r, f[j * 8 + 5] * r), pack2(f[j * 8 + 6] * r, f[j * 8 + 7] * r));
        dst[j * 32 + lane] = o;
        dst2[(j & 1) * 2048 + (j >> 1) * 1024] = o;
    }
}

#define ONKQ 45
constexpr int ONKV = 128 - 2 * ONKQ;
constexpr uint32_t SB0 = 1024;
constexpr uint32_t C_WS = 0, C_XN = 65536, C_MB = 98304, C_WO = 114688, C_SMEM = 232448;
constexpr uint32_t C_BAR = C_SMEM - 384, C_CAL = C_BAR + 192;
constexpr uint32_t C_SLOTQ = C_WO + ONKQ * 2048, C_QM = C_SLOTQ + 4096, C_KM = C_QM + 1024, C_QX = C_SLOTQ + 8192, C_KX = C_QX + 4096,
                   C_XSL = C_KX + 4096, C_OL = C_XSL + 5120;
constexpr uint32_t C_SLOTV = C_WO + ONKV * 2048, C_V = C_SLOTV + 8192, C_PL = C_V + 20480, C_SL = C_PL + 4096;
static_assert(C_OL + 3072 <= C_BAR && C_SL + 2560 <= C_BAR, "smem overflow");
enum { B_W0 = 0, B_W1, B_W2, B_WS, B_WO, B_XF0, B_XF1, B_SC, B_P0, B_P1, B_XS, B_OL, B_MF0, B_MF1, B_OF, B_RT0, B_RT1, B_NUM };
struct Descs { uint64_t sw[4], ns; };
constexpr uint64_t DSW = 0x4000004000010000ull, DNS = 0x0000001000080000ull;
template <int V> using ic = std::integral_constant<int, V>;
constexpr float SM_SCALE = 0.08838834764831845f * 1.4426950408889634f;

#define TSD(i) do {} while (0)
#define TS_FLUSH(w)
#define TSX(i, c)
#define TS(i)
#define NOFILL 0
#define DLY1 1300
#define DLY2 1450
#define DLYB 350
#define VLEAD 4

#define VEARLY 8
#define QSPLIT 20
__device__ __forceinline__ bool elect() {
    uint32_t r;
    asm volatile("{\n.reg .pred p;\nelect.sync _|p, 0xffffffff;\nselp.u32 %0, 1, 0, p;\n}" : "=r"(r));
    return r;
}
__device__ __forceinline__ int uni(int v) { return __shfl_sync(~0u, v, 0); }
__device__ __forceinline__ void calibrate(uint32_t cal, float keep) {
    const uint32_t t0 = gtick();
    uint32_t t, it = 0;
    do { t = gtick(); spin_guard(it); } while (t == t0);
    const uint32_t c = clk();
    const uint4 p = lds4u(cal);
    const float cpt = fminf(fmaxf(__fdividef((float)(c - p.y), (float)((t - p.x) & 0x7FFFFFF)), 16.f), 128.f);
    __syncwarp();
    sts4u(cal, make_uint4(t, c, __float_as_uint(keep > 0.f ? fmaf(keep, __uint_as_float(p.z) - cpt, cpt) : cpt), 0));
}
struct Stamps { uint32_t a, b, c; };
__device__ __forceinline__ Stamps load_stamps(const uint32_t* f, uint32_t l16, bool on = true) {
    const char* p = reinterpret_cast<const char*>(f) + (l16 >> 2) * FSTR;
    Stamps v;
    asm volatile("{\n.reg .pred p;\nsetp.ne.u32 p, %4, 0;\nmov.u32 %0, 63;\nmov.u32 %1, 63;\nmov.u32 %2, 63;\n"
                 "@p ld.relaxed.gpu.global.u32 %0, [%3];\n@p ld.relaxed.gpu.global.u32 %1, [%3 + %5];\n@p ld.relaxed.gpu.global.u32 %2, [%3 + %6];\n}"
                 : "=&r"(v.a), "=&r"(v.b), "=&r"(v.c) : "l"(p), "r"((uint32_t)on), "n"(128 * FSTR), "n"(256 * FSTR) : "memory");
    return v;
}
__device__ __forceinline__ uint32_t latest_stamp(Stamps v, const uint32_t* f, uint32_t l16, int s, uint32_t cal) {
    const uint4 p = lds4u(cal);
    uint32_t it = 0;
    while (__builtin_expect(!__all_sync(~0u, (((v.a ^ s) | (v.b ^ s) | (v.c ^ s)) & 63) == 0), 0)) { v = load_stamps(f, l16); spin_guard(it); }
    const uint32_t ref = p.x << 6;
    const int late = __reduce_max_sync(~0u, max(max((int)(v.a - ref), (int)(v.b - ref)), (int)(v.c - ref))) >> 6;
    return p.y + (int)((float)late * __uint_as_float(p.z));
}
__device__ __forceinline__ void wait_clock(uint32_t target) {
    uint32_t it = 0;
    while ((int)(clk() - target) < 0 && ++it < 4096) {}
}

template <int BYTES>
__device__ __forceinline__ bool incomplete(uint32_t buf, uint32_t l16) {
    uint32_t m = 0;
#pragma unroll 1
    for (int o = 0; o < BYTES; o += 256) m = max(m, umax4(lds4u(buf + o + (l16 & 255))));
    return __any_sync(~0u, m == ~0u);
}
__device__ __forceinline__ void refetch(uint32_t buf, const uint4* src, uint32_t bytes, uint32_t b, int w4, int barid, uint32_t& tries) {
    spin_guard(tries);
    bar_sync(barid, 128);
    if (w4 == 0 && elect()) { mbar_expect(b, bytes); bulk_ld(buf, src, bytes, b); }
    __syncwarp();
    mbar_wait(b, 0);
    bar_sync(barid, 128);
    if (w4 == 0 && elect()) mbar_arrive(b);
    __syncwarp();
}

template <bool ISV, int WG>
__device__ __forceinline__ void chain_main(const CUtensorMap* tA, const CUtensorMap* tB, const CUtensorMap* tWo,
                                           const uint32_t sb, const int cl, const int rank, const Descs& D) {
    const int tid = threadIdx.x;
    uint32_t l16 = __shfl_sync(~0u, (tid & 31) * 16, tid & 31);
    const int w4 = uni((tid >> 5) & 3);
    const int role = ISV ? 2 : uni(rank & 1), hh = ISV ? rank - 4 : rank >> 1, head = 2 * cl + hh;
    const uint32_t bar = sb + C_BAR;
    constexpr int ONK = ISV ? ONKV : ONKQ;
    const int ostart = uni(hh * 128 + role * ONKQ);

    uint32_t wk[24][4], wv[24][4];
    uint32_t a_adr;
    {
        const int colA = head * 128 + (ISV ? 0 : role * 64), colB = head * 128 + (ISV ? 64 : role * 64);
        auto load_chunk = [&](uint32_t dst, int j, uint32_t b) {
            mbar_expect(b, 65536);
            tma2d(dst, tA, colA, j * 128, b);
            tma2d(dst + 16384, tB, colB, j * 128, b);
            tma2d(dst + 32768, tB, colB, 512 + j * 128, b);
            tma2d(dst + 49152, tA, colA, 512 + j * 128, b);
        };
        if (WG == 0 && tid == 0)
            for (int j = 0; j < 3; j++) load_chunk(sb + j * 65536, j, bar + (B_W0 + j) * 8);
        if (WG == 1 && w4 == 0) calibrate(sb + C_CAL, 0.f);
        const int lane = tid & 31, kr = (lane & 7) + ((lane >> 4) << 3);
        a_adr = __shfl_sync(~0u, sb + WG * 32768 + kr * 128 + (((w4 * 2 + ((lane >> 3) & 1)) ^ (kr & 7)) << 4), lane);
#pragma unroll
        for (int j = 0; j < 3; j++) {
            mbar_wait(bar + (B_W0 + j) * 8, 0);
#pragma unroll
            for (int i = 0; i < 8; i++) {
                ldsm4t(wk[j * 8 + i], a_adr + j * 65536 + i * 2048);
                ldsm4t(wv[j * 8 + i], a_adr + j * 65536 + 16384 + i * 2048);
            }
            if (j != 1) {
                bar_sync(6, 256);
                if (WG == 0 && j == 0 && tid == 0) load_chunk(sb + C_WS, 3, bar + B_WS * 8);
                if (WG == 0 && j == 2 && w4 == 0) {
                    if (lane == 0) mbar_expect(bar + B_WO * 8, ONK * 2048);
                    __syncwarp();
                    for (int i = lane; i < ONK; i += 32) tma2d(sb + C_WO + i * 2048, tWo, cl * 64, (ostart + i) * 16, bar + B_WO * 8);
                }
                __syncwarp();
            }
        }
        if (NOFILL) { for (uint32_t o = C_WO + ONK * 2048 + tid * 16; o < C_BAR; o += 4096) sts4u(sb + o, make_uint4(0, 0, 0, 0)); bar_sync(6, 256); }
        asm volatile("griddepcontrol.wait;" ::: "memory");
        asm volatile("griddepcontrol.launch_dependents;" ::: "memory");
        if (WG == 1 && w4 == 0) calibrate(sb + C_CAL, 0.f);
    }

    constexpr uint32_t SLOT = ISV ? C_SLOTV : C_SLOTQ;
    constexpr int WS_A = (SB0 + C_WS + WG * 32768) >> 4, WO_A = (SB0 + C_WO) >> 4, MB_A = (SB0 + C_MB) >> 4;
#define XN_A(ks) (int)(((SB0 + C_XN + WG * 16384) >> 4) + ((ks) >> 2) * 256 + ((ks) & 3) * 2)
    const uint32_t slot = uni(sb + SLOT + w4 * 512), mbw = sb + C_MB + WG * 8192;
    const uint32_t sb_v = uni(mapa(sb, 4 + hh));
    const uint32_t sb_x = uni(mapa(sb, 2 * hh + WG));
    const uint32_t sb_o = uni(mapa(sb, w4));
    const uint32_t u_off = uni(ISV ? (head * 128 + w4 * 32) * 16 : (cl * 4 + rank) * 256 + (w4 & 1) * 128);
    const uint32_t v_row = uni(sb + C_V + (32 * (2 * WG + (w4 >> 1)) + 4 * (w4 & 1)) * 80);
    uint32_t* const my_flag = &g_flag[0][blockIdx.x * FSTR];
    int s = -1;
    uint32_t pf[4][4];
    float xk[16], xv[16];

    auto load_tokens = [&](int seg, int khalf, int g) {
        if (!NOFILL && elect()) {
            mbar_expect(bar + (B_XF0 + g) * 8, 16384);
            bulk_ld(sb + C_XN + g * 16384, g_xc + (seg * 4 + khalf * 2 + g) * 1024, 16384, bar + (B_XF0 + g) * 8);
        }
        __syncwarp();
    };
    auto prefetch = [&]() {
#pragma unroll
        for (int i = 0; i < 4; i++) ldsm4t(pf[i], a_adr + C_WS + (i & 1) * 16384 + (i >> 1) * 2048);
    };
    auto stream_a = [&](auto i0, auto i1, const uint64_t dk, const uint64_t dv) {
        if (NOFILL) return;
        wg_fence();
        static_for<i0.value, i1.value>([&](auto i_) {
            constexpr int i = i_.value & 7, part = i_.value >> 3, h = i_.value >> 1;
            if constexpr (part < 2 && !(i & 1)) wg32_rs<h != 0, XN_A(h)>(xk, wk[16 + h], DSW);
            if constexpr (part < 2 && (i & 1)) wg32_rs<h != 0, XN_A(h)>(xv, wv[16 + h], DSW);
            if constexpr (part == 2) wg32_ss<WS_A + i * 128, XN_A(8 + i)>(xk, dk);
            if constexpr (part == 3) wg32_ss<WS_A + 1024 + i * 128, XN_A(8 + i)>(xv, dv);
        });
        wg_commit();
    };
    auto token_softmax = [&]() {
        const int hi = w4 - 2, lane = l16 >> 4;
        const uint32_t src = sb + C_XSL + l16 + hi * 8;
        const int d0 = 16 * role + 8 * hi + (lane >> 2) - 2 * (lane & 3);
        mbar_wait(bar + B_XS * 8, s & 1);
        float e[10];
        float m = -INFINITY;
#pragma unroll
        for (int i = 0; i < 5; i++) {
            __syncwarp();
            const float2 a = lds2f(src + i * 512), b = lds2f(src + 2560 + i * 512);
            e[2 * i] = (i == 0 || d0 >= 8 * (i - 1)) ? a.x + b.x : -INFINITY;
            e[2 * i + 1] = (i == 0 || d0 > 8 * (i - 1)) ? a.y + b.y : -INFINITY;
            m = fmaxf(m, fmaxf(e[2 * i], e[2 * i + 1]));
        }
        m = fmaxf(m, __shfl_xor_sync(~0u, m, 1));
        m = fmaxf(m, __shfl_xor_sync(~0u, m, 2));
        m *= -SM_SCALE;
        float l = 0.f;
#pragma unroll
        for (int i = 0; i < 10; i++) { e[i] = ex2(fmaf(e[i], SM_SCALE, m)); l += e[i]; }
        l += __shfl_xor_sync(~0u, l, 1);
        l += __shfl_xor_sync(~0u, l, 2);
        l = rcp(l);
        const uint32_t pd = sb_v + C_PL + (s & 1) * 2048 + role * 768 + hi * 4, pb = sb_v + C_BAR + (B_P0 + (s & 1)) * 8;
        st_async1(pd + (l16 >> 1), pb, pack2(e[0] * l, e[1] * l));
        st_async1(pd + 256 + l16, pb, pack2(e[2] * l, e[3] * l));
        st_async1(pd + 264 + l16, pb, pack2(e[4] * l, e[5] * l));
        if (role) {
            st_async1(pd + 768 + l16, pb, pack2(e[6] * l, e[7] * l));
            st_async1(pd + 776 + l16, pb, pack2(e[8] * l, e[9] * l));
        }
        if (hi == 0 && l16 == 0) mbar_expect(bar + B_XS * 8, 3072 + role * 2048);
        __syncwarp();
    };

    auto windows = [&](auto first_) {
        constexpr bool FIRST = first_.value;
        const uint64_t dd[4] = {FIRST ? DSW : D.sw[0], FIRST ? DSW : D.sw[1], FIRST ? DSW : D.sw[2], FIRST ? DSW : D.sw[3]};
        TS(5);
        if constexpr (WG == 1) {
            constexpr int NE = ISV ? VEARLY : QSPLIT;
            TS(6);
            stream_a(ic<0>{}, ic<NE>{}, dd[0], dd[1]);
            Stamps st;
            if constexpr (!FIRST) {
                if (ISV) bar_sync(3, 256);
                else {
                    if (NOFILL) wait_clock(clk() + 400);
                    st = load_stamps(g_flag[0], l16, w4 < 2);
                }
            }
            stream_a(ic<NE>{}, ic<32>{}, dd[0], dd[1]);
            if (!NOFILL) bar_arrive(7, 256);
            uint32_t target = 0;
            if (!FIRST && !ISV && w4 < 2) target = latest_stamp(st, g_flag[0], l16, s, sb + C_CAL) + DLY1;
            TS(10);
            if (!NOFILL) {
                wg_wait<0>();
                reg_fence<16>(xk); reg_fence<16>(xv);
                if (w4 == 3) { bar_sync(2, 128); load_tokens(s + 1, 0, 1); }
                else bar_arrive(2, 128);
            }
            TS(7);
            if (!FIRST && !ISV && w4 < 2) {
                const uint32_t dsb = w4 ? sb_v : sb, bytes = w4 ? ONKV * 128 : ONKQ * 256, off = w4 ? role * (ONKV * 128) : 0;
                const char* src = reinterpret_cast<const char*>(&g_xo[s & 3][(w4 ? ostart + (2 - role) * ONKQ : ostart) * 16]) + off;
                wait_clock(target);
                if (elect()) bulk_ld(dsb + C_MB + off, src, bytes, dsb + C_BAR + B_OF * 8);
                __syncwarp();
                TS(8);
            }
        } else {
            if (!NOFILL) {
                mbar_wait(bar + B_XF0 * 8, 0);
                bar_sync(7, 256);
            }
            TS(6);
            stream_a(ic<0>{}, ic<32>{}, dd[0], dd[1]);
        }
        Stamps st;
        if constexpr (WG == 0) {
            if constexpr (!FIRST) {
                const uint32_t dst = sb_o + C_OL + rank * 512 + l16;
                const uint32_t can = sb + C_MB + l16 * 8 + (l16 >> 2), can2 = can + (l16 < (ONK * 2 - 64) * 16 ? 8192 : 0);
                float co[4];
                uint32_t tries = 0;
                TS(7);
                mbar_wait(bar + B_OF * 8, s & 1);
                TS(8);
                auto early = [&]() { return __any_sync(~0u, max(max(lds1u(can), lds1u(can + 4096)), lds1u(can2)) == ~0u); };
                wg8_chain<0, 10, WO_A, MB_A>(co, D.sw[0], D.ns);
                if (__builtin_expect(early(), 0)) {
                    wg_wait<0>();
                    do refetch(sb + C_MB, &g_xo[s & 3][ostart * 16], ONK * 256, bar + B_RT0 * 8, w4, 1, tries); while (early());
                    wg8_chain<0, 10, WO_A, MB_A>(co, DSW, DNS);
                }
                wg_wait<1>();
                bar_arrive(4, 192);
                wg8_chain<10, ONK, WO_A, MB_A>(co, D.sw[0], D.ns);
                bar_arrive(5, 256);
                wg_wait<0>();
                reg_fence<4>(co);
                if (__builtin_expect(st_async4_unless_nan(dst, sb_o + C_BAR + B_OL * 8, co), 0)) {
                    while (incomplete<ONK * 256>(sb + C_MB, l16)) {
                        refetch(sb + C_MB, &g_xo[s & 3][ostart * 16], ONK * 256, bar + B_RT0 * 8, w4, 1, tries);
                        co[0] = co[1] = co[2] = co[3] = 0.f;
#pragma unroll 1
                        for (int i = 0; i < ONK; i++) {
                            wg_fence();
                            wg8_ss<1, WO_A, MB_A>(co, DSW + i * 128, DNS + i * 16);
                            wg_commit();
                            wg_wait<0>();
                        }
                        reg_fence<4>(co);
                    }
                    st_async4(dst, sb_o + C_BAR + B_OL * 8, __float_as_uint(co[0]), __float_as_uint(co[1]), __float_as_uint(co[2]), __float_as_uint(co[3]));
                }
                bar_arrive(13, 160);
                TS(9);
                if (l16 == 0 && w4 == 3) mbar_expect(bar + B_OF * 8, ONK * 256);
                if (!ISV && w4 < 2) {
                    const uint32_t off = u_off + (l16 >> 2), src = sb + C_OL + l16 + w4 * 8;
                    char* gd = reinterpret_cast<char*>(&g_xmem[(s + 1) & 3][0]) + off;
                    mbar_wait(bar + B_OL * 8, s & 1);
                    const float2 a = lds2f(src), b = lds2f(src + 512), c = lds2f(src + 1024), d = lds2f(src + 1536), e = lds2f(src + 2048), f = lds2f(src + 2560);
                    st_relaxed1(gd, movm(pack2((a.x + b.x) + (c.x + d.x) + (e.x + f.x), (a.y + b.y) + (c.y + d.y) + (e.y + f.y))));
                    TS(10);
                    st_relaxed1(reinterpret_cast<char*>(&g_xmem[(s + 3) & 3][0]) + off, ~0u);
                    if (w4 == 0 && l16 == 0) mbar_expect(bar + B_OL * 8, 3072);
                }
                __syncwarp();
            } else {
                wg_wait<0>();
                bar_arrive(4, 192);
                bar_arrive(5, 256);
                mbar_wait(bar + B_WO * 8, 0);
            }
            if (!NOFILL) { reg_fence<16>(xk); reg_fence<16>(xv); }
        } else {
            if (w4 < 2) {
                bar_sync(4, 192);
                const uint32_t dep = lds2u(sb + C_CAL + 8).y;
                const uint32_t v = (gtick_dep(dep) << 6) | s, c = clk();
                if (w4 == 0) {
                    if (!FIRST) {
                        if (l16 == 0) st_relaxed1(my_flag + 96 * FSTR, v);
                        calibrate(sb + C_CAL, 0.75f);
                    }
                } else {
                    if (!FIRST) wait_clock(c + DLYB);
                    load_tokens(s + 1, 0, 0);
                }
            } else if (!ISV && !FIRST && !NOFILL) {
                token_softmax();
                TSX(9, w4 == 2);
            }
            if (!NOFILL) mbar_wait(bar + B_XF1 * 8, 1);
            bar_sync(5, 256);
            if (!FIRST) st = load_stamps(g_flag[1], l16, w4 == 0);
        }
        TS(11);
        auto store_tokens = [&](const float4* r) {
            uint32_t lo[4], hi[4];
#pragma unroll
            for (int j = 0; j < 4; j++) {
                lo[j] = pack2(xk[4 * j] + r[j].x, xk[4 * j + 1] + r[j].y);
                hi[j] = pack2(xk[4 * j + 2] + r[j].z, xk[4 * j + 3] + r[j].w);
            }
            if (!ISV) {
                const uint32_t d = sb + C_QX + WG * 4096 + w4 * 1024 + l16;
                stsm4t(d, lo[0], lo[1], lo[2], lo[3]);
                stsm4t(d + 512, hi[0], hi[1], hi[2], hi[3]);
            } else {
                const uint32_t d = v_row + ((s + 1) & 1) * 10240 + (l16 & 96) * 20 + (l16 & 16) * 5 + ((l16 >> 3) & 48);
                stsm4(d, lo[0], lo[1], lo[2], lo[3]);
                stsm4(d + 160, hi[0], hi[1], hi[2], hi[3]);
            }
        };
        if constexpr (WG == 1) {
            if (!NOFILL) {
                wg_fence();
                static_for<0, 16>([&](auto i) { wg32_rs<1, XN_A(i.value)>(xv, wv[i.value], dd[3]); });
                wg_commit();
                static_for<0, 16>([&](auto i) { wg32_rs<1, XN_A(i.value)>(xk, wk[i.value], dd[2]); });
                wg_commit();
                bar_arrive(7, 256);
                wg_wait<1>();
                reg_fence<16>(xv);
#pragma unroll
                for (int j = 0; j < 4; j++) sts4f(slot + l16 + j * 2048, xv[4 * j], xv[4 * j + 1], xv[4 * j + 2], xv[4 * j + 3]);
                bar_arrive(8, 256);
            }
            uint32_t target = 0;
            if (!FIRST && w4 == 0) target = latest_stamp(st, g_flag[1], l16, s, sb + C_CAL) + DLY2;
            if (!NOFILL) {
                wg_wait<0>();
                reg_fence<16>(xk);
                if (w4 == 3) { bar_sync(2, 128); if (s < NSEG - 2) load_tokens(s + 2, 1, 1); }
                else bar_arrive(2, 128);
            }
            TS(13);
            prefetch();
            if (w4 == 0) {
                const uint4* src = &g_xmem[(s + 1) & 3][0];
                if (l16 < 32) mbar_expect(bar + B_MF0 * 8 + (l16 >> 1), 8192);
                if (!FIRST) { bar_sync(13, 160); TS(3); wait_clock(target); }
                if (elect()) {
                    bulk_ld(sb + C_MB, src, 8192, bar + B_MF0 * 8);
                    bulk_ld(sb + C_MB + 8192, src + 512, 8192, bar + B_MF1 * 8);
                }
                __syncwarp();
                TS(4);
            }
            if (!NOFILL) {
                bar_sync(9, 256);
                float4 r[4];
#pragma unroll
                for (int j = 0; j < 4; j++) r[j] = lds4f(slot + l16 + j * 2048);
                store_tokens(r);
                bar_arrive(10, 256);
            }
        } else {
            if (!NOFILL) {
                mbar_wait(bar + B_XF0 * 8, 1);
                bar_sync(7, 256);
                TS(12);
                wg_fence();
                static_for<0, 16>([&](auto i) { wg32_rs<1, XN_A(i.value)>(xv, wv[i.value], dd[3]); });
                wg_commit();
                static_for<0, 6>([&](auto i) { wg32_rs<1, XN_A(i.value)>(xk, wk[i.value], dd[2]); });
                wg_commit();
                bar_sync(8, 256);
                float4 r[4];
#pragma unroll
                for (int j = 0; j < 4; j++) r[j] = lds4f(slot + l16 + j * 2048);
                wg_wait<1>();
                reg_fence<16>(xv);
#pragma unroll
                for (int j = 0; j < 4; j++) sts4f(slot + l16 + j * 2048, xv[4 * j], xv[4 * j + 1], xv[4 * j + 2], xv[4 * j + 3]);
                bar_arrive(9, 256);
                static_for<6, 16>([&](auto i) { wg32_rs<1, XN_A(i.value)>(xk, wk[i.value], dd[2]); });
                wg_commit();
                wg_wait<0>();
                reg_fence<16>(xk);
                TS(13);
                prefetch();
                store_tokens(r);
                bar_sync(10, 256);
            } else {
                prefetch();
            }
        }
    };

    if (w4 == 0) load_tokens(0, 1, WG);
    mbar_wait(bar + B_WS * 8, 0);
    if (WG == 1 && !NOFILL) mbar_wait(bar + B_XF1 * 8, 0);
    windows(ic<1>{});

#pragma unroll 1
    while (true) {
        s = uni(s + 1);
        asm volatile("" : "+r"(l16), "+r"(a_adr));
        TS_FLUSH(WG);
        TS(0);
        float ck[4], cv[4];
        uint32_t k0[2][4], k1[2][4];
        const uint32_t kl = sb + C_KX + ((l16 & 384) << 2) + (l16 & 112);
        {
            uint32_t tries = 0;
            const uint32_t can = mbw + l16 * 8 + (l16 >> 2);
            if (ISV && !NOFILL) mbar_wait(bar + (B_P0 + ((s - 1) & 1)) * 8, ((s - 1) >> 1) & 1);
            mbar_wait(bar + (B_MF0 + WG) * 8, s & 1);
            TS(1);
            while (true) {
                uint32_t b[2][4], c0, c1;
                float dk[4], dv[4];
                ldsm4(b[0], mbw + l16 + 12 * 512);
                bool bad = false;
#pragma unroll
                for (int i = 0; i < 4; i++) ck[i] = cv[i] = dk[i] = dv[i] = 0.f;
#pragma unroll
                for (int kp = 0; kp < 16; kp++) {
                    const int grp = kp / 5, ph = kp % 5, nx = kp + 1;
                    if (nx < 16) ldsm4(b[nx & 1], mbw + l16 + ((nx % 5) ? (nx / 5) * 4 + (nx % 5) - 1 : 12 + nx / 5) * 512);
                    if (kp == 0) { c0 = lds1u(can); c1 = lds1u(can + 4096); }
                    const uint32_t* bb = b[kp & 1];
                    if (ph) {
                        const int q = (grp * 4 + ph - 1) * 2, i = ph - 1;
                        ldsm4t(pf[i], a_adr + C_WS + (i & 1) * 16384 + (grp * 2 + 2 + (i >> 1)) * 2048);
                        __syncwarp();
                        mma16(cv, wv[q][0], wv[q][1], wv[q][2], wv[q][3], bb[0], bb[1]);
                        mma16(ck, wk[q][0], wk[q][1], wk[q][2], wk[q][3], bb[0], bb[1]);
                        mma16(dv, wv[q + 1][0], wv[q + 1][1], wv[q + 1][2], wv[q + 1][3], bb[2], bb[3]);
                        mma16(dk, wk[q + 1][0], wk[q + 1][1], wk[q + 1][2], wk[q + 1][3], bb[2], bb[3]);
                    } else {
                        mma16(cv, pf[1][0], pf[1][1], pf[1][2], pf[1][3], bb[0], bb[1]);
                        mma16(dv, pf[3][0], pf[3][1], pf[3][2], pf[3][3], bb[2], bb[3]);
                        mma16(ck, pf[0][0], pf[0][1], pf[0][2], pf[0][3], bb[0], bb[1]);
                        mma16(dk, pf[2][0], pf[2][1], pf[2][2], pf[2][3], bb[2], bb[3]);
                    }
                    if (kp == 1) {
                        bad = __any_sync(~0u, max(c0, c1) == ~0u);
                        if (__builtin_expect(bad, 0)) break;
                    }
                }
                if (!bad) {
#pragma unroll
                    for (int i = 0; i < 4; i++) { cv[i] += dv[i]; ck[i] += dk[i]; }
                    sts4f(slot + WG * 2048 + l16, cv[0], cv[1], cv[2], cv[3]);
                    if (!ISV && WG == 0) {
                        const uint32_t ka = kl + (w4 == 1 ? 256 : 0);
                        ldsm4(k0[0], ka); ldsm4(k0[1], ka + 2048);
                        ldsm4(k1[0], ka + 128); ldsm4(k1[1], ka + 128 + 2048);
                    }
                    TS(2);
                    if (__builtin_expect(!bar_sync_unless_nan(cv[0], cv[1]), 1)) break;
                    if (!incomplete<8192>(mbw, l16)) { bar_sync(6, 256); break; }
                }
                refetch(mbw, &g_xmem[s & 3][WG * 512], 8192, bar + (B_RT0 + WG) * 8, w4, 1 + WG, tries);
                prefetch();
            }
        }
        if constexpr (!ISV) {
            const uint32_t lane_b = sb + C_QM + ((l16 >> 1) & 128) + ((l16 & 128) << 2) + (l16 & 112);
            const uint32_t qx = sb + C_QX + WG * 256 + l16 + (l16 & 256);
            const uint32_t xd = sb_x + C_XSL + role * 2560 + l16, xb = sb_x + C_BAR + B_XS * 8;
            uint32_t tick;
            {
                const float4 r = lds4f(slot + (WG ^ 1) * 2048 + l16);
                stsm2t(sb + C_QM + WG * 1024 + w4 * 256 + (l16 & 255), pack2(ck[0] + r.x, ck[1] + r.y), pack2(ck[2] + r.z, ck[3] + r.w));
                if (WG == 1) { tick = gtick(); bar_arrive(6, 256); bar_sync(14, 256); }
                else bar_sync(6, 256);
                TSX(3, WG == 0 && w4 == 0);
            }
            auto tile = [&](float* d, const uint32_t (*q)[4], const uint32_t (*k)[4]) {
                d[0] = d[1] = d[2] = d[3] = 0.f;
#pragma unroll
                for (int i = 0; i < 4; i++) mma16(d, q[i][0], q[i][1], q[i][2], q[i][3], k[i >> 1][(i & 1) * 2], k[i >> 1][(i & 1) * 2 + 1]);
            };
            auto send = [&](int ti, const float* d) {
                st_async4(xd + ti * 512, xb, __float_as_uint(d[0]), __float_as_uint(d[1]), __float_as_uint(d[2]), __float_as_uint(d[3]));
            };
            if constexpr (WG == 0) {
                if (w4 < 2) {
                    uint32_t q0[4], q1[4];
                    const uint32_t dst = sb_v + C_SL + role * 1280 + w4 * 512 + l16;
                    ldsm4(q0, lane_b); ldsm4(q1, lane_b + 256);
                    bar_arrive(14, 256);
                    float s0[4] = {0.f, 0.f, 0.f, 0.f}, s1[4] = {0.f, 0.f, 0.f, 0.f}, s2[4] = {0.f, 0.f, 0.f, 0.f}, s3[4] = {0.f, 0.f, 0.f, 0.f};
                    mma16(s0, q0[0], q0[1], q0[2], q0[3], k0[0][0], k0[0][1]);
                    mma16(s1, q0[0], q0[1], q0[2], q0[3], k0[1][0], k0[1][1]);
                    mma16(s2, q0[0], q0[1], q0[2], q0[3], k1[0][0], k1[0][1]);
                    mma16(s3, q0[0], q0[1], q0[2], q0[3], k1[1][0], k1[1][1]);
                    mma16(s0, q1[0], q1[1], q1[2], q1[3], k0[0][2], k0[0][3]);
                    mma16(s1, q1[0], q1[1], q1[2], q1[3], k0[1][2], k0[1][3]);
                    mma16(s2, q1[0], q1[1], q1[2], q1[3], k1[0][2], k1[0][3]);
                    mma16(s3, q1[0], q1[1], q1[2], q1[3], k1[1][2], k1[1][3]);
                    st_async4(dst, sb_v + C_BAR + B_SC * 8, __float_as_uint(s0[0] + s1[2]), __float_as_uint(s0[1] + s1[3]),
                              __float_as_uint(s2[0] + s3[2]), __float_as_uint(s2[1] + s3[3]));
                    bar_arrive(12, 256);
                    TS(4);
                } else if (w4 == 2) {
                    uint32_t q0[4], q1[4], m0[4], m1[4];
                    const uint32_t dst = sb_v + C_SL + role * 1280 + 1024 + (l16 >> 1);
                    ldsm4(q0, lane_b); ldsm4(m0, sb + C_KM + l16); ldsm4(m1, sb + C_KM + 512 + l16); ldsm4(q1, lane_b + 256);
                    bar_arrive(14, 256);
                    float s0[4] = {0.f, 0.f, 0.f, 0.f}, s1[4] = {0.f, 0.f, 0.f, 0.f};
                    mma16(s0, q0[0], q0[1], q0[2], q0[3], m0[0], m0[1]);
                    mma16(s1, q0[0], q0[1], q0[2], q0[3], m1[0], m1[1]);
                    mma16(s0, q1[0], q1[1], q1[2], q1[3], m0[2], m0[3]);
                    mma16(s1, q1[0], q1[1], q1[2], q1[3], m1[2], m1[3]);
                    st_async2(dst, sb_v + C_BAR + B_SC * 8, __float_as_uint(s0[0] + s1[2]), __float_as_uint(s0[1] + s1[3]));
                    bar_arrive(12, 256);
                    if (s < NSEG - 1) load_tokens(s + 1, 1, 0);
                } else {
                    bar_sync(14, 256);
                    if (!NOFILL) {
                        uint32_t q[4][4], km[2][4];
                        float d0[4], d1[4], d2[4];
#pragma unroll
                        for (int i = 0; i < 4; i++) ldsm4(q[i], qx + i * 1024);
                        ldsm4(km[0], sb + C_KM + l16); ldsm4(km[1], sb + C_KM + 512 + l16);
                        tile(d1, q, k0); tile(d2, q, k1); tile(d0, q, km);
                        reg_fence<4>(d0);
                        bar_sync(12, 256);
                        send(0, d0); send(1, d1); send(2, d2);
                    } else {
                        bar_sync(12, 256);
                    }
                }
                if (__builtin_expect(s == NSEG - 1, 0)) break;
            } else {
                if (w4 == 3 && l16 == 0) st_relaxed1(my_flag, (tick << 6) | s);
                if (!NOFILL) {
                    uint32_t q[4][4];
                    float d0[4], d1[4];
#pragma unroll
                    for (int i = 0; i < 4; i++) ldsm4(q[i], qx + i * 1024);
                    ldsm4(k0[0], kl + w4 * 128); ldsm4(k0[1], kl + w4 * 128 + 2048);
                    ldsm4(k1[0], sb + C_KM + l16); ldsm4(k1[1], sb + C_KM + 512 + l16);
                    tile(d1, q, k0); tile(d0, q, k1);
                    mbar_wait(bar + B_XF1 * 8, s == NSEG - 1);
                    bar_sync(12, 256);
                    send(1 + w4, d1);
                    if (w4 == 0) send(0, d0);
                } else {
                    bar_sync(12, 256);
                }
                if (__builtin_expect(s == NSEG - 1, 0)) { if (w4 >= 2 && !NOFILL) token_softmax(); break; }
            }
        } else {
            const uint32_t lane_b = sb + C_V + w4 * 2560 + (l16 & 112) * 5 + ((l16 >> 3) & 48);
            auto load_values = [&](uint32_t (*vx)[4], uint32_t* vm, int ss) {
#pragma unroll
                for (int j = 0; j < 4; j++) ldsm4(vx[j], lane_b + (ss & 1) * 10240 + j * 640);
                ldsm4(vm, sb + C_V + (ss & 1) * 10240 + w4 * 2560 + 64 + l16 * 5);
            };
            auto token_output = [&](int ss, bool live, auto mid, auto late) {
                uint32_t vx[4][4], vm[4];
                const uint32_t pl = sb + C_PL + (ss & 1) * 2048 + WG * 768;
                const uint2 pm = lds2u(pl + (l16 >> 1));
                const uint4 p0 = lds4u(pl + 256 + l16);
                uint4 p1;
                if (WG) {
                    load_values(vx, vm, ss);
                    p1 = lds4u(pl + 768 + l16);
                } else {
                    const uint32_t a = lane_b + (ss & 1) * 10240 + ((l16 & 256) ? 640 - 32 : 0);
                    ldsm4(vm, sb + C_V + (ss & 1) * 10240 + w4 * 2560 + 64 + l16 * 5);
                    ldsm4(vx[0], a); ldsm4(vx[2], a + 1280);
                    vx[1][0] = vx[0][2]; vx[1][1] = vx[0][3]; vx[3][0] = vx[2][2]; vx[3][1] = vx[2][3];
                }
                mid();
                char* orow = reinterpret_cast<char*>(g_ox) + ((ss * 2 + WG) * (16 * HD * 2) + (u_off >> 3) + (l16 >> 6) * (HD * 2) + (l16 & 48));
                float o[4][4];
#pragma unroll
                for (int j = 0; j < 4; j++) { o[j][0] = o[j][1] = o[j][2] = o[j][3] = 0.f; mma8(o[j], pm.x, pm.y, vm[j]); }
#pragma unroll
                for (int j = 0; j < 4; j++) mma16(o[j], p0.x, p0.y, p0.z, p0.w, vx[j][0], vx[j][1]);
                if (WG) {
#pragma unroll
                    for (int j = 0; j < 4; j++) mma16(o[j], p1.x, p1.y, p1.z, p1.w, vx[j][2], vx[j][3]);
                }
                late();
                st_pred4(orow, make_uint4(pack2(o[0][0], o[0][1]), pack2(o[1][0], o[1][1]), pack2(o[2][0], o[2][1]), pack2(o[3][0], o[3][1])), live);
                st_pred4(orow + 8 * HD * 2, make_uint4(pack2(o[0][2], o[0][3]), pack2(o[1][2], o[1][3]), pack2(o[2][2], o[2][3]), pack2(o[3][2], o[3][3])), live);
            };
            const uint32_t vd = v_row + (s & 1) * 10240 + 64 + (l16 & 96) * 20 + ((l16 & 16) + ((l16 & 128) >> 2)) * 5;
            const float4 r = lds4f(slot + (WG ^ 1) * 2048 + l16);
            __syncwarp();
            auto finish = [&]() {
                stsm2(vd, pack2(ck[0] + r.x, ck[1] + r.y), pack2(ck[2] + r.z, ck[3] + r.w));
                if (WG == 1) {
                    const uint32_t tick = gtick();
                    bar_arrive(11, 256);
                    if (w4 == 3 && l16 == 0) st_relaxed1(my_flag, ((tick - VLEAD) << 6) | s);
                }
                TSX(3, WG == 0 && w4 == 0);
            };
            if (!NOFILL) {
                token_output(s - 1, s > 0, finish, [&]() { if (WG == 1) mbar_wait(bar + B_XF1 * 8, s == NSEG - 1); });
                if (WG == 1 && w4 == 1 && l16 == 0 && s > 0) mbar_expect(bar + (B_P0 + ((s - 1) & 1)) * 8, 2048);
            } else {
                finish();
            }
            TSD(7);
            if (WG == 0) bar_sync(11, 256);
            if (__builtin_expect(s == NSEG - 1, 0)) {
                bar_sync(6, 256);
                if (!NOFILL) {
                    mbar_wait(bar + (B_P0 + (s & 1)) * 8, (s >> 1) & 1);
                    token_output(s, true, []() {}, []() {});
                }
                mbar_wait(bar + B_SC * 8, s & 1);
                break;
            }
            if constexpr (WG == 0) {
                uint32_t vx[4][4], vm[4];
                load_values(vx, vm, s);
                const uint32_t oo = u_off + ((l16 & 48) << 3) + ((l16 >> 2) & 112);
                char* dst = reinterpret_cast<char*>(&g_xo[s & 3][0]) + oo;
                if (w4 == 3) load_tokens(s + 1, 1, 0);
                mbar_wait(bar + B_SC * 8, s & 1);
                TS(4);
                const float4 a0 = lds4f(sb + C_SL + l16), b0 = lds4f(sb + C_SL + 1280 + l16);
                const float4 a1 = lds4f(sb + C_SL + 512 + l16), b1 = lds4f(sb + C_SL + 1280 + 512 + l16);
                const float2 a2 = lds2f(sb + C_SL + 1024 + (l16 >> 1)), b2 = lds2f(sb + C_SL + 1280 + 1024 + (l16 >> 1));
                const float e[10] = {a0.x + b0.x, a0.y + b0.y, a0.z + b0.z, a0.w + b0.w, a1.x + b1.x, a1.y + b1.y, a1.z + b1.z, a1.w + b1.w,
                                     a2.x + b2.x, a2.y + b2.y};
                float m = fmaxf(fmaxf(fmaxf(e[0], e[1]), fmaxf(e[2], e[3])), fmaxf(fmaxf(e[4], e[5]), fmaxf(e[6], e[7])));
                m = fmaxf(m, fmaxf(e[8], e[9]));
                m = fmaxf(fmaxf(m, __shfl_xor_sync(~0u, m, 1)), fmaxf(__shfl_xor_sync(~0u, m, 2), __shfl_xor_sync(~0u, m, 3)));
                m *= -SM_SCALE;
                float x[10];
#pragma unroll
                for (int i = 0; i < 10; i++) x[i] = ex2(fmaf(e[i], SM_SCALE, m));
                float o[4][4];
                const uint32_t p0 = pack2(x[0], x[1]), p1 = pack2(x[2], x[3]), j0 = __float_as_uint(x[1]), j1 = __float_as_uint(x[3]);
#pragma unroll
                for (int j = 0; j < 4; j++) { o[j][0] = o[j][1] = o[j][2] = o[j][3] = 0.f; mma16(o[j], p0, j0, p1, j1, vx[j][0], vx[j][1]); }
                const uint32_t p2 = pack2(x[4], x[5]), p3 = pack2(x[6], x[7]), j2 = __float_as_uint(x[5]), j3 = __float_as_uint(x[7]);
#pragma unroll
                for (int j = 0; j < 4; j++) mma16(o[j], p2, j2, p3, j3, vx[j][2], vx[j][3]);
                const uint32_t p4 = pack2(x[8], x[9]), j4 = __float_as_uint(x[9]);
                float l = (((x[0] + x[1]) + (x[2] + x[3])) + ((x[4] + x[5]) + (x[6] + x[7]))) + (x[8] + x[9]);
                l = (l + __shfl_xor_sync(~0u, l, 1)) + (__shfl_xor_sync(~0u, l, 2) + __shfl_xor_sync(~0u, l, 3));
#pragma unroll
                for (int j = 0; j < 4; j++) mma8(o[j], p4, j4, vm[j]);
                l = rcp(l);
                st_relaxed4(reinterpret_cast<uint4*>(dst), make_uint4(pack2(o[0][0] * l, o[0][1] * l), pack2(o[1][0] * l, o[1][1] * l),
                                                                      pack2(o[2][0] * l, o[2][1] * l), pack2(o[3][0] * l, o[3][1] * l)));
                bar_arrive(3, 256);
                st_relaxed4(reinterpret_cast<uint4*>(reinterpret_cast<char*>(&g_xo[(s + 2) & 3][0]) + oo), make_uint4(~0u, ~0u, ~0u, ~0u));
                if (w4 == 0 && l16 == 0) mbar_expect(bar + B_SC * 8, 2560);
            }
        }
        windows(ic<0>{});
    }
}

__global__ void __cluster_dims__(6, 1, 1) __launch_bounds__(256, 1)
chain_kernel(const __grid_constant__ CUtensorMap tq, const __grid_constant__ CUtensorMap tk, const __grid_constant__ CUtensorMap tv,
             const __grid_constant__ CUtensorMap two, const __grid_constant__ Descs D, const __grid_constant__ Descs DV) {
    extern __shared__ __align__(1024) uint8_t smem[];
    const uint32_t sb = smem_u32(smem);
    const int rank = blockIdx.x % 6, cl = blockIdx.x / 6, role = rank >= 4 ? 2 : rank & 1;
    if (threadIdx.x == 0) {
        if ((sb & 0x3FFFF) != SB0) __trap();
        const uint32_t bar = sb + C_BAR;
        for (int i = 0; i < B_NUM; i++) mbar_init(bar + i * 8, 1);
        if (role == 2) {
            mbar_expect(bar + B_SC * 8, 2560);
            mbar_expect(bar + B_P0 * 8, 2048);
            mbar_expect(bar + B_P1 * 8, 2048);
            mbar_expect(bar + B_OF * 8, ONKV * 256);
        } else {
            mbar_expect(bar + B_XS * 8, role ? 5120 : 3072);
            mbar_expect(bar + B_OL * 8, 3072);
            mbar_expect(bar + B_OF * 8, ONKQ * 256);
        }
        asm volatile("fence.mbarrier_init.release.cluster;" ::: "memory");
        fence_async();
    }
    __syncthreads();
    cluster_sync();
    const int wg = uni(threadIdx.x >> 7);
    if (role == 2) {
        if (wg == 0) chain_main<true, 0>(&tv, &tv, &two, sb, cl, rank, DV);
        else chain_main<true, 1>(&tv, &tv, &two, sb, cl, rank, DV);
    } else {
        if (wg == 0) chain_main<false, 0>(&tq, &tk, &two, sb, cl, rank, D);
        else chain_main<false, 1>(&tq, &tk, &two, sb, cl, rank, D);
    }
    __syncwarp();
    cluster_sync();
}

constexpr int G_STAGES = 4;
constexpr uint32_t G_STAGE = 49152, G_EPI = G_STAGES * G_STAGE, G_BAR = G_EPI + 32768, G_SMEM = G_BAR + 256;

__device__ __forceinline__ void wg256(float* d, uint32_t da, uint32_t db, uint32_t accum) {
    asm volatile("{\n.reg .b64 da, db;\n.reg .pred p;\nsetp.ne.u32 p, %130, 0;\nmov.b64 da, {%128, " DESC_HI_SW128 "};\nmov.b64 db, {%129, " DESC_HI_SW128 "};\n"
                 "wgmma.mma_async.sync.aligned.m64n256k16.f32.bf16.bf16 {"
                 "%0,%1,%2,%3,%4,%5,%6,%7,%8,%9,%10,%11,%12,%13,%14,%15,%16,%17,%18,%19,%20,%21,%22,%23,%24,%25,%26,%27,%28,%29,%30,%31,"
                 "%32,%33,%34,%35,%36,%37,%38,%39,%40,%41,%42,%43,%44,%45,%46,%47,%48,%49,%50,%51,%52,%53,%54,%55,%56,%57,%58,%59,%60,%61,%62,%63,"
                 "%64,%65,%66,%67,%68,%69,%70,%71,%72,%73,%74,%75,%76,%77,%78,%79,%80,%81,%82,%83,%84,%85,%86,%87,%88,%89,%90,%91,%92,%93,%94,%95,"
                 "%96,%97,%98,%99,%100,%101,%102,%103,%104,%105,%106,%107,%108,%109,%110,%111,%112,%113,%114,%115,%116,%117,%118,%119,%120,%121,%122,%123,%124,%125,%126,%127"
                 "}, da, db, p, 1, 1, 0, 1;\n}"
                 : ACC16(d), ACC16((d + 16)), ACC16((d + 32)), ACC16((d + 48)), ACC16((d + 64)), ACC16((d + 80)), ACC16((d + 96)), ACC16((d + 112))
                 : "r"(da), "r"(db), "r"(accum));
}
__device__ __forceinline__ float sigmoidf_(float v) { return rcp(1.f + ex2(-1.4426950408889634f * v)); }

template <int MODE>
__global__ void __cluster_dims__(2, 1, 1) __launch_bounds__(384, 1)
gemm_kernel(const __grid_constant__ CUtensorMap tA, const __grid_constant__ CUtensorMap tB0, const __grid_constant__ CUtensorMap tB1,
            const __grid_constant__ CUtensorMap tOut, const __grid_constant__ CUtensorMap tX, const __grid_constant__ CUtensorMap tY) {
    constexpr int KB = MODE == 0 ? DM / 64 : (MODE == 1 ? FF / 64 : HD / 64);
    constexpr int NT = MODE == 0 ? FF / 128 : DM / 256;
    constexpr int NTILES = NT * 8;
    extern __shared__ __align__(1024) uint8_t smem[];
    const uint32_t sb = smem_u32(smem);
    const uint32_t full = sb + G_BAR, empty = full + 64;
    const int tid = threadIdx.x, lane = tid & 31;
    const int wg = __shfl_sync(~0u, tid >> 7, 0);
    const int rank = blockIdx.x & 1, pair = blockIdx.x >> 1, npair = gridDim.x >> 1;
    if (tid == 0) {
        for (int i = 0; i < G_STAGES; i++) { mbar_init(full + i * 8, 1); mbar_init(empty + i * 8, 16); }
        asm volatile("fence.mbarrier_init.release.cluster;" ::: "memory");
        fence_async();
    }
    __syncthreads();
    cluster_sync();
    if (wg == 0) {
        asm volatile("setmaxnreg.dec.sync.aligned.u32 40;");
        if (tid == 0) {
            uint32_t st = 0, ph = 1;
            for (int tile = pair; tile < NTILES; tile += npair) {
                const int mp = tile & 7, nt = tile >> 3, row0 = (mp * 2 + rank) * 128;
                const CUtensorMap* tB = (MODE == 0 && rank) ? &tB1 : &tB0;
                const int bcol = MODE == 0 ? nt * 128 : nt * 256 + rank * 128;
                for (int kb = 0; kb < KB; kb++) {
                    mbar_wait(empty + st * 8, ph);
                    const uint32_t base = sb + st * G_STAGE;
                    mbar_expect(full + st * 8, G_STAGE);
                    tma2d(base, &tA, kb * 64, row0, full + st * 8);
                    tma2d_mc(base + 16384 + rank * 16384, tB, bcol, kb * 64, full + st * 8, 3);
                    tma2d_mc(base + 16384 + rank * 16384 + 8192, tB, bcol + 64, kb * 64, full + st * 8, 3);
                    if (++st == G_STAGES) { st = 0; ph ^= 1; }
                }
                if (MODE == 2) {
                    for (int q = 0; q < 4; q++) {
                        mbar_wait(empty + st * 8, ph);
                        const uint32_t base = sb + st * G_STAGE;
                        mbar_expect(full + st * 8, 32768);
                        tma2d(base, &tX, nt * 256 + q * 64, row0, full + st * 8);
                        tma2d(base + 16384, &tY, nt * 256 + q * 64, row0, full + st * 8);
                        if (++st == G_STAGES) { st = 0; ph ^= 1; }
                    }
                }
            }
        }
        __syncwarp();
        cluster_sync();
    } else {
        asm volatile("setmaxnreg.inc.sync.aligned.u32 232;");
        const int cw = wg - 1, w4 = (tid >> 5) & 3;
        const uint32_t empty_dst = mapa(empty, lane & 1);
        const uint32_t epi = sb + G_EPI + cw * 16384;
        const int er = w4 * 16 + (lane & 15), ec = lane >> 4;
        uint32_t st = 0, ph = 0;
        float acc[128];
        for (int tile = pair; tile < NTILES; tile += npair) {
            const int mp = tile & 7, nt = tile >> 3, row0 = (mp * 2 + rank) * 128 + cw * 64;
            uint32_t prev = 0;
#pragma unroll 1
            for (int kb = 0; kb < KB; kb++) {
                mbar_wait(full + st * 8, ph);
                const uint32_t base = sb + st * G_STAGE;
                const uint32_t da = (((base + cw * 8192) & 0x3FFFF) >> 4) | (1u << 16);
                const uint32_t db = (((base + 16384) & 0x3FFFF) >> 4) | (512u << 16);
                wg_fence();
#pragma unroll
                for (int k = 0; k < 4; k++) wg256(acc, da + k * 2, db + k * 128, (kb | k) != 0);
                wg_commit();
                if (kb > 0) {
                    wg_wait<1>();
                    if (lane < 2) mbar_arrive_cluster(empty_dst + prev * 8);
                }
                prev = st;
                if (++st == G_STAGES) { st = 0; ph ^= 1; }
            }
            wg_wait<0>();
            reg_fence<128>(acc);
            if (lane < 2) mbar_arrive_cluster(empty_dst + prev * 8);
#pragma unroll
            for (int hp = 0; hp < (MODE == 0 ? 1 : 2); hp++) {
                uint32_t o[32];
#pragma unroll
                for (int bx = 0; bx < 2; bx++) {
                    uint32_t xa = 0;
                    if (MODE == 2) {
                        mbar_wait(full + st * 8, ph);
                        xa = sb + st * G_STAGE + (cw * 64 + er) * 128;
                    }
#pragma unroll
                    for (int j = 0; j < 4; j++) {
                        const int a0 = hp * 64 + bx * 32 + j * 8;
                        uint32_t* oo = o + bx * 16 + j * 4;
                        if (MODE == 0) {
#pragma unroll
                            for (int i = 0; i < 4; i++)
                                oo[i] = pack2(sigmoidf_(acc[a0 + 2 * i]) * acc[64 + a0 + 2 * i], sigmoidf_(acc[a0 + 2 * i + 1]) * acc[64 + a0 + 2 * i + 1]);
                        } else if (MODE == 1) {
#pragma unroll
                            for (int i = 0; i < 4; i++)
                                oo[i] = pack2(sigmoidf_(acc[a0 + 2 * i]) * acc[a0 + 2 * i], sigmoidf_(acc[a0 + 2 * i + 1]) * acc[a0 + 2 * i + 1]);
                        } else {
                            uint32_t xv[4], yv[4];
                            const uint32_t ad = xa + (((2 * j + ec) ^ (er & 7)) << 4);
                            ldsm4(xv, ad); ldsm4(yv, ad + 16384);
#pragma unroll
                            for (int i = 0; i < 4; i++)
                                oo[i] = pack2(fmaf(acc[a0 + 2 * i], bf_lo(yv[i]), bf_lo(xv[i])), fmaf(acc[a0 + 2 * i + 1], bf_hi(yv[i]), bf_hi(xv[i])));
                        }
                    }
                    if (MODE == 2) {
                        __syncwarp();
                        if (lane < 2) mbar_arrive_cluster(empty_dst + st * 8);
                        if (++st == G_STAGES) { st = 0; ph ^= 1; }
                    }
                }
                if ((tid & 127) == 0) asm volatile("cp.async.bulk.wait_group.read 0;" ::: "memory");
                bar_sync(1 + cw, 128);
#pragma unroll
                for (int bx = 0; bx < 2; bx++)
#pragma unroll
                    for (int j = 0; j < 4; j++) {
                        const uint32_t* oo = o + bx * 16 + j * 4;
                        stsm4(epi + bx * 8192 + er * 128 + (((2 * j + ec) ^ (er & 7)) << 4), oo[0], oo[1], oo[2], oo[3]);
                    }
                fence_async();
                bar_sync(1 + cw, 128);
                if ((tid & 127) == 0) {
                    const int col = MODE == 0 ? nt * 128 : nt * 256 + hp * 128;
                    tma2d_store(&tOut, col, row0, epi);
                    tma2d_store(&tOut, col + 64, row0, epi + 8192);
                    asm volatile("cp.async.bulk.commit_group;" ::: "memory");
                }
            }
        }
        if ((tid & 127) == 0) asm volatile("cp.async.bulk.wait_group 0;" ::: "memory");
        __syncwarp();
        cluster_sync();
    }
}

typedef CUresult (*EncodeFn)(CUtensorMap*, CUtensorMapDataType, cuuint32_t, void*, const cuuint64_t*, const cuuint64_t*, const cuuint32_t*,
                             const cuuint32_t*, CUtensorMapInterleave, CUtensorMapSwizzle, CUtensorMapL2promotion, CUtensorMapFloatOOBfill);

CUtensorMap make_map(EncodeFn enc, const void* p, int rows, int cols, int box_rows) {
    CUtensorMap m;
    cuuint64_t dims[2] = {(cuuint64_t)cols, (cuuint64_t)rows}, strides[1] = {(cuuint64_t)cols * 2};
    cuuint32_t box[2] = {64, (cuuint32_t)box_rows}, es[2] = {1, 1};
    enc(&m, CU_TENSOR_MAP_DATA_TYPE_BFLOAT16, 2, const_cast<void*>(p), dims, strides, box, es, CU_TENSOR_MAP_INTERLEAVE_NONE,
        CU_TENSOR_MAP_SWIZZLE_128B, CU_TENSOR_MAP_L2_PROMOTION_L2_128B, CU_TENSOR_MAP_FLOAT_OOB_FILL_NONE);
    return m;
}

}

extern "C" void kernel_launch(void* const* d_in, const int* in_sizes, int n_in, void* d_out, int out_size) {
    const __nv_bfloat16* x = (const __nv_bfloat16*)d_in[0];
    const __nv_bfloat16* mem0 = (const __nv_bfloat16*)d_in[1];
    void* fn = nullptr;
    cudaDriverEntryPointQueryResult qr;
    cudaGetDriverEntryPoint("cuTensorMapEncodeTiled", &fn, cudaEnableDefault, &qr);
    EncodeFn enc = (EncodeFn)fn;
    void *xn, *ox, *h, *y;
    cudaGetSymbolAddress(&xn, g_xn); cudaGetSymbolAddress(&ox, g_ox); cudaGetSymbolAddress(&h, g_h); cudaGetSymbolAddress(&y, g_y);

    const CUtensorMap tq = make_map(enc, d_in[2], DM, HD, 128), tk = make_map(enc, d_in[3], DM, HD, 128), tv = make_map(enc, d_in[4], DM, HD, 128);
    const CUtensorMap two16 = make_map(enc, d_in[5], HD, DM, 16);
    const CUtensorMap txn128 = make_map(enc, xn, SEQ, DM, 128), tg = make_map(enc, d_in[8], DM, FF, 64), tu = make_map(enc, d_in[9], DM, FF, 64);
    const CUtensorMap th64 = make_map(enc, h, SEQ, FF, 64), th128 = make_map(enc, h, SEQ, FF, 128), td = make_map(enc, d_in[10], FF, DM, 64);
    const CUtensorMap ty64 = make_map(enc, y, SEQ, DM, 64), ty128 = make_map(enc, y, SEQ, DM, 128), tx128 = make_map(enc, x, SEQ, DM, 128);
    const CUtensorMap tox = make_map(enc, ox, SEQ, HD, 128), two64 = make_map(enc, d_in[5], HD, DM, 64), tout = make_map(enc, d_out, SEQ, DM, 64);

    cudaFuncSetAttribute(chain_kernel, cudaFuncAttributeMaxDynamicSharedMemorySize, C_SMEM);
    cudaFuncSetAttribute(gemm_kernel<0>, cudaFuncAttributeMaxDynamicSharedMemorySize, G_SMEM);
    cudaFuncSetAttribute(gemm_kernel<1>, cudaFuncAttributeMaxDynamicSharedMemorySize, G_SMEM);
    cudaFuncSetAttribute(gemm_kernel<2>, cudaFuncAttributeMaxDynamicSharedMemorySize, G_SMEM);

    cudaStream_t st = cudaStreamPerThread;
    ln_kernel<<<SEQ / 8, 256, 0, st>>>(x, mem0);
    Descs D;
    for (int i = 0; i < 4; i++) D.sw[i] = DSW;
    D.ns = DNS;
    chain_kernel<<<96, 256, C_SMEM, st>>>(tq, tk, tv, two16, D, D);
    gemm_kernel<0><<<132, 384, G_SMEM, st>>>(txn128, tg, tu, th64, th64, th64);
    gemm_kernel<1><<<64, 384, G_SMEM, st>>>(th128, td, td, ty64, ty64, ty64);
    gemm_kernel<2><<<64, 384, G_SMEM, st>>>(tox, two64, two64, tout, tx128, ty128);
}
```

```cpp
#include <cuda_runtime.h>
#include <cuda_bf16.h>
#include <cuda.h>
#include <stdint.h>
#include <type_traits>

namespace {

constexpr int SEQ = 2048, DM = 1024, HD = 4096, FF = 3584, NSEG = 64;

__device__ __align__(1024) __nv_bfloat16 g_xn[SEQ * DM];
__device__ __align__(1024) uint4 g_xc[SEQ * DM / 8];
__device__ __align__(1024) __nv_bfloat16 g_ox[SEQ * HD];
__device__ __align__(1024) __nv_bfloat16 g_h[SEQ * FF];
__device__ __align__(1024) __nv_bfloat16 g_y[SEQ * DM];
__device__ __align__(1024) uint4 g_xmem[4][1024];
__device__ __align__(1024) uint4 g_xo[4][4096];
#define FSTR 8
__device__ __align__(1024) uint32_t g_flag[2][96 * FSTR];

__device__ __forceinline__ uint32_t smem_u32(const void* p) { return (uint32_t)__cvta_generic_to_shared(p); }
__device__ __forceinline__ uint32_t mapa(uint32_t a, uint32_t r) {
    uint32_t o; asm("mapa.shared::cluster.u32 %0, %1, %2;" : "=r"(o) : "r"(a), "r"(r)); return o;
}
__device__ __forceinline__ void mbar_init(uint32_t a, uint32_t cnt) {
    asm volatile("mbarrier.init.shared.b64 [%0], %1;" :: "r"(a), "r"(cnt) : "memory");
}
__device__ __forceinline__ void mbar_expect(uint32_t a, uint32_t bytes) {
    asm volatile("mbarrier.arrive.expect_tx.shared.b64 _, [%0], %1;" :: "r"(a), "r"(bytes) : "memory");
}
__device__ __forceinline__ void mbar_arrive_cluster(uint32_t a) {
    asm volatile("mbarrier.arrive.shared::cluster.b64 _, [%0];" :: "r"(a) : "memory");
}
__device__ __forceinline__ void spin_guard(uint32_t& it) {
    asm volatile("{\n.reg .pred p;\nadd.u32 %0, %0, 1;\nsetp.gt.u32 p, %0, 0x400000;\n@p st.shared.u32 [%0], %0;\n}" : "+r"(it));
}
__device__ __forceinline__ void mbar_wait(uint32_t a, uint32_t par) {
    asm volatile("{\n.reg .pred p;\n.reg .u32 i;\nmov.u32 i, 0;\n"
                 "WL:\nadd.u32 i, i, 1;\nsetp.gt.u32 p, i, 0x400000;\n@p st.shared.u32 [i], i;\n"
                 "mbarrier.try_wait.parity.shared::cta.b64 p, [%0], %1;\n@!p bra WL;\n}" :: "r"(a), "r"(par) : "memory");
}
__device__ __forceinline__ void mbar_arrive(uint32_t a) { asm volatile("mbarrier.arrive.shared.b64 _, [%0];" :: "r"(a) : "memory"); }
__device__ __forceinline__ void tma2d(uint32_t dst, const CUtensorMap* m, int c0, int c1, uint32_t bar) {
    asm volatile("cp.async.bulk.tensor.2d.shared::cluster.global.mbarrier::complete_tx::bytes [%0], [%1, {%3, %4}], [%2];"
                 :: "r"(dst), "l"(m), "r"(bar), "r"(c0), "r"(c1) : "memory");
}
__device__ __forceinline__ void tma2d_mc(uint32_t dst, const CUtensorMap* m, int c0, int c1, uint32_t bar, uint16_t mask) {
    asm volatile("cp.async.bulk.tensor.2d.shared::cluster.global.mbarrier::complete_tx::bytes.multicast::cluster [%0], [%1, {%3, %4}], [%2], %5;"
                 :: "r"(dst), "l"(m), "r"(bar), "r"(c0), "r"(c1), "h"(mask) : "memory");
}
__device__ __forceinline__ void bulk_mc(uint32_t dst, const void* src, uint32_t bytes, uint32_t bar, uint16_t mask) {
    asm volatile("cp.async.bulk.shared::cluster.global.mbarrier::complete_tx::bytes.multicast::cluster [%0], [%1], %2, [%3], %4;"
                 :: "r"(dst), "l"(src), "r"(bytes), "r"(bar), "h"(mask) : "memory");
}
__device__ __forceinline__ void bulk_ld(uint32_t dst, const void* src, uint32_t bytes, uint32_t bar) {
    asm volatile("cp.async.bulk.shared::cluster.global.mbarrier::complete_tx::bytes [%0], [%1], %2, [%3];"
                 :: "r"(dst), "l"(src), "r"(bytes), "r"(bar) : "memory");
}
__device__ __forceinline__ uint32_t gtick() { uint32_t c; asm volatile("mov.u32 %0, %%globaltimer_lo;" : "=r"(c)); return c >> 5; }
__device__ __forceinline__ uint32_t gtick_dep(uint32_t zero) {
    uint32_t c;
    asm volatile("{\n.reg .pred p;\nsetp.eq.u32 p, %1, 0;\nmov.u32 %0, 0;\n@p mov.u32 %0, %%globaltimer_lo;\n}" : "=r"(c) : "r"(zero));
    return c >> 5;
}
__device__ __forceinline__ uint32_t ld_relaxed1(const void* p) {
    uint32_t v; asm volatile("ld.relaxed.gpu.global.u32 %0, [%1];" : "=r"(v) : "l"(p) : "memory"); return v;
}
__device__ __forceinline__ bool any_nan(float a, float b) {
    uint32_t r;
    asm volatile("{\n.reg .pred p;\nsetp.nan.f32 p, %1, %2;\nvote.sync.any.pred p, p, 0xffffffff;\nselp.u32 %0, 1, 0, p;\n}" : "=r"(r) : "f"(a), "f"(b));
    return r;
}
__device__ __forceinline__ bool any_nan_unless(float a, float b, uint32_t off) {
    uint32_t r;
    asm volatile("{\n.reg .pred p, q;\nsetp.ne.u32 q, %3, 0xffffffff;\nsetp.nan.and.f32 p, %1, %2, q;\nvote.sync.any.pred p, p, 0xffffffff;\nselp.u32 %0, 1, 0, p;\n}"
                 : "=r"(r) : "f"(a), "f"(b), "r"(off));
    return r;
}
__device__ __forceinline__ bool st_async4_unless_nan(uint32_t a, uint32_t bar, const float* v) {
    uint32_t r;
    asm volatile("{\n.reg .pred p;\nsetp.nan.f32 p, %3, %4;\nvote.sync.any.pred p, p, 0xffffffff;\n"
                 "@!p st.async.shared::cluster.mbarrier::complete_tx::bytes.v4.f32 [%1], {%3,%4,%5,%6}, [%2];\nselp.u32 %0, 1, 0, p;\n}"
                 : "=r"(r) : "r"(a), "r"(bar), "f"(v[0]), "f"(v[1]), "f"(v[2]), "f"(v[3]) : "memory");
    return r;
}
__device__ __forceinline__ void bar_arrive(int id, int n) { asm volatile("bar.arrive %0, %1;" :: "r"(id), "r"(n) : "memory"); }
__device__ __forceinline__ uint32_t clk() { uint32_t c; asm volatile("mov.u32 %0, %%clock;" : "=r"(c)); return c; }
__device__ __forceinline__ void tma2d_store(const CUtensorMap* m, int c0, int c1, uint32_t src) {
    asm volatile("cp.async.bulk.tensor.2d.global.shared::cta.bulk_group [%0, {%1, %2}], [%3];"
                 :: "l"(m), "r"(c0), "r"(c1), "r"(src) : "memory");
}
__device__ __forceinline__ void bar_sync(int id, int n) { asm volatile("bar.sync %0, %1;" :: "r"(id), "r"(n) : "memory"); }
__device__ __forceinline__ void fence_async() { asm volatile("fence.proxy.async.shared::cta;" ::: "memory"); }
__device__ __forceinline__ void cluster_sync() {
    asm volatile("barrier.cluster.arrive.release.aligned;\nbarrier.cluster.wait.acquire.aligned;" ::: "memory");
}
__device__ __forceinline__ void ldsm4(uint32_t* r, uint32_t a) {
    asm volatile("ldmatrix.sync.aligned.m8n8.x4.shared.b16 {%0,%1,%2,%3}, [%4];"
                 : "=r"(r[0]), "=r"(r[1]), "=r"(r[2]), "=r"(r[3]) : "r"(a) : "memory");
}
__device__ __forceinline__ void ldsm4t(uint32_t* r, uint32_t a) {
    asm volatile("ldmatrix.sync.aligned.m8n8.x4.trans.shared.b16 {%0,%1,%2,%3}, [%4];"
                 : "=r"(r[0]), "=r"(r[1]), "=r"(r[2]), "=r"(r[3]) : "r"(a) : "memory");
}
__device__ __forceinline__ void stsm4(uint32_t a, uint32_t r0, uint32_t r1, uint32_t r2, uint32_t r3) {
    asm volatile("stmatrix.sync.aligned.m8n8.x4.shared.b16 [%0], {%1,%2,%3,%4};" :: "r"(a), "r"(r0), "r"(r1), "r"(r2), "r"(r3) : "memory");
}
__device__ __forceinline__ void stsm4t(uint32_t a, uint32_t r0, uint32_t r1, uint32_t r2, uint32_t r3) {
    asm volatile("stmatrix.sync.aligned.m8n8.x4.trans.shared.b16 [%0], {%1,%2,%3,%4};" :: "r"(a), "r"(r0), "r"(r1), "r"(r2), "r"(r3) : "memory");
}
__device__ __forceinline__ void stsm2(uint32_t a, uint32_t r0, uint32_t r1) {
    asm volatile("stmatrix.sync.aligned.m8n8.x2.shared.b16 [%0], {%1,%2};" :: "r"(a), "r"(r0), "r"(r1) : "memory");
}
__device__ __forceinline__ void stsm2t(uint32_t a, uint32_t r0, uint32_t r1) {
    asm volatile("stmatrix.sync.aligned.m8n8.x2.trans.shared.b16 [%0], {%1,%2};" :: "r"(a), "r"(r0), "r"(r1) : "memory");
}
__device__ __forceinline__ uint32_t movm(uint32_t a) {
    uint32_t d; asm volatile("movmatrix.sync.aligned.m8n8.trans.b16 %0, %1;" : "=r"(d) : "r"(a)); return d;
}
__device__ __forceinline__ void mma16(float* d, uint32_t a0, uint32_t a1, uint32_t a2, uint32_t a3, uint32_t b0, uint32_t b1) {
    asm volatile("mma.sync.aligned.m16n8k16.row.col.f32.bf16.bf16.f32 {%0,%1,%2,%3}, {%4,%5,%6,%7}, {%8,%9}, {%0,%1,%2,%3};"
                 : "+f"(d[0]), "+f"(d[1]), "+f"(d[2]), "+f"(d[3]) : "r"(a0), "r"(a1), "r"(a2), "r"(a3), "r"(b0), "r"(b1));
}
__device__ __forceinline__ void mma8(float* d, uint32_t a0, uint32_t a1, uint32_t b0) {
    asm volatile("mma.sync.aligned.m16n8k8.row.col.f32.bf16.bf16.f32 {%0,%1,%2,%3}, {%4,%5}, {%6}, {%0,%1,%2,%3};"
                 : "+f"(d[0]), "+f"(d[1]), "+f"(d[2]), "+f"(d[3]) : "r"(a0), "r"(a1), "r"(b0));
}
__device__ __forceinline__ uint32_t pack2(float lo, float hi) {
    uint32_t r; asm("cvt.rn.bf16x2.f32 %0, %1, %2;" : "=r"(r) : "f"(hi), "f"(lo)); return r;
}
__device__ __forceinline__ float bf_lo(uint32_t v) { return __uint_as_float(v << 16); }
__device__ __forceinline__ float bf_hi(uint32_t v) { return __uint_as_float(v & 0xFFFF0000u); }
__device__ __forceinline__ float ex2(float x) { float y; asm("ex2.approx.ftz.f32 %0, %1;" : "=f"(y) : "f"(x)); return y; }
__device__ __forceinline__ float rcp(float x) { float y; asm("rcp.approx.ftz.f32 %0, %1;" : "=f"(y) : "f"(x)); return y; }
__device__ __forceinline__ void sts4f(uint32_t a, float x, float y, float z, float w) {
    asm volatile("st.shared.v4.f32 [%0], {%1,%2,%3,%4};" :: "r"(a), "f"(x), "f"(y), "f"(z), "f"(w) : "memory");
}
__device__ __forceinline__ void sts4u(uint32_t a, uint4 v) {
    asm volatile("st.shared.v4.u32 [%0], {%1,%2,%3,%4};" :: "r"(a), "r"(v.x), "r"(v.y), "r"(v.z), "r"(v.w) : "memory");
}
__device__ __forceinline__ float4 lds4f(uint32_t a) {
    float4 v; asm volatile("ld.shared.v4.f32 {%0,%1,%2,%3}, [%4];" : "=f"(v.x), "=f"(v.y), "=f"(v.z), "=f"(v.w) : "r"(a) : "memory"); return v;
}
__device__ __forceinline__ float2 lds2f(uint32_t a) {
    float2 v; asm volatile("ld.shared.v2.f32 {%0,%1}, [%2];" : "=f"(v.x), "=f"(v.y) : "r"(a) : "memory"); return v;
}
__device__ __forceinline__ uint4 lds4u(uint32_t a) {
    uint4 v; asm volatile("ld.shared.v4.u32 {%0,%1,%2,%3}, [%4];" : "=r"(v.x), "=r"(v.y), "=r"(v.z), "=r"(v.w) : "r"(a) : "memory"); return v;
}
__device__ __forceinline__ uint32_t lds1u(uint32_t a) {
    uint32_t v; asm volatile("ld.shared.u32 %0, [%1];" : "=r"(v) : "r"(a) : "memory"); return v;
}
__device__ __forceinline__ uint2 lds2u(uint32_t a) {
    uint2 v; asm volatile("ld.shared.v2.u32 {%0,%1}, [%2];" : "=r"(v.x), "=r"(v.y) : "r"(a) : "memory"); return v;
}
__device__ __forceinline__ void st_async4(uint32_t a, uint32_t bar, uint32_t x, uint32_t y, uint32_t z, uint32_t w) {
    asm volatile("st.async.shared::cluster.mbarrier::complete_tx::bytes.v4.b32 [%0], {%1,%2,%3,%4}, [%5];"
                 :: "r"(a), "r"(x), "r"(y), "r"(z), "r"(w), "r"(bar) : "memory");
}
__device__ __forceinline__ void st_async2(uint32_t a, uint32_t bar, uint32_t x, uint32_t y) {
    asm volatile("st.async.shared::cluster.mbarrier::complete_tx::bytes.v2.b32 [%0], {%1,%2}, [%3];"
                 :: "r"(a), "r"(x), "r"(y), "r"(bar) : "memory");
}
__device__ __forceinline__ void st_async1(uint32_t a, uint32_t bar, uint32_t x) {
    asm volatile("st.async.shared::cluster.mbarrier::complete_tx::bytes.b32 [%0], %1, [%2];" :: "r"(a), "r"(x), "r"(bar) : "memory");
}
__device__ __forceinline__ uint4 ld_relaxed4(const uint4* p) {
    uint4 v;
    asm volatile("ld.relaxed.gpu.global.v4.u32 {%0,%1,%2,%3}, [%4];" : "=r"(v.x), "=r"(v.y), "=r"(v.z), "=r"(v.w) : "l"(p) : "memory");
    return v;
}
__device__ __forceinline__ void st_relaxed4(uint4* p, uint4 v) {
    asm volatile("st.relaxed.gpu.global.v4.u32 [%0], {%1,%2,%3,%4};" :: "l"(p), "r"(v.x), "r"(v.y), "r"(v.z), "r"(v.w) : "memory");
}
__device__ __forceinline__ void st_pred1(void* p, uint32_t v, bool on) {
    asm volatile("{\n.reg .pred p;\nsetp.ne.u32 p, %2, 0;\n@p st.relaxed.gpu.global.u32 [%0], %1;\n}" :: "l"(p), "r"(v), "r"((uint32_t)on) : "memory");
}
__device__ __forceinline__ void st_pred4(void* p, uint4 v, bool on) {
    asm volatile("{\n.reg .pred p;\nsetp.ne.u32 p, %5, 0;\n@p st.global.v4.u32 [%0], {%1,%2,%3,%4};\n}"
                 :: "l"(p), "r"(v.x), "r"(v.y), "r"(v.z), "r"(v.w), "r"((uint32_t)on) : "memory");
}
__device__ __forceinline__ void st_relaxed1(void* p, uint32_t v) {
    asm volatile("st.relaxed.gpu.global.u32 [%0], %1;" :: "l"(p), "r"(v) : "memory");
}
__device__ __forceinline__ uint32_t umax4(uint4 v) { return max(max(v.x, v.y), max(v.z, v.w)); }
__device__ __forceinline__ void wg_fence() { asm volatile("wgmma.fence.sync.aligned;" ::: "memory"); }
__device__ __forceinline__ void wg_commit() { asm volatile("wgmma.commit_group.sync.aligned;" ::: "memory"); }
template <int N> __device__ __forceinline__ void wg_wait() { asm volatile("wgmma.wait_group.sync.aligned %0;" :: "n"(N) : "memory"); }
template <int N> __device__ __forceinline__ void reg_fence(float* d) {
#pragma unroll
    for (int i = 0; i < N; i++) asm volatile("" : "+f"(d[i]) :: "memory");
}
#define ACC16(d) "+f"(d[0]), "+f"(d[1]), "+f"(d[2]), "+f"(d[3]), "+f"(d[4]), "+f"(d[5]), "+f"(d[6]), "+f"(d[7]), \
                 "+f"(d[8]), "+f"(d[9]), "+f"(d[10]), "+f"(d[11]), "+f"(d[12]), "+f"(d[13]), "+f"(d[14]), "+f"(d[15])
#define DESC_HI_SW128 "0x40000040"
#define OUT16(d) "=f"(d[0]), "=f"(d[1]), "=f"(d[2]), "=f"(d[3]), "=f"(d[4]), "=f"(d[5]), "=f"(d[6]), "=f"(d[7]), \
                 "=f"(d[8]), "=f"(d[9]), "=f"(d[10]), "=f"(d[11]), "=f"(d[12]), "=f"(d[13]), "=f"(d[14]), "=f"(d[15])
template <int ACCUM, int BOFF>
__device__ __forceinline__ void wg32_rs(float* d, const uint32_t* a, uint64_t dsw) {
    if (ACCUM)
        asm volatile("{\n.reg .b64 db;\nadd.s64 db, %20, %21;\n"
                     "wgmma.mma_async.sync.aligned.m64n32k16.f32.bf16.bf16 {%0,%1,%2,%3,%4,%5,%6,%7,%8,%9,%10,%11,%12,%13,%14,%15}, "
                     "{%16,%17,%18,%19}, db, 1, 1, 1, 0;\n}"
                     : ACC16(d) : "r"(a[0]), "r"(a[1]), "r"(a[2]), "r"(a[3]), "l"(dsw), "n"(BOFF));
    else
        asm volatile("{\n.reg .b64 db;\nadd.s64 db, %20, %21;\n"
                     "wgmma.mma_async.sync.aligned.m64n32k16.f32.bf16.bf16 {%0,%1,%2,%3,%4,%5,%6,%7,%8,%9,%10,%11,%12,%13,%14,%15}, "
                     "{%16,%17,%18,%19}, db, 0, 1, 1, 0;\n}"
                     : OUT16(d) : "r"(a[0]), "r"(a[1]), "r"(a[2]), "r"(a[3]), "l"(dsw), "n"(BOFF));
}
template <int AOFF, int BOFF>
__device__ __forceinline__ void wg32_ss(float* d, uint64_t dsw) {
    asm volatile("{\n.reg .b64 da, db;\nadd.s64 da, %16, %17;\nadd.s64 db, %16, %18;\n"
                 "wgmma.mma_async.sync.aligned.m64n32k16.f32.bf16.bf16 {%0,%1,%2,%3,%4,%5,%6,%7,%8,%9,%10,%11,%12,%13,%14,%15}, "
                 "da, db, 1, 1, 1, 1, 0;\n}"
                 : ACC16(d) : "l"(dsw), "n"(AOFF), "n"(BOFF));
}
template <int ACCUM, int AOFF, int BOFF>
__device__ __forceinline__ void wg8_ss(float* d, uint64_t dsw, uint64_t dns) {
    if (!ACCUM)
        asm volatile("{\n.reg .b64 da, db;\nadd.s64 da, %4, %6;\nadd.s64 db, %5, %7;\n"
                     "wgmma.mma_async.sync.aligned.m64n8k16.f32.bf16.bf16 {%0,%1,%2,%3}, da, db, 0, 1, 1, 1, 0;\n}"
                     : "=f"(d[0]), "=f"(d[1]), "=f"(d[2]), "=f"(d[3]) : "l"(dsw), "l"(dns), "n"(AOFF), "n"(BOFF));
    else
        asm volatile("{\n.reg .b64 da, db;\nadd.s64 da, %4, %6;\nadd.s64 db, %5, %7;\n"
                     "wgmma.mma_async.sync.aligned.m64n8k16.f32.bf16.bf16 {%0,%1,%2,%3}, da, db, 1, 1, 1, 1, 0;\n}"
                     : "+f"(d[0]), "+f"(d[1]), "+f"(d[2]), "+f"(d[3]) : "l"(dsw), "l"(dns), "n"(AOFF), "n"(BOFF));
}
template <int I0, int I1, class F>
__device__ __forceinline__ void static_for(F&& f) {
    if constexpr (I0 < I1) { f(std::integral_constant<int, I0>{}); static_for<I0 + 1, I1>(f); }
}
template <int I0, int I1, int AOFF, int BOFF>
__device__ __forceinline__ void wg8_chain(float* d, uint64_t dsw, uint64_t dns) {
    wg_fence();
    static_for<I0, I1>([&](auto i) { wg8_ss<i.value != 0, AOFF + i.value * 128, BOFF + i.value * 16>(d, dsw, dns); });
    wg_commit();
}

__global__ void __launch_bounds__(256) ln_kernel(const __nv_bfloat16* __restrict__ x, const __nv_bfloat16* __restrict__ mem0) {
    const int lane = threadIdx.x & 31, row = blockIdx.x * 8 + (threadIdx.x >> 5);
    const uint4* src = reinterpret_cast<const uint4*>(x + (size_t)row * DM);
    uint4 v[4];
#pragma unroll
    for (int j = 0; j < 4; j++) v[j] = src[j * 32 + lane];
    const int gi = blockIdx.x * 256 + threadIdx.x;
    const uint4 poison = make_uint4(~0u, ~0u, ~0u, ~0u);
    if (gi < 1024) {
        uint4 m = reinterpret_cast<const uint4*>(mem0)[(gi & 7) * 128 + (gi >> 3)];
        if (m.x == ~0u) m.x = 0x7FFF7FFFu;
        if (m.y == ~0u) m.y = 0x7FFF7FFFu;
        if (m.z == ~0u) m.z = 0x7FFF7FFFu;
        if (m.w == ~0u) m.w = 0x7FFF7FFFu;
        g_xmem[0][gi] = m;
    } else if (gi < 4096) {
        (&g_xmem[0][0])[gi] = poison;
    } else if (gi < 4096 + 16384) {
        (&g_xo[0][0])[gi - 4096] = poison;
    } else if (gi < 4096 + 16384 + 48 * FSTR) {
        reinterpret_cast<uint4*>(&g_flag[0][0])[gi - 4096 - 16384] = poison;
    }
    float f[32];
#pragma unroll
    for (int j = 0; j < 4; j++) {
        f[j * 8 + 0] = bf_lo(v[j].x); f[j * 8 + 1] = bf_hi(v[j].x); f[j * 8 + 2] = bf_lo(v[j].y); f[j * 8 + 3] = bf_hi(v[j].y);
        f[j * 8 + 4] = bf_lo(v[j].z); f[j * 8 + 5] = bf_hi(v[j].z); f[j * 8 + 6] = bf_lo(v[j].w); f[j * 8 + 7] = bf_hi(v[j].w);
    }
    float s = 0.f;
#pragma unroll
    for (int i = 0; i < 32; i++) s += f[i];
#pragma unroll
    for (int o = 16; o; o >>= 1) s += __shfl_xor_sync(~0u, s, o);
    const float mean = s * (1.f / DM);
    float q = 0.f;
#pragma unroll
    for (int i = 0; i < 32; i++) { f[i] -= mean; q += f[i] * f[i]; }
#pragma unroll
    for (int o = 16; o; o >>= 1) q += __shfl_xor_sync(~0u, q, o);
    const float r = 1.f / sqrtf(q * (1.f / DM) + 1e-5f);
    uint4* dst = reinterpret_cast<uint4*>(g_xn + (size_t)row * DM);
    uint4* dst2 = g_xc + (row >> 5) * 4096 + (lane >> 3) * 256 + (row & 31) * 8 + ((lane & 7) ^ (row & 7));
#pragma unroll
    for (int j = 0; j < 4; j++) {
        const uint4 o = make_uint4(pack2(f[j * 8] * r, f[j * 8 + 1] * r), pack2(f[j * 8 + 2] * r, f[j * 8 + 3] * r),
                                   pack2(f[j * 8 + 4] * r, f[j * 8 + 5] * r), pack2(f[j * 8 + 6] * r, f[j * 8 + 7] * r));
        dst[j * 32 + lane] = o;
        dst2[(j & 1) * 2048 + (j >> 1) * 1024] = o;
    }
}

#define ONKQ 45
constexpr int ONKV = 128 - 2 * ONKQ;
constexpr uint32_t SB0 = 1024;
constexpr uint32_t C_WS = 0, C_XN = 65536, C_MB = 98304, C_WO = 114688, C_SMEM = 232448;
constexpr uint32_t C_BAR = C_SMEM - 384, C_CAL = C_BAR + 192;
constexpr uint32_t C_SLOTQ = C_WO + ONKQ * 2048, C_QM = C_SLOTQ + 4096, C_KM = C_QM + 1024, C_QX = C_SLOTQ + 8192, C_KX = C_QX + 4096,
                   C_XSL = C_KX + 4096, C_OL = C_XSL + 5120;
constexpr uint32_t C_SLOTV = C_WO + ONKV * 2048, C_V = C_SLOTV + 8192, C_PL = C_V + 20480, C_SL = C_PL + 4096;
static_assert(C_OL + 3072 <= C_BAR && C_SL + 2560 <= C_BAR, "smem overflow");
enum { B_W0 = 0, B_W1, B_W2, B_WS, B_WO, B_XF0, B_XF1, B_SC, B_P0, B_P1, B_XS, B_OL, B_MF0, B_MF1, B_OF, B_RT0, B_RT1, B_VF, B_MBF, B_NUM };
struct Descs { uint64_t sw[4], ns; };
constexpr uint64_t DSW = 0x4000004000010000ull, DNS = 0x0000001000080000ull;
template <int V> using ic = std::integral_constant<int, V>;
constexpr float SM_SCALE = 0.08838834764831845f * 1.4426950408889634f;

#define TSD(i) do {} while (0)
#define TS_FLUSH(w)
#define TSX(i, c)
#define TS(i)
#define NOFILL 0
#define DLY1 2200
#define DLY2 1400
#define OTAIL 2
#define DLYS 450
#define DLYB 150
#define VLEAD 3

#define VEARLY 8
#define QSPLIT 20
__device__ __forceinline__ bool elect() {
    uint32_t r;
    asm volatile("{\n.reg .pred p;\nelect.sync _|p, 0xffffffff;\nselp.u32 %0, 1, 0, p;\n}" : "=r"(r));
    return r;
}
__device__ __forceinline__ int uni(int v) { return __shfl_sync(~0u, v, 0); }
__device__ __forceinline__ void calibrate(uint32_t cal, float keep) {
    const uint32_t t0 = gtick();
    uint32_t t, it = 0;
    do { t = gtick(); spin_guard(it); } while (t == t0);
    const uint32_t c = clk();
    const uint4 p = lds4u(cal);
    const float cpt = fminf(fmaxf(__fdividef((float)(c - p.y), (float)((t - p.x) & 0x7FFFFFF)), 16.f), 128.f);
    __syncwarp();
    sts4u(cal, make_uint4(t, c, __float_as_uint(keep > 0.f ? fmaf(keep, __uint_as_float(p.z) - cpt, cpt) : cpt), 0));
}
struct Stamps { uint32_t v[6]; };
__device__ __forceinline__ void load_stamps2(Stamps& t, const uint32_t* f, uint32_t l16, bool on = true) {
    const char* p = reinterpret_cast<const char*>(f) + (l16 >> 2) * FSTR;
    asm volatile("{\n.reg .pred p;\nsetp.ne.u32 p, %7, 0;\nmov.u32 %0, 63;\nmov.u32 %1, 63;\nmov.u32 %2, 63;\nmov.u32 %3, 63;\nmov.u32 %4, 63;\nmov.u32 %5, 63;\n"
                 "@p ld.relaxed.gpu.global.v2.u32 {%0, %1}, [%6];\n@p ld.relaxed.gpu.global.v2.u32 {%2, %3}, [%6 + %8];\n"
                 "@p ld.relaxed.gpu.global.v2.u32 {%4, %5}, [%6 + %9];\n}"
                 : "=&r"(t.v[0]), "=&r"(t.v[1]), "=&r"(t.v[2]), "=&r"(t.v[3]), "=&r"(t.v[4]), "=&r"(t.v[5])
                 : "l"(p), "r"((uint32_t)on), "n"(128 * FSTR), "n"(256 * FSTR) : "memory");
}
__device__ __forceinline__ void load_stamps1(uint32_t* v, const uint32_t* f, uint32_t l16, bool on = true) {
    const char* p = reinterpret_cast<const char*>(f) + (l16 >> 2) * FSTR;
    asm volatile("{\n.reg .pred p;\nsetp.ne.u32 p, %4, 0;\nmov.u32 %0, 63;\nmov.u32 %1, 63;\nmov.u32 %2, 63;\n"
                 "@p ld.relaxed.gpu.global.u32 %0, [%3];\n@p ld.relaxed.gpu.global.u32 %1, [%3 + %5];\n@p ld.relaxed.gpu.global.u32 %2, [%3 + %6];\n}"
                 : "=&r"(v[0]), "=&r"(v[1]), "=&r"(v[2]) : "l"(p), "r"((uint32_t)on), "n"(128 * FSTR), "n"(256 * FSTR) : "memory");
}
template <int N>
__device__ __forceinline__ bool stamps_ready(const uint32_t* v, int s) {
    uint32_t x = 0;
#pragma unroll
    for (int i = 0; i < N; i++) x |= v[i] ^ s;
    return __all_sync(~0u, (x & 63) == 0);
}
template <int N>
__device__ __forceinline__ uint32_t latest_stamp(const uint32_t* v, const uint4 cal) {
    int late = (int)(v[0] - (cal.x << 6));
#pragma unroll
    for (int i = 1; i < N; i++) late = max(late, (int)(v[i] - (cal.x << 6)));
    return cal.y + (int)((float)(__reduce_max_sync(~0u, late) >> 6) * __uint_as_float(cal.z));
}
__device__ __forceinline__ void wait_clock(uint32_t target) {
    uint32_t it = 0;
    while ((int)(clk() - target) < 0 && ++it < 4096) {}
}

template <int BYTES>
__device__ __forceinline__ bool incomplete(uint32_t buf, uint32_t l16) {
    uint32_t m = 0;
#pragma unroll 1
    for (int o = 0; o < BYTES; o += 256) m = max(m, umax4(lds4u(buf + o + (l16 & 255))));
    return __any_sync(~0u, m == ~0u);
}
__device__ __forceinline__ void refetch(uint32_t buf, const uint4* src, uint32_t bytes, uint32_t b, int w4, int barid, uint32_t& tries) {
    spin_guard(tries);
    bar_sync(barid, 128);
    if (w4 == 0 && elect()) { mbar_expect(b, bytes); bulk_ld(buf, src, bytes, b); }
    __syncwarp();
    mbar_wait(b, 0);
    bar_sync(barid, 128);
    if (w4 == 0 && elect()) mbar_arrive(b);
    __syncwarp();
}

template <bool ISV, int WG>
__device__ __forceinline__ void chain_main(const CUtensorMap* tA, const CUtensorMap* tB, const CUtensorMap* tWo,
                                           const uint32_t sb, const int cl, const int rank, const Descs& D) {
    const int tid = threadIdx.x;
    uint32_t l16 = __shfl_sync(~0u, (tid & 31) * 16, tid & 31);
    const int w4 = uni((tid >> 5) & 3);
    const int role = ISV ? 2 : uni(rank & 1), hh = ISV ? rank - 4 : rank >> 1, head = 2 * cl + hh;
    const uint32_t bar = sb + C_BAR;
    constexpr int ONK = ISV ? ONKV : ONKQ;
    const int ostart = uni(hh * 128 + role * ONKQ);

    uint32_t wk[24][4], wv[24][4];
    uint32_t a_adr;
    {
        const int colA = head * 128 + (ISV ? 0 : role * 64), colB = head * 128 + (ISV ? 64 : role * 64);
        auto load_chunk = [&](uint32_t dst, int j, uint32_t b) {
            mbar_expect(b, 65536);
            tma2d(dst, tA, colA, j * 128, b);
            tma2d(dst + 16384, tB, colB, j * 128, b);
            tma2d(dst + 32768, tB, colB, 512 + j * 128, b);
            tma2d(dst + 49152, tA, colA, 512 + j * 128, b);
        };
        if (WG == 0 && tid == 0)
            for (int j = 0; j < 3; j++) load_chunk(sb + j * 65536, j, bar + (B_W0 + j) * 8);
        if (WG == 1 && w4 == 0) calibrate(sb + C_CAL, 0.f);
        const int lane = tid & 31, kr = (lane & 7) + ((lane >> 4) << 3);
        a_adr = __shfl_sync(~0u, sb + WG * 32768 + kr * 128 + (((w4 * 2 + ((lane >> 3) & 1)) ^ (kr & 7)) << 4), lane);
#pragma unroll
        for (int j = 0; j < 3; j++) {
            mbar_wait(bar + (B_W0 + j) * 8, 0);
#pragma unroll
            for (int i = 0; i < 8; i++) {
                ldsm4t(wk[j * 8 + i], a_adr + j * 65536 + i * 2048);
                ldsm4t(wv[j * 8 + i], a_adr + j * 65536 + 16384 + i * 2048);
            }
            if (j != 1) {
                bar_sync(6, 256);
                if (WG == 0 && j == 0 && tid == 0) load_chunk(sb + C_WS, 3, bar + B_WS * 8);
                if (WG == 0 && j == 2 && w4 == 0) {
                    if (lane == 0) mbar_expect(bar + B_WO * 8, ONK * 2048);
                    __syncwarp();
                    for (int i = lane; i < ONK; i += 32) tma2d(sb + C_WO + i * 2048, tWo, cl * 64, (ostart + i) * 16, bar + B_WO * 8);
                }
                __syncwarp();
            }
        }
        if (NOFILL) { for (uint32_t o = C_WO + ONK * 2048 + tid * 16; o < C_BAR; o += 4096) sts4u(sb + o, make_uint4(0, 0, 0, 0)); bar_sync(6, 256); }
        asm volatile("griddepcontrol.wait;" ::: "memory");
        asm volatile("griddepcontrol.launch_dependents;" ::: "memory");
        if (WG == 1 && w4 == 0) calibrate(sb + C_CAL, 0.f);
    }

    constexpr uint32_t SLOT = ISV ? C_SLOTV : C_SLOTQ;
    constexpr int WS_A = (SB0 + C_WS + WG * 32768) >> 4, WO_A = (SB0 + C_WO) >> 4, MB_A = (SB0 + C_MB) >> 4;
#define XN_A(ks) (int)(((SB0 + C_XN + WG * 16384) >> 4) + ((ks) >> 2) * 256 + ((ks) & 3) * 2)
    const uint32_t slot = uni(sb + SLOT + w4 * 512), mbw = sb + C_MB + WG * 8192;
    const uint32_t sb_v = uni(mapa(sb, 4 + hh));
    const uint32_t sb_x = uni(mapa(sb, 2 * hh + WG));
    const uint32_t sb_o = uni(mapa(sb, w4));
    const uint32_t u_off = uni(ISV ? (head * 128 + w4 * 32) * 16 : (cl * 4 + rank) * 256 + (w4 & 1) * 128);
    const uint32_t v_row = uni(sb + C_V + (32 * (2 * WG + (w4 >> 1)) + 4 * (w4 & 1)) * 80);
    const uint32_t u_flag = uni(blockIdx.x * FSTR);
    int s = -1;
    uint32_t pf[4][4];
    float xk[16], xv[16];

    auto load_tokens = [&](int seg, int wina, int g) {
        const int khalf = ISV ? 1 - wina : wina;
        if (!NOFILL && elect()) {
            mbar_expect(bar + (B_XF0 + g) * 8, 16384);
            bulk_ld(sb + C_XN + g * 16384, g_xc + (seg * 4 + khalf * 2 + g) * 1024, 16384, bar + (B_XF0 + g) * 8);
        }
        __syncwarp();
    };
    auto prefetch = [&]() {
#pragma unroll
        for (int i = 0; i < 4; i++) ldsm4t(pf[i], a_adr + C_WS + (i & 1) * 16384 + (i >> 1) * 2048);
    };
    constexpr int HA = ISV ? 0 : 1;
    auto products = [&](auto give, auto half, auto init, auto i0, auto i1, const uint64_t d) {
        static_for<i0.value, i1.value>([&](auto i) {
            constexpr int ks = half.value * 16 + i.value, acc = !(init.value && i.value == 0);
            if constexpr (ks >= 24) wg32_ss<WS_A + give.value * 1024 + (ks - 24) * 128, XN_A(i.value)>(give.value ? xv : xk, d);
            else if constexpr (give.value) wg32_rs<acc, XN_A(i.value)>(xv, wv[ks], d);
            else wg32_rs<acc, XN_A(i.value)>(xk, wk[ks], d);
        });
    };
    auto stream_a = [&](const uint64_t dk, const uint64_t dv) {
        if (NOFILL) return;
        wg_fence();
        products(ic<0>{}, ic<HA>{}, ic<1>{}, ic<0>{}, ic<16>{}, dk);
        products(ic<1>{}, ic<HA>{}, ic<1>{}, ic<0>{}, ic<16>{}, dv);
        wg_commit();
    };
    auto token_softmax = [&]() {
        const int hi = w4 - 2, lane = l16 >> 4;
        const uint32_t src = sb + C_XSL + l16 + hi * 8;
        const int d0 = 16 * role + 8 * hi + (lane >> 2) - 2 * (lane & 3);
        mbar_wait(bar + B_XS * 8, s & 1);
        float e[10];
        float m = -INFINITY;
#pragma unroll
        for (int i = 0; i < 5; i++) {
            __syncwarp();
            const float2 a = lds2f(src + i * 512), b = lds2f(src + 2560 + i * 512);
            e[2 * i] = (i == 0 || d0 >= 8 * (i - 1)) ? a.x + b.x : -INFINITY;
            e[2 * i + 1] = (i == 0 || d0 > 8 * (i - 1)) ? a.y + b.y : -INFINITY;
            m = fmaxf(m, fmaxf(e[2 * i], e[2 * i + 1]));
        }
        m = fmaxf(m, __shfl_xor_sync(~0u, m, 1));
        m = fmaxf(m, __shfl_xor_sync(~0u, m, 2));
        m *= -SM_SCALE;
        float l = 0.f;
#pragma unroll
        for (int i = 0; i < 10; i++) { e[i] = ex2(fmaf(e[i], SM_SCALE, m)); l += e[i]; }
        l += __shfl_xor_sync(~0u, l, 1);
        l += __shfl_xor_sync(~0u, l, 2);
        l = rcp(l);
        const uint32_t pd = sb_v + C_PL + (s & 1) * 2048 + role * 768 + hi * 128 + (l16 >> 2), pb = sb_v + C_BAR + (B_P0 + (s & 1)) * 8;
        st_async1(pd, pb, pack2(e[0] * l, e[1] * l));
        st_async1(pd + 256, pb, pack2(e[2] * l, e[3] * l));
        st_async1(pd + 512, pb, pack2(e[4] * l, e[5] * l));
        if (role) {
            st_async1(pd + 768, pb, pack2(e[6] * l, e[7] * l));
            st_async1(pd + 1024, pb, pack2(e[8] * l, e[9] * l));
        }
        if (hi == 0 && l16 == 0) mbar_expect(bar + B_XS * 8, 3072 + role * 2048);
        __syncwarp();
    };

    auto windows = [&](auto first_) {
        constexpr bool FIRST = first_.value;
        const uint64_t dd[4] = {FIRST ? DSW : D.sw[0], FIRST ? DSW : D.sw[1], FIRST ? DSW : D.sw[2], FIRST ? DSW : D.sw[3]};
        TS(5);
        if constexpr (WG == 1) {
            TS(6);
            Stamps st;
            if (ISV && !FIRST) bar_sync(3, 256);
            if (!ISV && !FIRST) load_stamps2(st, g_flag[0], l16, w4 < 2);
            stream_a(dd[0], dd[1]);
            if (!NOFILL) {
                bar_arrive(7, 256);
                wg_wait<0>();
                reg_fence<16>(xk); reg_fence<16>(xv);
                if (w4 == 3) { bar_sync(2, 128); load_tokens(s + 1, 0, 1); }
                else bar_arrive(2, 128);
            }
            TS(7);
            if (!FIRST && !ISV && w4 < 2) {
                const uint4 cal = lds4u(sb + C_CAL);
                uint32_t it = 0;
                while (!stamps_ready<6>(st.v, s)) { TSD(0); load_stamps2(st, g_flag[0], l16); spin_guard(it); }
                TSD(5);
                const uint32_t target = latest_stamp<6>(st.v, cal) + DLY1;
                if (w4) mbar_wait(bar + B_VF * 8, s & 1);
                TS(10);
                const uint32_t dsb = w4 ? sb_v : sb, bytes = w4 ? ONKV * 128 : ONKQ * 256, off = w4 ? role * (ONKV * 128) : 0;
                const char* src = reinterpret_cast<const char*>(&g_xo[s & 3][(w4 ? ostart + (2 - role) * ONKQ : ostart) * 16]) + off;
                wait_clock(target);
                if (elect()) bulk_ld(dsb + C_MB + off, src, bytes, dsb + C_BAR + B_OF * 8);
                __syncwarp();
                TS(8);
            }
        } else {
            if (!NOFILL) {
                mbar_wait(bar + B_XF0 * 8, 0);
                bar_sync(7, 256);
            }
            TS(6);
            stream_a(dd[0], dd[1]);
        }
        Stamps st;
        if constexpr (WG == 0) {
            if constexpr (!FIRST) {
                const uint32_t dst = sb_o + C_OL + rank * 512 + ((l16 & 64) << 2) + ((l16 >> 1) & 192) + (l16 & 48);
                const uint32_t can = sb + C_MB + l16 * 8 + (l16 >> 2), can2 = can + (l16 < (ONK * 2 - 64) * 16 ? 8192 : 0);
                float co[4];
                uint32_t tries = 0;
                TS(7);
                mbar_wait(bar + B_OF * 8, s & 1);
                TS(8);
                auto early = [&]() { return __any_sync(~0u, max(max(lds1u(can), lds1u(can + 4096)), lds1u(can2)) == ~0u); };
                wg8_chain<0, 10, WO_A, MB_A>(co, D.sw[0], D.ns);
                if (__builtin_expect(early(), 0)) {
                    wg_wait<0>();
                    do refetch(sb + C_MB, &g_xo[s & 3][ostart * 16], ONK * 256, bar + B_RT0 * 8, w4, 1, tries); while (early());
                    wg8_chain<0, 10, WO_A, MB_A>(co, DSW, DNS);
                }
                wg_wait<1>();
                bar_arrive(4, 192);
                wg8_chain<10, ONK - OTAIL, WO_A, MB_A>(co, D.sw[0], D.ns);
                static_for<ONK - OTAIL, ONK>([&](auto i) { wg8_ss<1, WO_A + i.value * 128, MB_A + i.value * 16>(co, D.sw[0], D.ns); });
                wg_commit();
                wg_wait<1>();
                bar_arrive(5, 256);
                wg_wait<0>();
                reg_fence<4>(co);
                if (__builtin_expect(st_async4_unless_nan(dst, sb_o + C_BAR + B_OL * 8, co), 0)) {
                    while (incomplete<ONK * 256>(sb + C_MB, l16)) {
                        refetch(sb + C_MB, &g_xo[s & 3][ostart * 16], ONK * 256, bar + B_RT0 * 8, w4, 1, tries);
                        co[0] = co[1] = co[2] = co[3] = 0.f;
#pragma unroll 1
                        for (int i = 0; i < ONK; i++) {
                            wg_fence();
                            wg8_ss<1, WO_A, MB_A>(co, DSW + i * 128, DNS + i * 16);
                            wg_commit();
                            wg_wait<0>();
                        }
                        reg_fence<4>(co);
                    }
                    st_async4(dst, sb_o + C_BAR + B_OL * 8, __float_as_uint(co[0]), __float_as_uint(co[1]), __float_as_uint(co[2]), __float_as_uint(co[3]));
                }
                if (l16 < 32) mbar_arrive_cluster(mapa(bar + B_MBF * 8, 2 * hh + (l16 >> 4)));
                TS(9);
                if (l16 < 48 && w4 == 3) mbar_expect(bar + B_MF0 * 8 + (l16 >> 1), l16 == 32 ? ONK * 256 : 8192);
                if (!ISV && w4 < 2) {
                    const uint32_t off = u_off + (l16 >> 2);
                    const uint32_t src = sb + C_OL + w4 * 8 + ((l16 & 48) << 2) + ((l16 >> 3) & 48) + ((l16 >> 4) & 4);
                    char* gd = reinterpret_cast<char*>(&g_xmem[(s + 1) & 3][0]) + off;
                    mbar_wait(bar + B_OL * 8, s & 1);
                    float a[6], b[6];
#pragma unroll
                    for (int i = 0; i < 6; i++) { a[i] = __uint_as_float(lds1u(src + i * 512)); b[i] = __uint_as_float(lds1u(src + i * 512 + 256)); }
                    st_relaxed1(gd, pack2((a[0] + a[1]) + (a[2] + a[3]) + (a[4] + a[5]), (b[0] + b[1]) + (b[2] + b[3]) + (b[4] + b[5])));
                    TS(10);
                    st_relaxed1(reinterpret_cast<char*>(&g_xmem[(s + 3) & 3][0]) + off, ~0u);
                    if (w4 == 0 && l16 == 0) mbar_expect(bar + B_OL * 8, 3072);
                }
                __syncwarp();
            } else {
                wg_wait<0>();
                bar_arrive(4, 192);
                bar_arrive(5, 256);
                if (l16 < 32) mbar_arrive_cluster(mapa(bar + B_MBF * 8, 2 * hh + (l16 >> 4)));
                mbar_wait(bar + B_WO * 8, 0);
            }
            if (!NOFILL) { reg_fence<16>(xk); reg_fence<16>(xv); }
        } else {
            if (w4 < 2) {
                bar_sync(4, 192);
                const uint32_t dep = lds2u(sb + C_CAL + 8).y;
                const uint32_t v = ((gtick_dep(dep) - (ISV ? (ONKQ - ONKV) * 18 / 64 : 0)) << 6) | s, c = clk();
                if (w4 == 0) {
                    if (!FIRST) {
                        if (l16 == 0) st_relaxed1(&g_flag[1][u_flag + dep], v);
                        if (!ISV) { calibrate(sb + C_CAL, 0.75f); wait_clock(c + DLYS); }
                    }
                } else {
                    if (!FIRST) wait_clock(c + DLYB);
                    load_tokens(s + 1, 0, 0);
                }
            } else if (!ISV && !FIRST && !NOFILL) {
                token_softmax();
                TSX(9, w4 == 2);
            }
            if (!NOFILL) mbar_wait(bar + B_XF1 * 8, 1);
            if (!FIRST && !ISV) load_stamps1(st.v, g_flag[1], l16, w4 == 0);
            bar_sync(5, 256);
        }
        TS(11);
        auto store_tokens = [&](const float4* r) {
            uint32_t lo[4], hi[4];
#pragma unroll
            for (int j = 0; j < 4; j++) {
                lo[j] = pack2(xk[4 * j] + r[j].x, xk[4 * j + 1] + r[j].y);
                hi[j] = pack2(xk[4 * j + 2] + r[j].z, xk[4 * j + 3] + r[j].w);
            }
            if (!ISV) {
                const uint32_t d = sb + C_QX + WG * 4096 + w4 * 1024 + l16;
                stsm4t(d, lo[0], lo[1], lo[2], lo[3]);
                stsm4t(d + 512, hi[0], hi[1], hi[2], hi[3]);
            } else {
                const uint32_t d = v_row + ((s + 1) & 1) * 10240 + (l16 & 96) * 20 + (l16 & 16) * 5 + ((l16 >> 3) & 48);
                stsm4(d, lo[0], lo[1], lo[2], lo[3]);
                stsm4(d + 160, hi[0], hi[1], hi[2], hi[3]);
            }
        };
        if constexpr (WG == 1) {
            if (!NOFILL) {
                wg_fence();
                products(ic<1>{}, ic<1 - HA>{}, ic<0>{}, ic<0>{}, ic<16>{}, dd[3]);
                wg_commit();
                __syncwarp();
                if (!FIRST && !ISV) load_stamps1(st.v + 3, g_flag[1], l16, w4 == 0);
                __syncwarp();
                products(ic<0>{}, ic<1 - HA>{}, ic<0>{}, ic<0>{}, ic<16>{}, dd[2]);
                wg_commit();
                bar_arrive(7, 256);
                wg_wait<1>();
                reg_fence<16>(xv);
#pragma unroll
                for (int j = 0; j < 4; j++) sts4f(slot + l16 + j * 2048, xv[4 * j], xv[4 * j + 1], xv[4 * j + 2], xv[4 * j + 3]);
                bar_arrive(8, 256);
            }
            if (!NOFILL) {
                wg_wait<0>();
                reg_fence<16>(xk);
                if (w4 == 3) { bar_sync(2, 128); if (s < NSEG - 2) load_tokens(s + 2, 1, 1); }
                else bar_arrive(2, 128);
            }
            TS(13);
            if (!ISV && w4 == 0) {
                const uint4* src = &g_xmem[(s + 1) & 3][role * 512];
                mbar_wait(bar + B_MBF * 8, (s + 1) & 1);
                TSD(6);
                if (!FIRST) {
                    const uint4 cal = lds4u(sb + C_CAL);
                    if (!stamps_ready<3>(st.v, s)) {
                        uint32_t it = 0;
                        TSD(9);
                        if (!NOFILL) { st.v[0] = st.v[3]; st.v[1] = st.v[4]; st.v[2] = st.v[5]; }
                        while (!stamps_ready<3>(st.v, s)) { TSD(12); load_stamps1(st.v, g_flag[1], l16); spin_guard(it); }
                    }
                    TSD(2);
                    const uint32_t target = latest_stamp<3>(st.v, cal) + DLY2;
                    TS(3);
                    wait_clock(target);
                }
                if (elect()) bulk_mc(sb + C_MB + role * 8192, src, 8192, bar + (B_MF0 + role) * 8, (uint16_t)((3 << (2 * hh)) | (16 << hh)));
                __syncwarp();
                TS(4);
            }
            prefetch();
            if (!NOFILL) {
                bar_sync(9, 256);
                float4 r[4];
#pragma unroll
                for (int j = 0; j < 4; j++) r[j] = lds4f(slot + l16 + j * 2048);
                store_tokens(r);
                bar_arrive(10, 256);
            }
        } else {
            if (!NOFILL) {
                mbar_wait(bar + B_XF0 * 8, 1);
                bar_sync(7, 256);
                TS(12);
                wg_fence();
                products(ic<1>{}, ic<1 - HA>{}, ic<0>{}, ic<0>{}, ic<16>{}, dd[3]);
                wg_commit();
                products(ic<0>{}, ic<1 - HA>{}, ic<0>{}, ic<0>{}, ic<6>{}, dd[2]);
                wg_commit();
                bar_sync(8, 256);
                float4 r[4];
#pragma unroll
                for (int j = 0; j < 4; j++) r[j] = lds4f(slot + l16 + j * 2048);
                wg_wait<1>();
                reg_fence<16>(xv);
#pragma unroll
                for (int j = 0; j < 4; j++) sts4f(slot + l16 + j * 2048, xv[4 * j], xv[4 * j + 1], xv[4 * j + 2], xv[4 * j + 3]);
                bar_arrive(9, 256);
                products(ic<0>{}, ic<1 - HA>{}, ic<0>{}, ic<6>{}, ic<16>{}, dd[2]);
                wg_commit();
                wg_wait<0>();
                reg_fence<16>(xk);
                TS(13);
                prefetch();
                store_tokens(r);
                bar_sync(10, 256);
            } else {
                prefetch();
            }
        }
    };

    if (w4 == 0) load_tokens(0, 1, WG);
    mbar_wait(bar + B_WS * 8, 0);
    if (WG == 1 && !NOFILL) mbar_wait(bar + B_XF1 * 8, 0);
    windows(ic<1>{});

#pragma unroll 1
    while (true) {
        s = uni(s + 1);
        asm volatile("" : "+r"(l16), "+r"(a_adr));
        TS_FLUSH(WG);
        TS(0);
        float ck[4], cv[4];
        uint32_t k0[2][4], k1[2][4];
        const uint32_t kl = sb + C_KX + ((l16 & 384) << 2) + (l16 & 112);
        {
            const uint32_t can = mbw + l16 * 8 + (l16 >> 2);
            uint32_t tries = 0;
            for (;; tries |= 1) {
                asm volatile("" : "+r"(tries));
                if (__builtin_expect(tries, 0)) {
                    if (__any_sync(~0u, max(lds1u(can), lds1u(can + 4096)) == ~0u) || incomplete<8192>(mbw, l16))
                        refetch(mbw, &g_xmem[s & 3][WG * 512], 8192, bar + (B_RT0 + WG) * 8, w4, 1 + WG, tries);
                    else tries = ~0u;
                    prefetch();
                }
                mbar_wait(bar + (B_MF0 + WG) * 8, s & 1);
                TS(1);
                uint32_t b[2][4];
                float dk[4], dv[4];
                ldsm4(b[0], mbw + l16 + 12 * 512);
#pragma unroll
                for (int i = 0; i < 4; i++) ck[i] = cv[i] = dk[i] = dv[i] = 0.f;
                auto kpair = [&](auto kp_) {
                    constexpr int kp = kp_.value, grp = kp / 5, ph = kp % 5, nx = kp + 1;
                    if constexpr (nx < 16) ldsm4(b[nx & 1], mbw + l16 + ((nx % 5) ? (nx / 5) * 4 + (nx % 5) - 1 : 12 + nx / 5) * 512);
                    const uint32_t* bb = b[kp & 1];
                    if constexpr (ph != 0) {
                        constexpr int q = (grp * 4 + ph - 1) * 2, i = ph - 1;
                        ldsm4t(pf[i], a_adr + C_WS + (i & 1) * 16384 + (grp * 2 + 2 + (i >> 1)) * 2048);
                        __syncwarp();
                        mma16(cv, wv[q][0], wv[q][1], wv[q][2], wv[q][3], bb[0], bb[1]);
                        mma16(ck, wk[q][0], wk[q][1], wk[q][2], wk[q][3], bb[0], bb[1]);
                        mma16(dv, wv[q + 1][0], wv[q + 1][1], wv[q + 1][2], wv[q + 1][3], bb[2], bb[3]);
                        mma16(dk, wk[q + 1][0], wk[q + 1][1], wk[q + 1][2], wk[q + 1][3], bb[2], bb[3]);
                    } else {
                        mma16(cv, pf[1][0], pf[1][1], pf[1][2], pf[1][3], bb[0], bb[1]);
                        mma16(dv, pf[3][0], pf[3][1], pf[3][2], pf[3][3], bb[2], bb[3]);
                        mma16(ck, pf[0][0], pf[0][1], pf[0][2], pf[0][3], bb[0], bb[1]);
                        mma16(dk, pf[2][0], pf[2][1], pf[2][2], pf[2][3], bb[2], bb[3]);
                    }
                };
                kpair(ic<0>{});
                const uint32_t c0 = lds1u(can), c1 = lds1u(can + 4096);
                kpair(ic<1>{});
                if (__builtin_expect(__any_sync(~0u, max(c0, c1) == ~0u), 0)) continue;
                st_pred1(&g_flag[0][u_flag + WG + l16], ((gtick() - (ISV ? VLEAD : 0)) << 6) | s, w4 * 512 + l16 == 1536);
                static_for<2, 16>(kpair);
#pragma unroll
                for (int i = 0; i < 4; i++) cv[i] += dv[i];
                sts4f(slot + WG * 2048 + l16, cv[0], cv[1], cv[2], cv[3]);
#pragma unroll
                for (int i = 0; i < 4; i++) ck[i] += dk[i];
                TS(2);
                if (__builtin_expect(!any_nan_unless(cv[0], cv[1], tries), 1)) break;
            }
            if (!ISV && WG == 0) {
                const uint32_t ka = kl + (w4 == 1 ? 256 : 0);
                ldsm4(k0[0], ka); ldsm4(k0[1], ka + 2048);
                ldsm4(k1[0], ka + 128); ldsm4(k1[1], ka + 128 + 2048);
            }
            bar_sync(6, 256);
        }
        if constexpr (!ISV) {
            const uint32_t lane_b = sb + C_QM + ((l16 >> 1) & 128) + ((l16 & 128) << 2) + (l16 & 112);
            const uint32_t qx = sb + C_QX + WG * 256 + l16 + (l16 & 256);
            const uint32_t xd = sb_x + C_XSL + role * 2560 + l16, xb = sb_x + C_BAR + B_XS * 8;
            {
                const float4 r = lds4f(slot + (WG ^ 1) * 2048 + l16);
                stsm2t(sb + C_QM + WG * 1024 + w4 * 256 + (l16 & 255), pack2(ck[0] + r.x, ck[1] + r.y), pack2(ck[2] + r.z, ck[3] + r.w));
            }
            auto tile = [&](float* d, const uint32_t (*q)[4], const uint32_t (*k)[4]) {
                d[0] = d[1] = d[2] = d[3] = 0.f;
#pragma unroll
                for (int i = 0; i < 4; i++) mma16(d, q[i][0], q[i][1], q[i][2], q[i][3], k[i >> 1][(i & 1) * 2], k[i >> 1][(i & 1) * 2 + 1]);
            };
            auto send = [&](int ti, const float* d) {
                st_async4(xd + ti * 512, xb, __float_as_uint(d[0]), __float_as_uint(d[1]), __float_as_uint(d[2]), __float_as_uint(d[3]));
            };
            if constexpr (WG == 0) {
                if (w4 < 2) {
                    uint32_t q0[4], q1[4];
                    const uint32_t dst = sb_v + C_SL + role * 1280 + w4 * 512 + l16;
                    bar_sync(6, 256);
                    TS(3);
                    ldsm4(q0, lane_b); ldsm4(q1, lane_b + 256);
                    float s0[4] = {0.f, 0.f, 0.f, 0.f}, s1[4] = {0.f, 0.f, 0.f, 0.f}, s2[4] = {0.f, 0.f, 0.f, 0.f}, s3[4] = {0.f, 0.f, 0.f, 0.f};
                    mma16(s0, q0[0], q0[1], q0[2], q0[3], k0[0][0], k0[0][1]);
                    mma16(s1, q0[0], q0[1], q0[2], q0[3], k0[1][0], k0[1][1]);
                    mma16(s2, q0[0], q0[1], q0[2], q0[3], k1[0][0], k1[0][1]);
                    mma16(s3, q0[0], q0[1], q0[2], q0[3], k1[1][0], k1[1][1]);
                    mma16(s0, q1[0], q1[1], q1[2], q1[3], k0[0][2], k0[0][3]);
                    mma16(s1, q1[0], q1[1], q1[2], q1[3], k0[1][2], k0[1][3]);
                    mma16(s2, q1[0], q1[1], q1[2], q1[3], k1[0][2], k1[0][3]);
                    mma16(s3, q1[0], q1[1], q1[2], q1[3], k1[1][2], k1[1][3]);
                    st_async4(dst, sb_v + C_BAR + B_SC * 8, __float_as_uint(s0[0] + s1[2]), __float_as_uint(s0[1] + s1[3]),
                              __float_as_uint(s2[0] + s3[2]), __float_as_uint(s2[1] + s3[3]));
                    bar_arrive(12, 256);
                    TS(4);
                } else if (w4 == 2) {
                    uint32_t q0[4], q1[4], m0[4], m1[4];
                    const uint32_t dst = sb_v + C_SL + role * 1280 + 1024 + (l16 >> 1);
                    bar_sync(6, 256);
                    ldsm4(q0, lane_b); ldsm4(m0, sb + C_KM + l16); ldsm4(m1, sb + C_KM + 512 + l16); ldsm4(q1, lane_b + 256);
                    float s0[4] = {0.f, 0.f, 0.f, 0.f}, s1[4] = {0.f, 0.f, 0.f, 0.f};
                    mma16(s0, q0[0], q0[1], q0[2], q0[3], m0[0], m0[1]);
                    mma16(s1, q0[0], q0[1], q0[2], q0[3], m1[0], m1[1]);
                    mma16(s0, q1[0], q1[1], q1[2], q1[3], m0[2], m0[3]);
                    mma16(s1, q1[0], q1[1], q1[2], q1[3], m1[2], m1[3]);
                    st_async2(dst, sb_v + C_BAR + B_SC * 8, __float_as_uint(s0[0] + s1[2]), __float_as_uint(s0[1] + s1[3]));
                    bar_arrive(12, 256);
                    if (s < NSEG - 1) load_tokens(s + 1, 1, 0);
                } else {
                    bar_sync(6, 256);
                    if (!NOFILL) mbar_wait(bar + B_XF1 * 8, s == NSEG - 1);
                    if (!NOFILL) {
                        uint32_t q[4][4], km[2][4];
                        float d0[4], d1[4], d2[4];
#pragma unroll
                        for (int i = 0; i < 4; i++) ldsm4(q[i], qx + i * 1024);
                        ldsm4(km[0], sb + C_KM + l16); ldsm4(km[1], sb + C_KM + 512 + l16);
                        tile(d1, q, k0); tile(d2, q, k1); tile(d0, q, km);
                        reg_fence<4>(d0);
                        bar_sync(12, 256);
                        send(0, d0); send(1, d1); send(2, d2);
                    } else {
                        bar_sync(12, 256);
                    }
                }
                if (__builtin_expect(s == NSEG - 1, 0)) break;
            } else {
                bar_sync(6, 256);
                if (!NOFILL) {
                    mbar_wait(bar + B_XF1 * 8, s == NSEG - 1);
                    uint32_t q[4][4];
                    float d0[4], d1[4];
#pragma unroll
                    for (int i = 0; i < 4; i++) ldsm4(q[i], qx + i * 1024);
                    ldsm4(k0[0], kl + w4 * 128); ldsm4(k0[1], kl + w4 * 128 + 2048);
                    ldsm4(k1[0], sb + C_KM + l16); ldsm4(k1[1], sb + C_KM + 512 + l16);
                    tile(d1, q, k0); tile(d0, q, k1);
                    bar_sync(12, 256);
                    send(1 + w4, d1);
                    if (w4 == 0) send(0, d0);
                } else {
                    bar_sync(12, 256);
                }
                if (__builtin_expect(s == NSEG - 1, 0)) { if (w4 >= 2 && !NOFILL) token_softmax(); break; }
            }
        } else {
            const uint32_t lane_b = sb + C_V + w4 * 2560 + (l16 & 112) * 5 + ((l16 >> 3) & 48);
            auto load_values = [&](uint32_t (*vx)[4], uint32_t* vm, int ss) {
#pragma unroll
                for (int j = 0; j < 4; j++) ldsm4(vx[j], lane_b + (ss & 1) * 10240 + j * 640);
                ldsm4(vm, sb + C_V + (ss & 1) * 10240 + w4 * 2560 + 64 + l16 * 5);
            };
            auto token_output = [&](int ss, bool live, auto mid) {
                uint32_t vx[4][4], vm[4];
                const uint32_t pl = sb + C_PL + (ss & 1) * 2048 + (l16 >> 2);
                auto lds_frag = [&](uint32_t a) { return make_uint4(lds1u(a), lds1u(a + 128), lds1u(a + 256), lds1u(a + 384)); };
                load_values(vx, vm, ss);
                mid();
                char* orow = reinterpret_cast<char*>(g_ox) + (ss * (32 * HD * 2) + (u_off >> 3) + (l16 >> 6) * (HD * 2) + (l16 & 48));
#pragma unroll
                for (int mh = 1; mh >= 0; mh--) {
                    __syncwarp();
                    const uint2 pm = make_uint2(lds1u(pl + mh * 768), lds1u(pl + mh * 768 + 128));
                    const uint4 p0 = lds_frag(pl + mh * 768 + 256);
                    float o[4][4];
#pragma unroll
                    for (int j = 0; j < 4; j++) { o[j][0] = o[j][1] = o[j][2] = o[j][3] = 0.f; mma8(o[j], pm.x, pm.y, vm[j]); }
#pragma unroll
                    for (int j = 0; j < 4; j++) mma16(o[j], p0.x, p0.y, p0.z, p0.w, vx[j][0], vx[j][1]);
                    if (mh) {
                        const uint4 p1 = lds_frag(pl + 1536);
#pragma unroll
                        for (int j = 0; j < 4; j++) mma16(o[j], p1.x, p1.y, p1.z, p1.w, vx[j][2], vx[j][3]);
                    }
                    st_pred4(orow + mh * (16 * HD * 2),
                             make_uint4(pack2(o[0][0], o[0][1]), pack2(o[1][0], o[1][1]), pack2(o[2][0], o[2][1]), pack2(o[3][0], o[3][1])), live);
                    st_pred4(orow + mh * (16 * HD * 2) + 8 * HD * 2,
                             make_uint4(pack2(o[0][2], o[0][3]), pack2(o[1][2], o[1][3]), pack2(o[2][2], o[2][3]), pack2(o[3][2], o[3][3])), live);
                }
            };
            const uint32_t vd = v_row + (s & 1) * 10240 + 64 + (l16 & 96) * 20 + ((l16 & 16) + ((l16 & 128) >> 2)) * 5;
            const float4 r = lds4f(slot + (WG ^ 1) * 2048 + l16);
            __syncwarp();
            auto finish = [&]() {
                stsm2(vd, pack2(ck[0] + r.x, ck[1] + r.y), pack2(ck[2] + r.z, ck[3] + r.w));
                if (WG == 1) {
                    bar_arrive(11, 256);
                    if (w4 == 3 && l16 < 32) mbar_arrive_cluster(mapa(bar + B_VF * 8, 2 * hh + (l16 >> 4)));
                }
                TSX(3, WG == 0 && w4 == 0);
            };
            if (!NOFILL && WG == 1) {
                token_output(s - 1, s > 0, [&]() { finish(); mbar_wait(bar + (B_P0 + ((s - 1) & 1)) * 8, ((s - 1) >> 1) & 1); });
                if (w4 == 1 && l16 == 0 && s > 0) mbar_expect(bar + (B_P0 + ((s - 1) & 1)) * 8, 2048);
                mbar_wait(bar + B_XF1 * 8, s == NSEG - 1);
            } else {
                finish();
            }
            if (WG == 0) bar_sync(11, 256);
            if (__builtin_expect(s == NSEG - 1, 0)) {
                bar_sync(6, 256);
                if (!NOFILL && WG == 1) token_output(s, true, [&]() { mbar_wait(bar + (B_P0 + (s & 1)) * 8, (s >> 1) & 1); });
                mbar_wait(bar + B_SC * 8, s & 1);
                break;
            }
            if constexpr (WG == 0) {
                uint32_t vx[4][4], vm[4];
                load_values(vx, vm, s);
                const uint32_t oo = u_off + ((l16 & 48) << 3) + ((l16 >> 2) & 112);
                char* dst = reinterpret_cast<char*>(&g_xo[s & 3][0]) + oo;
                if (w4 == 3) load_tokens(s + 1, 1, 0);
                mbar_wait(bar + B_SC * 8, s & 1);
                TS(4);
                const float4 a0 = lds4f(sb + C_SL + l16), b0 = lds4f(sb + C_SL + 1280 + l16);
                const float4 a1 = lds4f(sb + C_SL + 512 + l16), b1 = lds4f(sb + C_SL + 1280 + 512 + l16);
                const float2 a2 = lds2f(sb + C_SL + 1024 + (l16 >> 1)), b2 = lds2f(sb + C_SL + 1280 + 1024 + (l16 >> 1));
                const float e[10] = {a0.x + b0.x, a0.y + b0.y, a0.z + b0.z, a0.w + b0.w, a1.x + b1.x, a1.y + b1.y, a1.z + b1.z, a1.w + b1.w,
                                     a2.x + b2.x, a2.y + b2.y};
                float m = fmaxf(fmaxf(fmaxf(e[0], e[1]), fmaxf(e[2], e[3])), fmaxf(fmaxf(e[4], e[5]), fmaxf(e[6], e[7])));
                m = fmaxf(m, fmaxf(e[8], e[9]));
                m = fmaxf(fmaxf(m, __shfl_xor_sync(~0u, m, 1)), fmaxf(__shfl_xor_sync(~0u, m, 2), __shfl_xor_sync(~0u, m, 3)));
                m *= -SM_SCALE;
                float x[10];
#pragma unroll
                for (int i = 0; i < 10; i++) x[i] = ex2(fmaf(e[i], SM_SCALE, m));
                float o[4][4];
                const uint32_t p0 = pack2(x[0], x[1]), p1 = pack2(x[2], x[3]), j0 = __float_as_uint(x[1]), j1 = __float_as_uint(x[3]);
#pragma unroll
                for (int j = 0; j < 4; j++) { o[j][0] = o[j][1] = o[j][2] = o[j][3] = 0.f; mma16(o[j], p0, j0, p1, j1, vx[j][0], vx[j][1]); }
                const uint32_t p2 = pack2(x[4], x[5]), p3 = pack2(x[6], x[7]), j2 = __float_as_uint(x[5]), j3 = __float_as_uint(x[7]);
#pragma unroll
                for (int j = 0; j < 4; j++) mma16(o[j], p2, j2, p3, j3, vx[j][2], vx[j][3]);
                const uint32_t p4 = pack2(x[8], x[9]), j4 = __float_as_uint(x[9]);
                float l = (((x[0] + x[1]) + (x[2] + x[3])) + ((x[4] + x[5]) + (x[6] + x[7]))) + (x[8] + x[9]);
                l = (l + __shfl_xor_sync(~0u, l, 1)) + (__shfl_xor_sync(~0u, l, 2) + __shfl_xor_sync(~0u, l, 3));
#pragma unroll
                for (int j = 0; j < 4; j++) mma8(o[j], p4, j4, vm[j]);
                l = rcp(l);
                st_relaxed4(reinterpret_cast<uint4*>(dst), make_uint4(pack2(o[0][0] * l, o[0][1] * l), pack2(o[1][0] * l, o[1][1] * l),
                                                                      pack2(o[2][0] * l, o[2][1] * l), pack2(o[3][0] * l, o[3][1] * l)));
                bar_arrive(3, 256);
                st_relaxed4(reinterpret_cast<uint4*>(reinterpret_cast<char*>(&g_xo[(s + 2) & 3][0]) + oo), make_uint4(~0u, ~0u, ~0u, ~0u));
                if (w4 == 0 && l16 == 0) mbar_expect(bar + B_SC * 8, 2560);
            }
        }
        windows(ic<0>{});
    }
}

__global__ void __cluster_dims__(6, 1, 1) __launch_bounds__(256, 1)
chain_kernel(const __grid_constant__ CUtensorMap tq, const __grid_constant__ CUtensorMap tk, const __grid_constant__ CUtensorMap tv,
             const __grid_constant__ CUtensorMap two, const __grid_constant__ Descs D, const __grid_constant__ Descs DV) {
    extern __shared__ __align__(1024) uint8_t smem[];
    const uint32_t sb = smem_u32(smem);
    const int rank = blockIdx.x % 6, cl = blockIdx.x / 6, role = rank >= 4 ? 2 : rank & 1;
    if (threadIdx.x == 0) {
        if ((sb & 0x3FFFF) != SB0) __trap();
        const uint32_t bar = sb + C_BAR;
        for (int i = 0; i < B_NUM; i++) mbar_init(bar + i * 8, i == B_MBF ? 12 : 1);
        mbar_expect(bar + B_MF0 * 8, 8192);
        mbar_expect(bar + B_MF1 * 8, 8192);
        if (role == 2) {
            mbar_expect(bar + B_SC * 8, 2560);
            mbar_expect(bar + B_P0 * 8, 2048);
            mbar_expect(bar + B_P1 * 8, 2048);
            mbar_expect(bar + B_OF * 8, ONKV * 256);
        } else {
            mbar_expect(bar + B_XS * 8, role ? 5120 : 3072);
            mbar_expect(bar + B_OL * 8, 3072);
            mbar_expect(bar + B_OF * 8, ONKQ * 256);
        }
        asm volatile("fence.mbarrier_init.release.cluster;" ::: "memory");
        fence_async();
    }
    __syncthreads();
    cluster_sync();
    const int wg = uni(threadIdx.x >> 7);
    if (role == 2) {
        if (wg == 0) chain_main<true, 0>(&tv, &tv, &two, sb, cl, rank, DV);
        else chain_main<true, 1>(&tv, &tv, &two, sb, cl, rank, DV);
    } else {
        if (wg == 0) chain_main<false, 0>(&tq, &tk, &two, sb, cl, rank, D);
        else chain_main<false, 1>(&tq, &tk, &two, sb, cl, rank, D);
    }
    __syncwarp();
    cluster_sync();
}

constexpr int G_STAGES = 4;
constexpr uint32_t G_STAGE = 49152, G_EPI = G_STAGES * G_STAGE, G_BAR = G_EPI + 32768, G_SMEM = G_BAR + 256;

__device__ __forceinline__ void wg256(float* d, uint32_t da, uint32_t db, uint32_t accum) {
    asm volatile("{\n.reg .b64 da, db;\n.reg .pred p;\nsetp.ne.u32 p, %130, 0;\nmov.b64 da, {%128, " DESC_HI_SW128 "};\nmov.b64 db, {%129, " DESC_HI_SW128 "};\n"
                 "wgmma.mma_async.sync.aligned.m64n256k16.f32.bf16.bf16 {"
                 "%0,%1,%2,%3,%4,%5,%6,%7,%8,%9,%10,%11,%12,%13,%14,%15,%16,%17,%18,%19,%20,%21,%22,%23,%24,%25,%26,%27,%28,%29,%30,%31,"
                 "%32,%33,%34,%35,%36,%37,%38,%39,%40,%41,%42,%43,%44,%45,%46,%47,%48,%49,%50,%51,%52,%53,%54,%55,%56,%57,%58,%59,%60,%61,%62,%63,"
                 "%64,%65,%66,%67,%68,%69,%70,%71,%72,%73,%74,%75,%76,%77,%78,%79,%80,%81,%82,%83,%84,%85,%86,%87,%88,%89,%90,%91,%92,%93,%94,%95,"
                 "%96,%97,%98,%99,%100,%101,%102,%103,%104,%105,%106,%107,%108,%109,%110,%111,%112,%113,%114,%115,%116,%117,%118,%119,%120,%121,%122,%123,%124,%125,%126,%127"
                 "}, da, db, p, 1, 1, 0, 1;\n}"
                 : ACC16(d), ACC16((d + 16)), ACC16((d + 32)), ACC16((d + 48)), ACC16((d + 64)), ACC16((d + 80)), ACC16((d + 96)), ACC16((d + 112))
                 : "r"(da), "r"(db), "r"(accum));
}
__device__ __forceinline__ float sigmoidf_(float v) { return rcp(1.f + ex2(-1.4426950408889634f * v)); }

template <int MODE>
__global__ void __cluster_dims__(2, 1, 1) __launch_bounds__(384, 1)
gemm_kernel(const __grid_constant__ CUtensorMap tA, const __grid_constant__ CUtensorMap tB0, const __grid_constant__ CUtensorMap tB1,
            const __grid_constant__ CUtensorMap tOut, const __grid_constant__ CUtensorMap tX, const __grid_constant__ CUtensorMap tY) {
    constexpr int KB = MODE == 0 ? DM / 64 : (MODE == 1 ? FF / 64 : HD / 64);
    constexpr int NT = MODE == 0 ? FF / 128 : DM / 256;
    constexpr int NTILES = NT * 8;
    extern __shared__ __align__(1024) uint8_t smem[];
    const uint32_t sb = smem_u32(smem);
    const uint32_t full = sb + G_BAR, empty = full + 64;
    const int tid = threadIdx.x, lane = tid & 31;
    const int wg = __shfl_sync(~0u, tid >> 7, 0);
    const int rank = blockIdx.x & 1, pair = blockIdx.x >> 1, npair = gridDim.x >> 1;
    if (tid == 0) {
        for (int i = 0; i < G_STAGES; i++) { mbar_init(full + i * 8, 1); mbar_init(empty + i * 8, 16); }
        asm volatile("fence.mbarrier_init.release.cluster;" ::: "memory");
        fence_async();
    }
    __syncthreads();
    cluster_sync();
    if (wg == 0) {
        asm volatile("setmaxnreg.dec.sync.aligned.u32 40;");
        if (tid == 0) {
            uint32_t st = 0, ph = 1;
            for (int tile = pair; tile < NTILES; tile += npair) {
                const int mp = tile & 7, nt = tile >> 3, row0 = (mp * 2 + rank) * 128;
                const CUtensorMap* tB = (MODE == 0 && rank) ? &tB1 : &tB0;
                const int bcol = MODE == 0 ? nt * 128 : nt * 256 + rank * 128;
                for (int kb = 0; kb < KB; kb++) {
                    mbar_wait(empty + st * 8, ph);
                    const uint32_t base = sb + st * G_STAGE;
                    mbar_expect(full + st * 8, G_STAGE);
                    tma2d(base, &tA, kb * 64, row0, full + st * 8);
                    tma2d_mc(base + 16384 + rank * 16384, tB, bcol, kb * 64, full + st * 8, 3);
                    tma2d_mc(base + 16384 + rank * 16384 + 8192, tB, bcol + 64, kb * 64, full + st * 8, 3);
                    if (++st == G_STAGES) { st = 0; ph ^= 1; }
                }
                if (MODE == 2) {
                    for (int q = 0; q < 4; q++) {
                        mbar_wait(empty + st * 8, ph);
                        const uint32_t base = sb + st * G_STAGE;
                        mbar_expect(full + st * 8, 32768);
                        tma2d(base, &tX, nt * 256 + q * 64, row0, full + st * 8);
                        tma2d(base + 16384, &tY, nt * 256 + q * 64, row0, full + st * 8);
                        if (++st == G_STAGES) { st = 0; ph ^= 1; }
                    }
                }
            }
        }
        __syncwarp();
        cluster_sync();
    } else {
        asm volatile("setmaxnreg.inc.sync.aligned.u32 232;");
        const int cw = wg - 1, w4 = (tid >> 5) & 3;
        const uint32_t empty_dst = mapa(empty, lane & 1);
        const uint32_t epi = sb + G_EPI + cw * 16384;
        const int er = w4 * 16 + (lane & 15), ec = lane >> 4;
        uint32_t st = 0, ph = 0;
        float acc[128];
        for (int tile = pair; tile < NTILES; tile += npair) {
            const int mp = tile & 7, nt = tile >> 3, row0 = (mp * 2 + rank) * 128 + cw * 64;
            uint32_t prev = 0;
#pragma unroll 1
            for (int kb = 0; kb < KB; kb++) {
                mbar_wait(full + st * 8, ph);
                const uint32_t base = sb + st * G_STAGE;
                const uint32_t da = (((base + cw * 8192) & 0x3FFFF) >> 4) | (1u << 16);
                const uint32_t db = (((base + 16384) & 0x3FFFF) >> 4) | (512u << 16);
                wg_fence();
#pragma unroll
                for (int k = 0; k < 4; k++) wg256(acc, da + k * 2, db + k * 128, (kb | k) != 0);
                wg_commit();
                if (kb > 0) {
                    wg_wait<1>();
                    if (lane < 2) mbar_arrive_cluster(empty_dst + prev * 8);
                }
                prev = st;
                if (++st == G_STAGES) { st = 0; ph ^= 1; }
            }
            wg_wait<0>();
            reg_fence<128>(acc);
            if (lane < 2) mbar_arrive_cluster(empty_dst + prev * 8);
#pragma unroll
            for (int hp = 0; hp < (MODE == 0 ? 1 : 2); hp++) {
                uint32_t o[32];
#pragma unroll
                for (int bx = 0; bx < 2; bx++) {
                    uint32_t xa = 0;
                    if (MODE == 2) {
                        mbar_wait(full + st * 8, ph);
                        xa = sb + st * G_STAGE + (cw * 64 + er) * 128;
                    }
#pragma unroll
                    for (int j = 0; j < 4; j++) {
                        const int a0 = hp * 64 + bx * 32 + j * 8;
                        uint32_t* oo = o + bx * 16 + j * 4;
                        if (MODE == 0) {
#pragma unroll
                            for (int i = 0; i < 4; i++)
                                oo[i] = pack2(sigmoidf_(acc[a0 + 2 * i]) * acc[64 + a0 + 2 * i], sigmoidf_(acc[a0 + 2 * i + 1]) * acc[64 + a0 + 2 * i + 1]);
                        } else if (MODE == 1) {
#pragma unroll
                            for (int i = 0; i < 4; i++)
                                oo[i] = pack2(sigmoidf_(acc[a0 + 2 * i]) * acc[a0 + 2 * i], sigmoidf_(acc[a0 + 2 * i + 1]) * acc[a0 + 2 * i + 1]);
                        } else {
                            uint32_t xv[4], yv[4];
                            const uint32_t ad = xa + (((2 * j + ec) ^ (er & 7)) << 4);
                            ldsm4(xv, ad); ldsm4(yv, ad + 16384);
#pragma unroll
                            for (int i = 0; i < 4; i++)
                                oo[i] = pack2(fmaf(acc[a0 + 2 * i], bf_lo(yv[i]), bf_lo(xv[i])), fmaf(acc[a0 + 2 * i + 1], bf_hi(yv[i]), bf_hi(xv[i])));
                        }
                    }
                    if (MODE == 2) {
                        __syncwarp();
                        if (lane < 2) mbar_arrive_cluster(empty_dst + st * 8);
                        if (++st == G_STAGES) { st = 0; ph ^= 1; }
                    }
                }
                if ((tid & 127) == 0) asm volatile("cp.async.bulk.wait_group.read 0;" ::: "memory");
                bar_sync(1 + cw, 128);
#pragma unroll
                for (int bx = 0; bx < 2; bx++)
#pragma unroll
                    for (int j = 0; j < 4; j++) {
                        const uint32_t* oo = o + bx * 16 + j * 4;
                        stsm4(epi + bx * 8192 + er * 128 + (((2 * j + ec) ^ (er & 7)) << 4), oo[0], oo[1], oo[2], oo[3]);
                    }
                fence_async();
                bar_sync(1 + cw, 128);
                if ((tid & 127) == 0) {
                    const int col = MODE == 0 ? nt * 128 : nt * 256 + hp * 128;
                    tma2d_store(&tOut, col, row0, epi);
                    tma2d_store(&tOut, col + 64, row0, epi + 8192);
                    asm volatile("cp.async.bulk.commit_group;" ::: "memory");
                }
            }
        }
        if ((tid & 127) == 0) asm volatile("cp.async.bulk.wait_group 0;" ::: "memory");
        __syncwarp();
        cluster_sync();
    }
}

typedef CUresult (*EncodeFn)(CUtensorMap*, CUtensorMapDataType, cuuint32_t, void*, const cuuint64_t*, const cuuint64_t*, const cuuint32_t*,
                             const cuuint32_t*, CUtensorMapInterleave, CUtensorMapSwizzle, CUtensorMapL2promotion, CUtensorMapFloatOOBfill);

CUtensorMap make_map(EncodeFn enc, const void* p, int rows, int cols, int box_rows) {
    CUtensorMap m;
    cuuint64_t dims[2] = {(cuuint64_t)cols, (cuuint64_t)rows}, strides[1] = {(cuuint64_t)cols * 2};
    cuuint32_t box[2] = {64, (cuuint32_t)box_rows}, es[2] = {1, 1};
    enc(&m, CU_TENSOR_MAP_DATA_TYPE_BFLOAT16, 2, const_cast<void*>(p), dims, strides, box, es, CU_TENSOR_MAP_INTERLEAVE_NONE,
        CU_TENSOR_MAP_SWIZZLE_128B, CU_TENSOR_MAP_L2_PROMOTION_L2_128B, CU_TENSOR_MAP_FLOAT_OOB_FILL_NONE);
    return m;
}

}

extern "C" void kernel_launch(void* const* d_in, const int* in_sizes, int n_in, void* d_out, int out_size) {
    const __nv_bfloat16* x = (const __nv_bfloat16*)d_in[0];
    const __nv_bfloat16* mem0 = (const __nv_bfloat16*)d_in[1];
    void* fn = nullptr;
    cudaDriverEntryPointQueryResult qr;
    cudaGetDriverEntryPoint("cuTensorMapEncodeTiled", &fn, cudaEnableDefault, &qr);
    EncodeFn enc = (EncodeFn)fn;
    void *xn, *ox, *h, *y;
    cudaGetSymbolAddress(&xn, g_xn); cudaGetSymbolAddress(&ox, g_ox); cudaGetSymbolAddress(&h, g_h); cudaGetSymbolAddress(&y, g_y);

    const CUtensorMap tq = make_map(enc, d_in[2], DM, HD, 128), tk = make_map(enc, d_in[3], DM, HD, 128), tv = make_map(enc, d_in[4], DM, HD, 128);
    const CUtensorMap two16 = make_map(enc, d_in[5], HD, DM, 16);
    const CUtensorMap txn128 = make_map(enc, xn, SEQ, DM, 128), tg = make_map(enc, d_in[8], DM, FF, 64), tu = make_map(enc, d_in[9], DM, FF, 64);
    const CUtensorMap th64 = make_map(enc, h, SEQ, FF, 64), th128 = make_map(enc, h, SEQ, FF, 128), td = make_map(enc, d_in[10], FF, DM, 64);
    const CUtensorMap ty64 = make_map(enc, y, SEQ, DM, 64), ty128 = make_map(enc, y, SEQ, DM, 128), tx128 = make_map(enc, x, SEQ, DM, 128);
    const CUtensorMap tox = make_map(enc, ox, SEQ, HD, 128), two64 = make_map(enc, d_in[5], HD, DM, 64), tout = make_map(enc, d_out, SEQ, DM, 64);

    cudaFuncSetAttribute(chain_kernel, cudaFuncAttributeMaxDynamicSharedMemorySize, C_SMEM);
    cudaFuncSetAttribute(gemm_kernel<0>, cudaFuncAttributeMaxDynamicSharedMemorySize, G_SMEM);
    cudaFuncSetAttribute(gemm_kernel<1>, cudaFuncAttributeMaxDynamicSharedMemorySize, G_SMEM);
    cudaFuncSetAttribute(gemm_kernel<2>, cudaFuncAttributeMaxDynamicSharedMemorySize, G_SMEM);

    cudaStream_t st = cudaStreamPerThread;
    ln_kernel<<<SEQ / 8, 256, 0, st>>>(x, mem0);
    Descs D;
    for (int i = 0; i < 4; i++) D.sw[i] = DSW;
    D.ns = DNS;
    chain_kernel<<<96, 256, C_SMEM, st>>>(tq, tk, tv, two16, D, D);
    gemm_kernel<0><<<132, 384, G_SMEM, st>>>(txn128, tg, tu, th64, th64, th64);
    gemm_kernel<1><<<64, 384, G_SMEM, st>>>(th128, td, td, ty64, ty64, ty64);
    gemm_kernel<2><<<64, 384, G_SMEM, st>>>(tox, two64, two64, tout, tx128, ty128);
}
```

```cpp
#include <cuda_runtime.h>
#include <cuda_bf16.h>
#include <cuda.h>
#include <stdint.h>
#include <type_traits>

namespace {

constexpr int SEQ = 2048, DM = 1024, HD = 4096, FF = 3584, NSEG = 64;

__device__ __align__(1024) __nv_bfloat16 g_xn[SEQ * DM];
__device__ __align__(1024) uint4 g_xc[SEQ * DM / 8];
__device__ __align__(1024) __nv_bfloat16 g_ox[SEQ * HD];
__device__ __align__(1024) __nv_bfloat16 g_h[SEQ * FF];
__device__ __align__(1024) __nv_bfloat16 g_y[SEQ * DM];
__device__ __align__(1024) uint4 g_xmem[4][1024];
__device__ __align__(1024) uint4 g_xo[4][4096];
#define FSTR 8
__device__ __align__(1024) uint32_t g_flag[2][96 * FSTR];

__device__ __forceinline__ uint32_t smem_u32(const void* p) { return (uint32_t)__cvta_generic_to_shared(p); }
__device__ __forceinline__ uint32_t mapa(uint32_t a, uint32_t r) {
    uint32_t o; asm("mapa.shared::cluster.u32 %0, %1, %2;" : "=r"(o) : "r"(a), "r"(r)); return o;
}
__device__ __forceinline__ void mbar_init(uint32_t a, uint32_t cnt) {
    asm volatile("mbarrier.init.shared.b64 [%0], %1;" :: "r"(a), "r"(cnt) : "memory");
}
__device__ __forceinline__ void mbar_expect(uint32_t a, uint32_t bytes) {
    asm volatile("mbarrier.arrive.expect_tx.shared.b64 _, [%0], %1;" :: "r"(a), "r"(bytes) : "memory");
}
__device__ __forceinline__ void mbar_arrive_cluster(uint32_t a) {
    asm volatile("mbarrier.arrive.shared::cluster.b64 _, [%0];" :: "r"(a) : "memory");
}
__device__ __forceinline__ void spin_guard(uint32_t& it) {
    asm volatile("{\n.reg .pred p;\nadd.u32 %0, %0, 1;\nsetp.gt.u32 p, %0, 0x400000;\n@p st.shared.u32 [%0], %0;\n}" : "+r"(it));
}
__device__ __forceinline__ void mbar_wait(uint32_t a, uint32_t par) {
    asm volatile("{\n.reg .pred p;\n.reg .u32 i;\nmov.u32 i, 0;\n"
                 "WL:\nadd.u32 i, i, 1;\nsetp.gt.u32 p, i, 0x400000;\n@p st.shared.u32 [i], i;\n"
                 "mbarrier.try_wait.parity.shared::cta.b64 p, [%0], %1;\n@!p bra WL;\n}" :: "r"(a), "r"(par) : "memory");
}
__device__ __forceinline__ void mbar_arrive(uint32_t a) { asm volatile("mbarrier.arrive.shared.b64 _, [%0];" :: "r"(a) : "memory"); }
__device__ __forceinline__ void tma2d(uint32_t dst, const CUtensorMap* m, int c0, int c1, uint32_t bar) {
    asm volatile("cp.async.bulk.tensor.2d.shared::cluster.global.mbarrier::complete_tx::bytes [%0], [%1, {%3, %4}], [%2];"
                 :: "r"(dst), "l"(m), "r"(bar), "r"(c0), "r"(c1) : "memory");
}
__device__ __forceinline__ void tma2d_mc(uint32_t dst, const CUtensorMap* m, int c0, int c1, uint32_t bar, uint16_t mask) {
    asm volatile("cp.async.bulk.tensor.2d.shared::cluster.global.mbarrier::complete_tx::bytes.multicast::cluster [%0], [%1, {%3, %4}], [%2], %5;"
                 :: "r"(dst), "l"(m), "r"(bar), "r"(c0), "r"(c1), "h"(mask) : "memory");
}
__device__ __forceinline__ void bulk_mc(uint32_t dst, const void* src, uint32_t bytes, uint32_t bar, uint16_t mask) {
    asm volatile("cp.async.bulk.shared::cluster.global.mbarrier::complete_tx::bytes.multicast::cluster [%0], [%1], %2, [%3], %4;"
                 :: "r"(dst), "l"(src), "r"(bytes), "r"(bar), "h"(mask) : "memory");
}
__device__ __forceinline__ void bulk_ld(uint32_t dst, const void* src, uint32_t bytes, uint32_t bar) {
    asm volatile("cp.async.bulk.shared::cluster.global.mbarrier::complete_tx::bytes [%0], [%1], %2, [%3];"
                 :: "r"(dst), "l"(src), "r"(bytes), "r"(bar) : "memory");
}
__device__ __forceinline__ uint32_t gtick() { uint32_t c; asm volatile("mov.u32 %0, %%globaltimer_lo;" : "=r"(c)); return c >> 5; }
__device__ __forceinline__ uint32_t gtick_dep(uint32_t zero) {
    uint32_t c;
    asm volatile("{\n.reg .pred p;\nsetp.eq.u32 p, %1, 0;\nmov.u32 %0, 0;\n@p mov.u32 %0, %%globaltimer_lo;\n}" : "=r"(c) : "r"(zero));
    return c >> 5;
}
__device__ __forceinline__ uint32_t ld_relaxed1(const void* p) {
    uint32_t v; asm volatile("ld.relaxed.gpu.global.u32 %0, [%1];" : "=r"(v) : "l"(p) : "memory"); return v;
}
__device__ __forceinline__ bool any_nan(float a, float b) {
    uint32_t r;
    asm volatile("{\n.reg .pred p;\nsetp.nan.f32 p, %1, %2;\nvote.sync.any.pred p, p, 0xffffffff;\nselp.u32 %0, 1, 0, p;\n}" : "=r"(r) : "f"(a), "f"(b));
    return r;
}
__device__ __forceinline__ bool any_nan_unless(float a, float b, uint32_t off) {
    uint32_t r;
    asm volatile("{\n.reg .pred p, q;\nsetp.ne.u32 q, %3, 0xffffffff;\nsetp.nan.and.f32 p, %1, %2, q;\nvote.sync.any.pred p, p, 0xffffffff;\nselp.u32 %0, 1, 0, p;\n}"
                 : "=r"(r) : "f"(a), "f"(b), "r"(off));
    return r;
}
__device__ __forceinline__ bool st_async4_unless_nan(uint32_t a, uint32_t bar, const float* v) {
    uint32_t r;
    asm volatile("{\n.reg .pred p;\nsetp.nan.f32 p, %3, %4;\nvote.sync.any.pred p, p, 0xffffffff;\n"
                 "@!p st.async.shared::cluster.mbarrier::complete_tx::bytes.v4.f32 [%1], {%3,%4,%5,%6}, [%2];\nselp.u32 %0, 1, 0, p;\n}"
                 : "=r"(r) : "r"(a), "r"(bar), "f"(v[0]), "f"(v[1]), "f"(v[2]), "f"(v[3]) : "memory");
    return r;
}
__device__ __forceinline__ void bar_arrive(int id, int n) { asm volatile("bar.arrive %0, %1;" :: "r"(id), "r"(n) : "memory"); }
__device__ __forceinline__ uint32_t clk() { uint32_t c; asm volatile("mov.u32 %0, %%clock;" : "=r"(c)); return c; }
__device__ __forceinline__ void tma2d_store(const CUtensorMap* m, int c0, int c1, uint32_t src) {
    asm volatile("cp.async.bulk.tensor.2d.global.shared::cta.bulk_group [%0, {%1, %2}], [%3];"
                 :: "l"(m), "r"(c0), "r"(c1), "r"(src) : "memory");
}
__device__ __forceinline__ void bar_sync(int id, int n) { asm volatile("bar.sync %0, %1;" :: "r"(id), "r"(n) : "memory"); }
__device__ __forceinline__ void fence_async() { asm volatile("fence.proxy.async.shared::cta;" ::: "memory"); }
__device__ __forceinline__ void cluster_sync() {
    asm volatile("barrier.cluster.arrive.release.aligned;\nbarrier.cluster.wait.acquire.aligned;" ::: "memory");
}
__device__ __forceinline__ void ldsm4(uint32_t* r, uint32_t a) {
    asm volatile("ldmatrix.sync.aligned.m8n8.x4.shared.b16 {%0,%1,%2,%3}, [%4];"
                 : "=r"(r[0]), "=r"(r[1]), "=r"(r[2]), "=r"(r[3]) : "r"(a) : "memory");
}
__device__ __forceinline__ void ldsm4t(uint32_t* r, uint32_t a) {
    asm volatile("ldmatrix.sync.aligned.m8n8.x4.trans.shared.b16 {%0,%1,%2,%3}, [%4];"
                 : "=r"(r[0]), "=r"(r[1]), "=r"(r[2]), "=r"(r[3]) : "r"(a) : "memory");
}
__device__ __forceinline__ void stsm4(uint32_t a, uint32_t r0, uint32_t r1, uint32_t r2, uint32_t r3) {
    asm volatile("stmatrix.sync.aligned.m8n8.x4.shared.b16 [%0], {%1,%2,%3,%4};" :: "r"(a), "r"(r0), "r"(r1), "r"(r2), "r"(r3) : "memory");
}
__device__ __forceinline__ void stsm4t(uint32_t a, uint32_t r0, uint32_t r1, uint32_t r2, uint32_t r3) {
    asm volatile("stmatrix.sync.aligned.m8n8.x4.trans.shared.b16 [%0], {%1,%2,%3,%4};" :: "r"(a), "r"(r0), "r"(r1), "r"(r2), "r"(r3) : "memory");
}
__device__ __forceinline__ void stsm2(uint32_t a, uint32_t r0, uint32_t r1) {
    asm volatile("stmatrix.sync.aligned.m8n8.x2.shared.b16 [%0], {%1,%2};" :: "r"(a), "r"(r0), "r"(r1) : "memory");
}
__device__ __forceinline__ void stsm2t(uint32_t a, uint32_t r0, uint32_t r1) {
    asm volatile("stmatrix.sync.aligned.m8n8.x2.trans.shared.b16 [%0], {%1,%2};" :: "r"(a), "r"(r0), "r"(r1) : "memory");
}
__device__ __forceinline__ uint32_t movm(uint32_t a) {
    uint32_t d; asm volatile("movmatrix.sync.aligned.m8n8.trans.b16 %0, %1;" : "=r"(d) : "r"(a)); return d;
}
__device__ __forceinline__ void mma16(float* d, uint32_t a0, uint32_t a1, uint32_t a2, uint32_t a3, uint32_t b0, uint32_t b1) {
    asm volatile("mma.sync.aligned.m16n8k16.row.col.f32.bf16.bf16.f32 {%0,%1,%2,%3}, {%4,%5,%6,%7}, {%8,%9}, {%0,%1,%2,%3};"
                 : "+f"(d[0]), "+f"(d[1]), "+f"(d[2]), "+f"(d[3]) : "r"(a0), "r"(a1), "r"(a2), "r"(a3), "r"(b0), "r"(b1));
}
__device__ __forceinline__ void mma8(float* d, uint32_t a0, uint32_t a1, uint32_t b0) {
    asm volatile("mma.sync.aligned.m16n8k8.row.col.f32.bf16.bf16.f32 {%0,%1,%2,%3}, {%4,%5}, {%6}, {%0,%1,%2,%3};"
                 : "+f"(d[0]), "+f"(d[1]), "+f"(d[2]), "+f"(d[3]) : "r"(a0), "r"(a1), "r"(b0));
}
__device__ __forceinline__ uint32_t pack2(float lo, float hi) {
    uint32_t r; asm("cvt.rn.bf16x2.f32 %0, %1, %2;" : "=r"(r) : "f"(hi), "f"(lo)); return r;
}
__device__ __forceinline__ float bf_lo(uint32_t v) { return __uint_as_float(v << 16); }
__device__ __forceinline__ float bf_hi(uint32_t v) { return __uint_as_float(v & 0xFFFF0000u); }
__device__ __forceinline__ float ex2(float x) { float y; asm("ex2.approx.ftz.f32 %0, %1;" : "=f"(y) : "f"(x)); return y; }
__device__ __forceinline__ float rcp(float x) { float y; asm("rcp.approx.ftz.f32 %0, %1;" : "=f"(y) : "f"(x)); return y; }
__device__ __forceinline__ void sts4f(uint32_t a, float x, float y, float z, float w) {
    asm volatile("st.shared.v4.f32 [%0], {%1,%2,%3,%4};" :: "r"(a), "f"(x), "f"(y), "f"(z), "f"(w) : "memory");
}
__device__ __forceinline__ void sts4u(uint32_t a, uint4 v) {
    asm volatile("st.shared.v4.u32 [%0], {%1,%2,%3,%4};" :: "r"(a), "r"(v.x), "r"(v.y), "r"(v.z), "r"(v.w) : "memory");
}
__device__ __forceinline__ float4 lds4f(uint32_t a) {
    float4 v; asm volatile("ld.shared.v4.f32 {%0,%1,%2,%3}, [%4];" : "=f"(v.x), "=f"(v.y), "=f"(v.z), "=f"(v.w) : "r"(a) : "memory"); return v;
}
__device__ __forceinline__ float2 lds2f(uint32_t a) {
    float2 v; asm volatile("ld.shared.v2.f32 {%0,%1}, [%2];" : "=f"(v.x), "=f"(v.y) : "r"(a) : "memory"); return v;
}
__device__ __forceinline__ uint4 lds4u(uint32_t a) {
    uint4 v; asm volatile("ld.shared.v4.u32 {%0,%1,%2,%3}, [%4];" : "=r"(v.x), "=r"(v.y), "=r"(v.z), "=r"(v.w) : "r"(a) : "memory"); return v;
}
__device__ __forceinline__ uint32_t lds1u(uint32_t a) {
    uint32_t v; asm volatile("ld.shared.u32 %0, [%1];" : "=r"(v) : "r"(a) : "memory"); return v;
}
__device__ __forceinline__ uint2 lds2u(uint32_t a) {
    uint2 v; asm volatile("ld.shared.v2.u32 {%0,%1}, [%2];" : "=r"(v.x), "=r"(v.y) : "r"(a) : "memory"); return v;
}
__device__ __forceinline__ void st_async4(uint32_t a, uint32_t bar, uint32_t x, uint32_t y, uint32_t z, uint32_t w) {
    asm volatile("st.async.shared::cluster.mbarrier::complete_tx::bytes.v4.b32 [%0], {%1,%2,%3,%4}, [%5];"
                 :: "r"(a), "r"(x), "r"(y), "r"(z), "r"(w), "r"(bar) : "memory");
}
__device__ __forceinline__ void st_async2(uint32_t a, uint32_t bar, uint32_t x, uint32_t y) {
    asm volatile("st.async.shared::cluster.mbarrier::complete_tx::bytes.v2.b32 [%0], {%1,%2}, [%3];"
                 :: "r"(a), "r"(x), "r"(y), "r"(bar) : "memory");
}
__device__ __forceinline__ void st_async1(uint32_t a, uint32_t bar, uint32_t x) {
    asm volatile("st.async.shared::cluster.mbarrier::complete_tx::bytes.b32 [%0], %1, [%2];" :: "r"(a), "r"(x), "r"(bar) : "memory");
}
__device__ __forceinline__ uint4 ld_relaxed4(const uint4* p) {
    uint4 v;
    asm volatile("ld.relaxed.gpu.global.v4.u32 {%0,%1,%2,%3}, [%4];" : "=r"(v.x), "=r"(v.y), "=r"(v.z), "=r"(v.w) : "l"(p) : "memory");
    return v;
}
__device__ __forceinline__ void st_relaxed4(uint4* p, uint4 v) {
    asm volatile("st.relaxed.gpu.global.v4.u32 [%0], {%1,%2,%3,%4};" :: "l"(p), "r"(v.x), "r"(v.y), "r"(v.z), "r"(v.w) : "memory");
}
__device__ __forceinline__ void st_pred1(void* p, uint32_t v, bool on) {
    asm volatile("{\n.reg .pred p;\nsetp.ne.u32 p, %2, 0;\n@p st.relaxed.gpu.global.u32 [%0], %1;\n}" :: "l"(p), "r"(v), "r"((uint32_t)on) : "memory");
}
__device__ __forceinline__ void st_pred4(void* p, uint4 v, bool on) {
    asm volatile("{\n.reg .pred p;\nsetp.ne.u32 p, %5, 0;\n@p st.global.v4.u32 [%0], {%1,%2,%3,%4};\n}"
                 :: "l"(p), "r"(v.x), "r"(v.y), "r"(v.z), "r"(v.w), "r"((uint32_t)on) : "memory");
}
__device__ __forceinline__ void st_relaxed1(void* p, uint32_t v) {
    asm volatile("st.relaxed.gpu.global.u32 [%0], %1;" :: "l"(p), "r"(v) : "memory");
}
__device__ __forceinline__ uint32_t umax4(uint4 v) { return max(max(v.x, v.y), max(v.z, v.w)); }
__device__ __forceinline__ void wg_fence() { asm volatile("wgmma.fence.sync.aligned;" ::: "memory"); }
__device__ __forceinline__ void wg_commit() { asm volatile("wgmma.commit_group.sync.aligned;" ::: "memory"); }
template <int N> __device__ __forceinline__ void wg_wait() { asm volatile("wgmma.wait_group.sync.aligned %0;" :: "n"(N) : "memory"); }
template <int N> __device__ __forceinline__ void reg_fence(float* d) {
#pragma unroll
    for (int i = 0; i < N; i++) asm volatile("" : "+f"(d[i]) :: "memory");
}
#define ACC16(d) "+f"(d[0]), "+f"(d[1]), "+f"(d[2]), "+f"(d[3]), "+f"(d[4]), "+f"(d[5]), "+f"(d[6]), "+f"(d[7]), \
                 "+f"(d[8]), "+f"(d[9]), "+f"(d[10]), "+f"(d[11]), "+f"(d[12]), "+f"(d[13]), "+f"(d[14]), "+f"(d[15])
#define DESC_HI_SW128 "0x40000040"
#define OUT16(d) "=f"(d[0]), "=f"(d[1]), "=f"(d[2]), "=f"(d[3]), "=f"(d[4]), "=f"(d[5]), "=f"(d[6]), "=f"(d[7]), \
                 "=f"(d[8]), "=f"(d[9]), "=f"(d[10]), "=f"(d[11]), "=f"(d[12]), "=f"(d[13]), "=f"(d[14]), "=f"(d[15])
template <int ACCUM, int BOFF>
__device__ __forceinline__ void wg32_rs(float* d, const uint32_t* a, uint64_t dsw) {
    if (ACCUM)
        asm volatile("{\n.reg .b64 db;\nadd.s64 db, %20, %21;\n"
                     "wgmma.mma_async.sync.aligned.m64n32k16.f32.bf16.bf16 {%0,%1,%2,%3,%4,%5,%6,%7,%8,%9,%10,%11,%12,%13,%14,%15}, "
                     "{%16,%17,%18,%19}, db, 1, 1, 1, 0;\n}"
                     : ACC16(d) : "r"(a[0]), "r"(a[1]), "r"(a[2]), "r"(a[3]), "l"(dsw), "n"(BOFF));
    else
        asm volatile("{\n.reg .b64 db;\nadd.s64 db, %20, %21;\n"
                     "wgmma.mma_async.sync.aligned.m64n32k16.f32.bf16.bf16 {%0,%1,%2,%3,%4,%5,%6,%7,%8,%9,%10,%11,%12,%13,%14,%15}, "
                     "{%16,%17,%18,%19}, db, 0, 1, 1, 0;\n}"
                     : OUT16(d) : "r"(a[0]), "r"(a[1]), "r"(a[2]), "r"(a[3]), "l"(dsw), "n"(BOFF));
}
template <int AOFF, int BOFF>
__device__ __forceinline__ void wg32_ss(float* d, uint64_t dsw) {
    asm volatile("{\n.reg .b64 da, db;\nadd.s64 da, %16, %17;\nadd.s64 db, %16, %18;\n"
                 "wgmma.mma_async.sync.aligned.m64n32k16.f32.bf16.bf16 {%0,%1,%2,%3,%4,%5,%6,%7,%8,%9,%10,%11,%12,%13,%14,%15}, "
                 "da, db, 1, 1, 1, 1, 0;\n}"
                 : ACC16(d) : "l"(dsw), "n"(AOFF), "n"(BOFF));
}
template <int ACCUM, int AOFF, int BOFF>
__device__ __forceinline__ void wg8_ss(float* d, uint64_t dsw, uint64_t dns) {
    if (!ACCUM)
        asm volatile("{\n.reg .b64 da, db;\nadd.s64 da, %4, %6;\nadd.s64 db, %5, %7;\n"
                     "wgmma.mma_async.sync.aligned.m64n8k16.f32.bf16.bf16 {%0,%1,%2,%3}, da, db, 0, 1, 1, 1, 0;\n}"
                     : "=f"(d[0]), "=f"(d[1]), "=f"(d[2]), "=f"(d[3]) : "l"(dsw), "l"(dns), "n"(AOFF), "n"(BOFF));
    else
        asm volatile("{\n.reg .b64 da, db;\nadd.s64 da, %4, %6;\nadd.s64 db, %5, %7;\n"
                     "wgmma.mma_async.sync.aligned.m64n8k16.f32.bf16.bf16 {%0,%1,%2,%3}, da, db, 1, 1, 1, 1, 0;\n}"
                     : "+f"(d[0]), "+f"(d[1]), "+f"(d[2]), "+f"(d[3]) : "l"(dsw), "l"(dns), "n"(AOFF), "n"(BOFF));
}
template <int I0, int I1, class F>
__device__ __forceinline__ void static_for(F&& f) {
    if constexpr (I0 < I1) { f(std::integral_constant<int, I0>{}); static_for<I0 + 1, I1>(f); }
}
template <int I0, int I1, int AOFF, int BOFF>
__device__ __forceinline__ void wg8_chain(float* d, uint64_t dsw, uint64_t dns) {
    wg_fence();
    static_for<I0, I1>([&](auto i) { wg8_ss<i.value != 0, AOFF + i.value * 128, BOFF + i.value * 16>(d, dsw, dns); });
    wg_commit();
}

__global__ void __launch_bounds__(256) ln_kernel(const __nv_bfloat16* __restrict__ x, const __nv_bfloat16* __restrict__ mem0) {
    const int lane = threadIdx.x & 31, row = blockIdx.x * 8 + (threadIdx.x >> 5);
    const uint4* src = reinterpret_cast<const uint4*>(x + (size_t)row * DM);
    uint4 v[4];
#pragma unroll
    for (int j = 0; j < 4; j++) v[j] = src[j * 32 + lane];
    const int gi = blockIdx.x * 256 + threadIdx.x;
    const uint4 poison = make_uint4(~0u, ~0u, ~0u, ~0u);
    if (gi < 1024) {
        uint4 m = reinterpret_cast<const uint4*>(mem0)[(gi & 7) * 128 + (gi >> 3)];
        if (m.x == ~0u) m.x = 0x7FFF7FFFu;
        if (m.y == ~0u) m.y = 0x7FFF7FFFu;
        if (m.z == ~0u) m.z = 0x7FFF7FFFu;
        if (m.w == ~0u) m.w = 0x7FFF7FFFu;
        g_xmem[0][gi] = m;
    } else if (gi < 4096) {
        (&g_xmem[0][0])[gi] = poison;
    } else if (gi < 4096 + 16384) {
        (&g_xo[0][0])[gi - 4096] = poison;
    } else if (gi < 4096 + 16384 + 48 * FSTR) {
        reinterpret_cast<uint4*>(&g_flag[0][0])[gi - 4096 - 16384] = poison;
    }
    float f[32];
#pragma unroll
    for (int j = 0; j < 4; j++) {
        f[j * 8 + 0] = bf_lo(v[j].x); f[j * 8 + 1] = bf_hi(v[j].x); f[j * 8 + 2] = bf_lo(v[j].y); f[j * 8 + 3] = bf_hi(v[j].y);
        f[j * 8 + 4] = bf_lo(v[j].z); f[j * 8 + 5] = bf_hi(v[j].z); f[j * 8 + 6] = bf_lo(v[j].w); f[j * 8 + 7] = bf_hi(v[j].w);
    }
    float s = 0.f;
#pragma unroll
    for (int i = 0; i < 32; i++) s += f[i];
#pragma unroll
    for (int o = 16; o; o >>= 1) s += __shfl_xor_sync(~0u, s, o);
    const float mean = s * (1.f / DM);
    float q = 0.f;
#pragma unroll
    for (int i = 0; i < 32; i++) { f[i] -= mean; q += f[i] * f[i]; }
#pragma unroll
    for (int o = 16; o; o >>= 1) q += __shfl_xor_sync(~0u, q, o);
    const float r = 1.f / sqrtf(q * (1.f / DM) + 1e-5f);
    uint4* dst = reinterpret_cast<uint4*>(g_xn + (size_t)row * DM);
    uint4* dst2 = g_xc + (row >> 5) * 4096 + (lane >> 3) * 256 + (row & 31) * 8 + ((lane & 7) ^ (row & 7));
#pragma unroll
    for (int j = 0; j < 4; j++) {
        const uint4 o = make_uint4(pack2(f[j * 8] * r, f[j * 8 + 1] * r), pack2(f[j * 8 + 2] * r, f[j * 8 + 3] * r),
                                   pack2(f[j * 8 + 4] * r, f[j * 8 + 5] * r), pack2(f[j * 8 + 6] * r, f[j * 8 + 7] * r));
        dst[j * 32 + lane] = o;
        dst2[(j & 1) * 2048 + (j >> 1) * 1024] = o;
    }
}

#define ONKQ 45
constexpr int ONKV = 128 - 2 * ONKQ;
constexpr uint32_t SB0 = 1024;
constexpr uint32_t C_WS = 0, C_XN = 65536, C_MB = 98304, C_WO = 114688, C_SMEM = 232448;
constexpr uint32_t C_BAR = C_SMEM - 384, C_CAL = C_BAR + 192;
constexpr uint32_t C_SLOTQ = C_WO + ONKQ * 2048, C_QM = C_SLOTQ + 4096, C_KM = C_QM + 1024, C_QX = C_SLOTQ + 8192, C_KX = C_QX + 4096,
                   C_XSL = C_KX + 4096, C_OL = C_XSL + 5120;
constexpr uint32_t C_SLOTV = C_WO + ONKV * 2048, C_V = C_SLOTV + 8192, C_PL = C_V + 20480, C_SL = C_PL + 4096;
static_assert(C_OL + 3072 <= C_BAR && C_SL + 2560 <= C_BAR, "smem overflow");
enum { B_W0 = 0, B_W1, B_W2, B_WS, B_WO, B_XF0, B_XF1, B_SC, B_P0, B_P1, B_XS, B_OL, B_MF0, B_MF1, B_OF, B_RT0, B_RT1, B_VF, B_MBF, B_NUM };
struct Descs { uint64_t sw[4], ns; };
constexpr uint64_t DSW = 0x4000004000010000ull, DNS = 0x0000001000080000ull;
template <int V> using ic = std::integral_constant<int, V>;
constexpr float SM_SCALE = 0.08838834764831845f * 1.4426950408889634f;

#define TSD(i) do {} while (0)
#define TS_FLUSH(w)
#define TSX(i, c)
#define TS(i)
#define NOFILL 0
#define DLY1 2250
#define DLY2 1350
#define STPOS 12
#define OTAIL 3
#define DLYS 450
#define DLYB 100
#define VLEAD 3

#define VEARLY 8
#define QSPLIT 20
__device__ __forceinline__ bool elect() {
    uint32_t r;
    asm volatile("{\n.reg .pred p;\nelect.sync _|p, 0xffffffff;\nselp.u32 %0, 1, 0, p;\n}" : "=r"(r));
    return r;
}
__device__ __forceinline__ int uni(int v) { return __shfl_sync(~0u, v, 0); }
__device__ __forceinline__ void calibrate(uint32_t cal, float keep) {
    const uint32_t t0 = gtick();
    uint32_t t, it = 0;
    do { t = gtick(); spin_guard(it); } while (t == t0);
    const uint32_t c = clk();
    const uint4 p = lds4u(cal);
    const float cpt = 256.f * fminf(fmaxf(__fdividef((float)(c - p.y), (float)((t - p.x) & 0x7FFFFFF)), 16.f), 128.f);
    __syncwarp();
    sts4u(cal, make_uint4(t, c, (uint32_t)(keep > 0.f ? fmaf(keep, (float)p.z - cpt, cpt) : cpt), 0));
}
struct Stamps { uint32_t v[6]; };
__device__ __forceinline__ void load_stamps2(Stamps& t, const uint32_t* f, uint32_t l16, bool on = true) {
    const char* p = reinterpret_cast<const char*>(f) + (l16 >> 2) * FSTR;
    asm volatile("{\n.reg .pred p;\nsetp.ne.u32 p, %7, 0;\nmov.u32 %0, 63;\nmov.u32 %1, 63;\nmov.u32 %2, 63;\nmov.u32 %3, 63;\nmov.u32 %4, 63;\nmov.u32 %5, 63;\n"
                 "@p ld.relaxed.gpu.global.v2.u32 {%0, %1}, [%6];\n@p ld.relaxed.gpu.global.v2.u32 {%2, %3}, [%6 + %8];\n"
                 "@p ld.relaxed.gpu.global.v2.u32 {%4, %5}, [%6 + %9];\n}"
                 : "=&r"(t.v[0]), "=&r"(t.v[1]), "=&r"(t.v[2]), "=&r"(t.v[3]), "=&r"(t.v[4]), "=&r"(t.v[5])
                 : "l"(p), "r"((uint32_t)on), "n"(128 * FSTR), "n"(256 * FSTR) : "memory");
}
__device__ __forceinline__ void load_stamps1(uint32_t* v, const uint32_t* f, uint32_t l16, bool on = true) {
    const char* p = reinterpret_cast<const char*>(f) + (l16 >> 2) * FSTR;
    asm volatile("{\n.reg .pred p;\nsetp.ne.u32 p, %4, 0;\nmov.u32 %0, 63;\nmov.u32 %1, 63;\nmov.u32 %2, 63;\n"
                 "@p ld.relaxed.gpu.global.u32 %0, [%3];\n@p ld.relaxed.gpu.global.u32 %1, [%3 + %5];\n@p ld.relaxed.gpu.global.u32 %2, [%3 + %6];\n}"
                 : "=&r"(v[0]), "=&r"(v[1]), "=&r"(v[2]) : "l"(p), "r"((uint32_t)on), "n"(128 * FSTR), "n"(256 * FSTR) : "memory");
}
template <int N>
__device__ __forceinline__ uint32_t stamps_missing(const uint32_t* v, int s) {
    uint32_t x = 0;
#pragma unroll
    for (int i = 0; i < N; i++) x |= v[i] ^ s;
    return x & 63;
}
template <int N>
__device__ __forceinline__ uint32_t latest_stamp(const uint32_t* v, const uint4 cal) {
    int late = (int)(v[0] - (cal.x << 6));
#pragma unroll
    for (int i = 1; i < N; i++) late = max(late, (int)(v[i] - (cal.x << 6)));
    return cal.y + (((late >> 6) * (int)cal.z) >> 8);
}
__device__ __forceinline__ void wait_clock(uint32_t target) {
    while (__any_sync(~0u, target - clk() < 65536u)) {}
}

template <int BYTES>
__device__ __forceinline__ bool incomplete(uint32_t buf, uint32_t l16) {
    uint32_t m = 0;
#pragma unroll 1
    for (int o = 0; o < BYTES; o += 256) m = max(m, umax4(lds4u(buf + o + (l16 & 255))));
    return __any_sync(~0u, m == ~0u);
}
__device__ __forceinline__ void refetch(uint32_t buf, const uint4* src, uint32_t bytes, uint32_t b, int w4, int barid, uint32_t& tries) {
    spin_guard(tries);
    bar_sync(barid, 128);
    if (w4 == 0 && elect()) { mbar_expect(b, bytes); bulk_ld(buf, src, bytes, b); }
    __syncwarp();
    mbar_wait(b, 0);
    bar_sync(barid, 128);
    if (w4 == 0 && elect()) mbar_arrive(b);
    __syncwarp();
}

template <bool ISV, int WG>
__device__ __forceinline__ void chain_main(const CUtensorMap* tA, const CUtensorMap* tB, const CUtensorMap* tWo,
                                           const uint32_t sb, const int cl, const int rank, const Descs& D) {
    const int tid = threadIdx.x;
    uint32_t l16 = __shfl_sync(~0u, (tid & 31) * 16, tid & 31);
    const int w4 = uni((tid >> 5) & 3);
    const int role = ISV ? 2 : uni(rank & 1), hh = ISV ? rank - 4 : rank >> 1, head = 2 * cl + hh;
    const uint32_t bar = sb + C_BAR;
    constexpr int ONK = ISV ? ONKV : ONKQ;
    const int ostart = uni(hh * 128 + role * ONKQ);

    uint32_t wk[24][4], wv[24][4];
    uint32_t a_adr;
    {
        const int colA = head * 128 + (ISV ? 0 : role * 64), colB = head * 128 + (ISV ? 64 : role * 64);
        auto load_chunk = [&](uint32_t dst, int j, uint32_t b) {
            mbar_expect(b, 65536);
            tma2d(dst, tA, colA, j * 128, b);
            tma2d(dst + 16384, tB, colB, j * 128, b);
            tma2d(dst + 32768, tB, colB, 512 + j * 128, b);
            tma2d(dst + 49152, tA, colA, 512 + j * 128, b);
        };
        if (WG == 0 && tid == 0)
            for (int j = 0; j < 3; j++) load_chunk(sb + j * 65536, j, bar + (B_W0 + j) * 8);
        if (WG == 1 && w4 == 0) calibrate(sb + C_CAL, 0.f);
        const int lane = tid & 31, kr = (lane & 7) + ((lane >> 4) << 3);
        a_adr = __shfl_sync(~0u, sb + WG * 32768 + kr * 128 + (((w4 * 2 + ((lane >> 3) & 1)) ^ (kr & 7)) << 4), lane);
#pragma unroll
        for (int j = 0; j < 3; j++) {
            mbar_wait(bar + (B_W0 + j) * 8, 0);
#pragma unroll
            for (int i = 0; i < 8; i++) {
                ldsm4t(wk[j * 8 + i], a_adr + j * 65536 + i * 2048);
                ldsm4t(wv[j * 8 + i], a_adr + j * 65536 + 16384 + i * 2048);
            }
            if (j != 1) {
                bar_sync(6, 256);
                if (WG == 0 && j == 0 && tid == 0) load_chunk(sb + C_WS, 3, bar + B_WS * 8);
                if (WG == 0 && j == 2 && w4 == 0) {
                    if (lane == 0) mbar_expect(bar + B_WO * 8, ONK * 2048);
                    __syncwarp();
                    for (int i = lane; i < ONK; i += 32) tma2d(sb + C_WO + i * 2048, tWo, cl * 64, (ostart + i) * 16, bar + B_WO * 8);
                }
                __syncwarp();
            }
        }
        if (NOFILL) { for (uint32_t o = C_WO + ONK * 2048 + tid * 16; o < C_BAR; o += 4096) sts4u(sb + o, make_uint4(0, 0, 0, 0)); bar_sync(6, 256); }
        asm volatile("griddepcontrol.wait;" ::: "memory");
        asm volatile("griddepcontrol.launch_dependents;" ::: "memory");
        if (WG == 1 && w4 == 0) calibrate(sb + C_CAL, 0.f);
    }

    constexpr uint32_t SLOT = ISV ? C_SLOTV : C_SLOTQ;
    constexpr int WS_A = (SB0 + C_WS + WG * 32768) >> 4, WO_A = (SB0 + C_WO) >> 4, MB_A = (SB0 + C_MB) >> 4;
#define XN_A(ks) (int)(((SB0 + C_XN + WG * 16384) >> 4) + ((ks) >> 2) * 256 + ((ks) & 3) * 2)
    const uint32_t slot = uni(sb + SLOT + w4 * 512), mbw = sb + C_MB + WG * 8192;
    const uint32_t sb_v = uni(mapa(sb, 4 + hh));
    const uint32_t sb_x = uni(mapa(sb, 2 * hh + WG));
    const uint32_t sb_o = uni(mapa(sb, w4));
    const uint32_t u_off = uni(ISV ? (head * 128 + w4 * 32) * 16 : (cl * 4 + rank) * 256 + (w4 & 1) * 128);
    const uint32_t v_row = uni(sb + C_V + (2 * WG + (w4 >> 1)) * 512), v_b = uni((w4 & 1) * 64);
    const uint32_t u_flag = uni(blockIdx.x * FSTR);
    const uint32_t f_bytes = uni(w4 ? ONKV * 128 : ONKQ * 256), f_bar = uni((w4 ? sb_v : sb) + C_BAR + B_OF * 8);
    const uint32_t f_dst = uni(w4 ? sb_v + C_MB + role * (ONKV * 128) : sb + C_MB);
    const uint32_t f_src = uni(w4 ? (ostart + (2 - role) * ONKQ) * 256 + role * (ONKV * 128) : ostart * 256);
    const uint32_t m_dst = uni(sb + C_MB + role * 8192), m_bar = uni(bar + (B_MF0 + role) * 8);
    uint32_t target, missing;
    int s = -1;
    uint32_t pf[4][4];
    float xk[16], xv[16];

    auto load_tokens = [&](int seg, int wina, int g) {
        const int khalf = ISV ? 1 - wina : wina;
        if (!NOFILL && elect()) {
            mbar_expect(bar + (B_XF0 + g) * 8, 16384);
            bulk_ld(sb + C_XN + g * 16384, g_xc + (seg * 4 + khalf * 2 + g) * 1024, 16384, bar + (B_XF0 + g) * 8);
        }
        __syncwarp();
    };
    auto prefetch = [&]() {
#pragma unroll
        for (int i = 0; i < 4; i++) ldsm4t(pf[i], a_adr + C_WS + (i & 1) * 16384 + (i >> 1) * 2048);
    };
    constexpr int HA = ISV ? 0 : 1;
    auto products = [&](auto give, auto half, auto init, auto i0, auto i1, const uint64_t d) {
        static_for<i0.value, i1.value>([&](auto i) {
            constexpr int ks = half.value * 16 + i.value, acc = !(init.value && i.value == 0);
            if constexpr (ks >= 24) wg32_ss<WS_A + give.value * 1024 + (ks - 24) * 128, XN_A(i.value)>(give.value ? xv : xk, d);
            else if constexpr (give.value) wg32_rs<acc, XN_A(i.value)>(xv, wv[ks], d);
            else wg32_rs<acc, XN_A(i.value)>(xk, wk[ks], d);
        });
    };
    auto stream_a = [&](const uint64_t dk, const uint64_t dv) {
        if (NOFILL) return;
        wg_fence();
        products(ic<0>{}, ic<HA>{}, ic<1>{}, ic<0>{}, ic<8>{}, dk);
        products(ic<1>{}, ic<HA>{}, ic<1>{}, ic<0>{}, ic<16>{}, dv);
        products(ic<0>{}, ic<HA>{}, ic<1>{}, ic<8>{}, ic<16>{}, dk);
        wg_commit();
    };
    auto token_softmax = [&]() {
        const int hi = w4 - 2, lane = l16 >> 4;
        const uint32_t src = sb + C_XSL + l16 + hi * 8;
        const int d0 = 16 * role + 8 * hi + (lane >> 2) - 2 * (lane & 3);
        mbar_wait(bar + B_XS * 8, s & 1);
        float e[10];
        float m = -INFINITY;
#pragma unroll
        for (int i = 0; i < 5; i++) {
            __syncwarp();
            const float2 a = lds2f(src + i * 512), b = lds2f(src + 2560 + i * 512);
            e[2 * i] = (i == 0 || d0 >= 8 * (i - 1)) ? a.x + b.x : -INFINITY;
            e[2 * i + 1] = (i == 0 || d0 > 8 * (i - 1)) ? a.y + b.y : -INFINITY;
            m = fmaxf(m, fmaxf(e[2 * i], e[2 * i + 1]));
        }
        m = fmaxf(m, __shfl_xor_sync(~0u, m, 1));
        m = fmaxf(m, __shfl_xor_sync(~0u, m, 2));
        m *= -SM_SCALE;
        float l = 0.f;
#pragma unroll
        for (int i = 0; i < 10; i++) { e[i] = ex2(fmaf(e[i], SM_SCALE, m)); l += e[i]; }
        l += __shfl_xor_sync(~0u, l, 1);
        l += __shfl_xor_sync(~0u, l, 2);
        l = rcp(l);
        const uint32_t pd = sb_v + C_PL + (s & 1) * 2048 + role * 768 + hi * 128 + (l16 >> 2), pb = sb_v + C_BAR + (B_P0 + (s & 1)) * 8;
        st_async1(pd, pb, pack2(e[0] * l, e[1] * l));
        st_async1(pd + 256, pb, pack2(e[2] * l, e[3] * l));
        st_async1(pd + 512, pb, pack2(e[4] * l, e[5] * l));
        if (role) {
            st_async1(pd + 768, pb, pack2(e[6] * l, e[7] * l));
            st_async1(pd + 1024, pb, pack2(e[8] * l, e[9] * l));
        }
        if (hi == 0 && l16 == 0) mbar_expect(bar + B_XS * 8, 3072 + role * 2048);
        __syncwarp();
    };

    auto windows = [&](auto first_) {
        constexpr bool FIRST = first_.value;
        asm volatile("" : "+r"(l16));
        const uint64_t dd[4] = {FIRST ? DSW : D.sw[0], FIRST ? DSW : D.sw[1], FIRST ? DSW : D.sw[2], FIRST ? DSW : D.sw[3]};
        TS(5);
        if constexpr (WG == 1) {
            TS(6);
            if (ISV && !FIRST) bar_sync(3, 256);
            stream_a(dd[0], dd[1]);
            if (!NOFILL) bar_arrive(7, 256);
            if (!FIRST && !ISV && w4 < 2) {
                const char* src = reinterpret_cast<const char*>(&g_xo[s & 3][0]) + f_src;
                if (__builtin_expect(__any_sync(~0u, missing), 0)) {
                    Stamps st;
                    uint32_t it = 0;
                    do { load_stamps2(st, g_flag[0], l16); spin_guard(it); } while (__any_sync(~0u, stamps_missing<6>(st.v, s)));
                    target = latest_stamp<6>(st.v, lds4u(sb + C_CAL)) + DLY1;
                }
                mbar_wait(bar + B_VF * 8, s & 1);
                TS(10);
                wait_clock(target);
                if (elect()) bulk_ld(f_dst, src, f_bytes, f_bar);
                __syncwarp();
                TS(8);
            }
            if (!NOFILL) {
                wg_wait<0>();
                reg_fence<16>(xk); reg_fence<16>(xv);
                if (w4 == 3) { bar_sync(2, 128); load_tokens(s + 1, 0, 1); }
                else bar_arrive(2, 128);
            }
            TS(7);
        } else {
            if (!NOFILL) {
                mbar_wait(bar + B_XF0 * 8, 0);
                bar_sync(7, 256);
            }
            TS(6);
            stream_a(dd[0], dd[1]);
        }
        Stamps st;
        uint4 cal;
        if constexpr (WG == 0) {
            if constexpr (!FIRST) {
                const uint32_t dst = sb_o + C_OL + rank * 512 + ((l16 & 64) << 2) + ((l16 >> 1) & 192) + (l16 & 48);
                const uint32_t can = sb + C_MB + l16 * 8 + (l16 >> 2), can2 = can + (l16 < (ONK * 2 - 64) * 16 ? 8192 : 0);
                float co[4];
                uint32_t tries = 0;
                TS(7);
                mbar_wait(bar + B_OF * 8, s & 1);
                TS(8);
                auto early = [&]() { return __any_sync(~0u, max(max(lds1u(can), lds1u(can + 4096)), lds1u(can2)) == ~0u); };
                wg8_chain<0, 10, WO_A, MB_A>(co, D.sw[0], D.ns);
                if (__builtin_expect(early(), 0)) {
                    wg_wait<0>();
                    do refetch(sb + C_MB, &g_xo[s & 3][ostart * 16], ONK * 256, bar + B_RT0 * 8, w4, 1, tries); while (early());
                    wg8_chain<0, 10, WO_A, MB_A>(co, DSW, DNS);
                }
                wg_wait<1>();
                bar_arrive(4, 192);
                wg8_chain<10, ONK - OTAIL, WO_A, MB_A>(co, D.sw[0], D.ns);
                static_for<ONK - OTAIL, ONK>([&](auto i) { wg8_ss<1, WO_A + i.value * 128, MB_A + i.value * 16>(co, D.sw[0], D.ns); });
                wg_commit();
                wg_wait<1>();
                bar_arrive(5, 256);
                wg_wait<0>();
                reg_fence<4>(co);
                if (__builtin_expect(st_async4_unless_nan(dst, sb_o + C_BAR + B_OL * 8, co), 0)) {
                    while (incomplete<ONK * 256>(sb + C_MB, l16)) {
                        refetch(sb + C_MB, &g_xo[s & 3][ostart * 16], ONK * 256, bar + B_RT0 * 8, w4, 1, tries);
                        co[0] = co[1] = co[2] = co[3] = 0.f;
#pragma unroll 1
                        for (int i = 0; i < ONK; i++) {
                            wg_fence();
                            wg8_ss<1, WO_A, MB_A>(co, DSW + i * 128, DNS + i * 16);
                            wg_commit();
                            wg_wait<0>();
                        }
                        reg_fence<4>(co);
                    }
                    st_async4(dst, sb_o + C_BAR + B_OL * 8, __float_as_uint(co[0]), __float_as_uint(co[1]), __float_as_uint(co[2]), __float_as_uint(co[3]));
                }
                if (l16 < 32) mbar_arrive_cluster(mapa(bar + B_MBF * 8, 2 * hh + (l16 >> 4)));
                TS(9);
                if (l16 < 48 && w4 == 3) mbar_expect(bar + B_MF0 * 8 + (l16 >> 1), l16 == 32 ? ONK * 256 : 8192);
                if (!ISV && w4 < 2) {
                    const uint32_t off = u_off + (l16 >> 2);
                    const uint32_t src = sb + C_OL + w4 * 8 + ((l16 & 48) << 2) + ((l16 >> 3) & 48) + ((l16 >> 4) & 4);
                    char* gd = reinterpret_cast<char*>(&g_xmem[(s + 1) & 3][0]) + off;
                    st_relaxed1(reinterpret_cast<char*>(&g_xmem[(s + 3) & 3][0]) + off, ~0u);
                    mbar_wait(bar + B_OL * 8, s & 1);
                    float a[6], b[6];
#pragma unroll
                    for (int i = 0; i < 6; i++) { a[i] = __uint_as_float(lds1u(src + i * 512)); b[i] = __uint_as_float(lds1u(src + i * 512 + 256)); }
                    st_relaxed1(gd, pack2((a[0] + a[1]) + (a[2] + a[3]) + (a[4] + a[5]), (b[0] + b[1]) + (b[2] + b[3]) + (b[4] + b[5])));
                    TS(10);
                    if (w4 == 0 && l16 == 0) mbar_expect(bar + B_OL * 8, 3072);
                }
                __syncwarp();
            } else {
                wg_wait<0>();
                bar_arrive(4, 192);
                bar_arrive(5, 256);
                if (l16 < 32) mbar_arrive_cluster(mapa(bar + B_MBF * 8, 2 * hh + (l16 >> 4)));
                mbar_wait(bar + B_WO * 8, 0);
            }
            if (!NOFILL) { reg_fence<16>(xk); reg_fence<16>(xv); }
        } else {
            if (w4 < 2) {
                bar_sync(4, 192);
                const uint32_t dep = lds2u(sb + C_CAL + 8).y;
                const uint32_t v = ((gtick_dep(dep) - (ISV ? (ONKQ - ONKV) * 18 / 64 : 0)) << 6) | s, c = clk();
                if (w4 == 0) {
                    if (!FIRST) {
                        if (l16 == 0) st_relaxed1(&g_flag[1][u_flag + dep], v);
                        if (!ISV) { calibrate(sb + C_CAL, 0.75f); wait_clock(c + DLYS); }
                    }
                } else {
                    if (!FIRST) wait_clock(c + DLYB);
                    load_tokens(s + 1, 0, 0);
                }
            } else if (!ISV && !FIRST && !NOFILL) {
                token_softmax();
                TSX(9, w4 == 2);
            }
            if (!NOFILL) mbar_wait(bar + B_XF1 * 8, 1);
            if (!FIRST && !ISV) { load_stamps1(st.v, g_flag[1], l16, w4 == 0); cal = lds4u(sb + C_CAL); }
            bar_sync(5, 256);
        }
        TS(11);
        auto store_tokens = [&](const float4* r) {
            uint32_t lo[4], hi[4];
#pragma unroll
            for (int j = 0; j < 4; j++) {
                lo[j] = pack2(xk[4 * j] + r[j].x, xk[4 * j + 1] + r[j].y);
                hi[j] = pack2(xk[4 * j + 2] + r[j].z, xk[4 * j + 3] + r[j].w);
            }
            if (!ISV) {
                const uint32_t d = sb + C_QX + WG * 4096 + w4 * 1024 + l16;
                stsm4t(d, lo[0], lo[1], lo[2], lo[3]);
                stsm4t(d + 512, hi[0], hi[1], hi[2], hi[3]);
            } else {
                const uint32_t d = v_row + ((s + 1) & 1) * 10240 + ((l16 & 384) << 4) + ((l16 & 96) << 2) + ((l16 & 112) ^ v_b);
                stsm4(d, lo[0], lo[1], lo[2], lo[3]);
                stsm4(d ^ 32, hi[0], hi[1], hi[2], hi[3]);
            }
        };
        if constexpr (WG == 1) {
            if (!NOFILL) {
                wg_fence();
                products(ic<1>{}, ic<1 - HA>{}, ic<0>{}, ic<0>{}, ic<16>{}, dd[3]);
                wg_commit();
                __syncwarp();
                if (!FIRST && !ISV) load_stamps1(st.v + 3, g_flag[1], l16, w4 == 0);
                __syncwarp();
                products(ic<0>{}, ic<1 - HA>{}, ic<0>{}, ic<0>{}, ic<16>{}, dd[2]);
                wg_commit();
                bar_arrive(7, 256);
                wg_wait<1>();
                reg_fence<16>(xv);
#pragma unroll
                for (int j = 0; j < 4; j++) sts4f(slot + l16 + j * 2048, xv[4 * j], xv[4 * j + 1], xv[4 * j + 2], xv[4 * j + 3]);
                bar_arrive(8, 256);
            }
            if (!NOFILL) {
                wg_wait<0>();
                reg_fence<16>(xk);
                if (w4 != 3) bar_arrive(13, 128);
                else if (!ISV) { bar_sync(13, 128); if (s < NSEG - 2) load_tokens(s + 2, 1, 1); }
            }
            TS(13);
            if (!ISV && w4 == 0) {
                const uint4* src = &g_xmem[(s + 1) & 3][role * 512];
                mbar_wait(bar + B_MBF * 8, (s + 1) & 1);
                if (!FIRST) {
                    if (__builtin_expect(__any_sync(~0u, stamps_missing<3>(st.v, s)), 0)) {
                        uint32_t it = 0;
                        if (!NOFILL) { st.v[0] = st.v[3]; st.v[1] = st.v[4]; st.v[2] = st.v[5]; }
                        while (__any_sync(~0u, stamps_missing<3>(st.v, s))) { load_stamps1(st.v, g_flag[1], l16); spin_guard(it); }
                    }
                    target = latest_stamp<3>(st.v, cal) + DLY2;
                    TS(3);
                    wait_clock(target);
                }
                if (elect()) {
                    if (hh) bulk_mc(m_dst, src, 8192, m_bar, 0x2C);
                    else bulk_mc(m_dst, src, 8192, m_bar, 0x13);
                }
                __syncwarp();
                TS(4);
            }
            prefetch();
            if (!NOFILL) {
                bar_sync(9, 256);
                float4 r[4];
#pragma unroll
                for (int j = 0; j < 4; j++) r[j] = lds4f(slot + l16 + j * 2048);
                store_tokens(r);
                bar_arrive(10, 256);
                if (ISV && w4 == 3) bar_sync(13, 128);
            }
        } else {
            if (!NOFILL) {
                mbar_wait(bar + B_XF0 * 8, 1);
                bar_sync(7, 256);
                TS(12);
                wg_fence();
                products(ic<1>{}, ic<1 - HA>{}, ic<0>{}, ic<0>{}, ic<16>{}, dd[3]);
                wg_commit();
                products(ic<0>{}, ic<1 - HA>{}, ic<0>{}, ic<0>{}, ic<6>{}, dd[2]);
                wg_commit();
                bar_sync(8, 256);
                float4 r[4];
#pragma unroll
                for (int j = 0; j < 4; j++) r[j] = lds4f(slot + l16 + j * 2048);
                wg_wait<1>();
                reg_fence<16>(xv);
#pragma unroll
                for (int j = 0; j < 4; j++) sts4f(slot + l16 + j * 2048, xv[4 * j], xv[4 * j + 1], xv[4 * j + 2], xv[4 * j + 3]);
                bar_arrive(9, 256);
                products(ic<0>{}, ic<1 - HA>{}, ic<0>{}, ic<6>{}, ic<16>{}, dd[2]);
                wg_commit();
                wg_wait<0>();
                reg_fence<16>(xk);
                TS(13);
                prefetch();
                store_tokens(r);
            } else {
                prefetch();
            }
        }
    };

    if (w4 == 0) load_tokens(0, 1, WG);
    mbar_wait(bar + B_WS * 8, 0);
    if (WG == 1 && !NOFILL) mbar_wait(bar + B_XF1 * 8, 0);
    windows(ic<1>{});

#pragma unroll 1
    while (true) {
        s++;
        asm volatile("" : "+r"(l16), "+r"(a_adr));
        TS_FLUSH(WG);
        TS(0);
        float ck[4], cv[4];
        uint32_t k0[2][4], k1[2][4];
        Stamps st1;
        const uint32_t kl = sb + C_KX + ((l16 & 384) << 2) + (l16 & 112);
        {
            const uint32_t can = mbw + l16 * 8 + (l16 >> 2);
            uint32_t tries = 0;
            bool synced = false;
            for (;; tries |= 1) {
                asm volatile("" : "+r"(tries));
                if (__builtin_expect(tries, 0)) {
                    if (__any_sync(~0u, max(lds1u(can), lds1u(can + 4096)) == ~0u) || incomplete<8192>(mbw, l16))
                        refetch(mbw, &g_xmem[s & 3][WG * 512], 8192, bar + (B_RT0 + WG) * 8, w4, 1 + WG, tries);
                    else tries = ~0u;
                    prefetch();
                }
                mbar_wait(bar + (B_MF0 + WG) * 8, s & 1);
                TS(1);
                uint32_t b[2][4];
                float dk[4], dv[4];
                ldsm4(b[0], mbw + l16 + 12 * 512);
#pragma unroll
                for (int i = 0; i < 4; i++) ck[i] = cv[i] = dk[i] = dv[i] = 0.f;
                auto kpair = [&](auto kp_) {
                    constexpr int kp = kp_.value, grp = kp / 5, ph = kp % 5, nx = kp + 1;
                    if constexpr (nx < 16) ldsm4(b[nx & 1], mbw + l16 + ((nx % 5) ? (nx / 5) * 4 + (nx % 5) - 1 : 12 + nx / 5) * 512);
                    const uint32_t* bb = b[kp & 1];
                    if constexpr (ph != 0) {
                        constexpr int q = (grp * 4 + ph - 1) * 2, i = ph - 1;
                        ldsm4t(pf[i], a_adr + C_WS + (i & 1) * 16384 + (grp * 2 + 2 + (i >> 1)) * 2048);
                        __syncwarp();
                        mma16(cv, wv[q][0], wv[q][1], wv[q][2], wv[q][3], bb[0], bb[1]);
                        mma16(ck, wk[q][0], wk[q][1], wk[q][2], wk[q][3], bb[0], bb[1]);
                        mma16(dv, wv[q + 1][0], wv[q + 1][1], wv[q + 1][2], wv[q + 1][3], bb[2], bb[3]);
                        mma16(dk, wk[q + 1][0], wk[q + 1][1], wk[q + 1][2], wk[q + 1][3], bb[2], bb[3]);
                    } else {
                        mma16(cv, pf[1][0], pf[1][1], pf[1][2], pf[1][3], bb[0], bb[1]);
                        mma16(dv, pf[3][0], pf[3][1], pf[3][2], pf[3][3], bb[2], bb[3]);
                        mma16(ck, pf[0][0], pf[0][1], pf[0][2], pf[0][3], bb[0], bb[1]);
                        mma16(dk, pf[2][0], pf[2][1], pf[2][2], pf[2][3], bb[2], bb[3]);
                    }
                };
                kpair(ic<0>{});
                const uint32_t c0 = lds1u(can), c1 = lds1u(can + 4096);
                kpair(ic<1>{});
                if (__builtin_expect(__any_sync(~0u, max(c0, c1) == ~0u), 0)) continue;
                st_pred1(&g_flag[0][u_flag + WG + l16], ((gtick() - (ISV ? VLEAD : 0)) << 6) | s, w4 * 512 + l16 == 1536);
                if (WG == 0 && !NOFILL && !synced) bar_sync(10, 256);
                synced = true;
                static_for<2, STPOS>(kpair);
                if (!ISV && WG == 1) load_stamps2(st1, g_flag[0], l16, w4 < 2);
                static_for<STPOS, 16>(kpair);
#pragma unroll
                for (int i = 0; i < 4; i++) cv[i] += dv[i];
                sts4f(slot + WG * 2048 + l16, cv[0], cv[1], cv[2], cv[3]);
#pragma unroll
                for (int i = 0; i < 4; i++) ck[i] += dk[i];
                TS(2);
                if (__builtin_expect(!any_nan_unless(cv[0], cv[1], tries), 1)) break;
            }
            if (!ISV && WG == 0) {
                const uint32_t ka = kl + (w4 == 1 ? 256 : 0);
                ldsm4(k0[0], ka); ldsm4(k0[1], ka + 2048);
                ldsm4(k1[0], ka + 128); ldsm4(k1[1], ka + 128 + 2048);
            }
            if (ISV && WG == 1 && w4 == 3 && s < NSEG - 1) load_tokens(s + 1, 1, 1);
            bar_sync(6, 256);
        }
        if constexpr (!ISV) {
            const uint32_t lane_b = sb + C_QM + ((l16 >> 1) & 128) + ((l16 & 128) << 2) + (l16 & 112);
            const uint32_t qx = sb + C_QX + WG * 256 + l16 + (l16 & 256);
            const uint32_t xd = sb_x + C_XSL + role * 2560 + l16, xb = sb_x + C_BAR + B_XS * 8;
            {
                const float4 r = lds4f(slot + (WG ^ 1) * 2048 + l16);
                stsm2t(sb + C_QM + WG * 1024 + w4 * 256 + (l16 & 255), pack2(ck[0] + r.x, ck[1] + r.y), pack2(ck[2] + r.z, ck[3] + r.w));
            }
            auto tile = [&](float* d, const uint32_t (*q)[4], const uint32_t (*k)[4]) {
                d[0] = d[1] = d[2] = d[3] = 0.f;
#pragma unroll
                for (int i = 0; i < 4; i++) mma16(d, q[i][0], q[i][1], q[i][2], q[i][3], k[i >> 1][(i & 1) * 2], k[i >> 1][(i & 1) * 2 + 1]);
            };
            auto send = [&](int ti, const float* d) {
                st_async4(xd + ti * 512, xb, __float_as_uint(d[0]), __float_as_uint(d[1]), __float_as_uint(d[2]), __float_as_uint(d[3]));
            };
            if constexpr (WG == 0) {
                if (w4 < 2) {
                    uint32_t q0[4], q1[4];
                    const uint32_t dst = sb_v + C_SL + role * 1280 + w4 * 512 + l16;
                    bar_sync(6, 256);
                    TS(3);
                    ldsm4(q0, lane_b); ldsm4(q1, lane_b + 256);
                    float s0[4] = {0.f, 0.f, 0.f, 0.f}, s1[4] = {0.f, 0.f, 0.f, 0.f}, s2[4] = {0.f, 0.f, 0.f, 0.f}, s3[4] = {0.f, 0.f, 0.f, 0.f};
                    mma16(s0, q0[0], q0[1], q0[2], q0[3], k0[0][0], k0[0][1]);
                    mma16(s1, q0[0], q0[1], q0[2], q0[3], k0[1][0], k0[1][1]);
                    mma16(s2, q0[0], q0[1], q0[2], q0[3], k1[0][0], k1[0][1]);
                    mma16(s3, q0[0], q0[1], q0[2], q0[3], k1[1][0], k1[1][1]);
                    mma16(s0, q1[0], q1[1], q1[2], q1[3], k0[0][2], k0[0][3]);
                    mma16(s1, q1[0], q1[1], q1[2], q1[3], k0[1][2], k0[1][3]);
                    mma16(s2, q1[0], q1[1], q1[2], q1[3], k1[0][2], k1[0][3]);
                    mma16(s3, q1[0], q1[1], q1[2], q1[3], k1[1][2], k1[1][3]);
                    st_async4(dst, sb_v + C_BAR + B_SC * 8, __float_as_uint(s0[0] + s1[2]), __float_as_uint(s0[1] + s1[3]),
                              __float_as_uint(s2[0] + s3[2]), __float_as_uint(s2[1] + s3[3]));
                    bar_arrive(12, 256);
                    TS(4);
                } else if (w4 == 2) {
                    uint32_t q0[4], q1[4], m0[4], m1[4];
                    const uint32_t dst = sb_v + C_SL + role * 1280 + 1024 + (l16 >> 1);
                    bar_sync(6, 256);
                    ldsm4(q0, lane_b); ldsm4(m0, sb + C_KM + l16); ldsm4(m1, sb + C_KM + 512 + l16); ldsm4(q1, lane_b + 256);
                    float s0[4] = {0.f, 0.f, 0.f, 0.f}, s1[4] = {0.f, 0.f, 0.f, 0.f};
                    mma16(s0, q0[0], q0[1], q0[2], q0[3], m0[0], m0[1]);
                    mma16(s1, q0[0], q0[1], q0[2], q0[3], m1[0], m1[1]);
                    mma16(s0, q1[0], q1[1], q1[2], q1[3], m0[2], m0[3]);
                    mma16(s1, q1[0], q1[1], q1[2], q1[3], m1[2], m1[3]);
                    st_async2(dst, sb_v + C_BAR + B_SC * 8, __float_as_uint(s0[0] + s1[2]), __float_as_uint(s0[1] + s1[3]));
                    bar_arrive(12, 256);
                } else {
                    bar_sync(6, 256);
                    if (s < NSEG - 1) load_tokens(s + 1, 1, 0);
                    if (!NOFILL) {
                        uint32_t q[4][4], km[2][4];
                        float d0[4], d1[4], d2[4];
#pragma unroll
                        for (int i = 0; i < 4; i++) ldsm4(q[i], qx + i * 1024);
                        ldsm4(km[0], sb + C_KM + l16); ldsm4(km[1], sb + C_KM + 512 + l16);
                        tile(d1, q, k0); tile(d2, q, k1); tile(d0, q, km);
                        reg_fence<4>(d0);
                        bar_sync(12, 256);
                        send(0, d0); send(1, d1); send(2, d2);
                    } else {
                        bar_sync(12, 256);
                    }
                }
                if (__builtin_expect(s == NSEG - 1, 0)) break;
            } else {
                bar_sync(6, 256);
                if (!NOFILL) mbar_wait(bar + B_XF1 * 8, s == NSEG - 1);
                missing = stamps_missing<6>(st1.v, s);
                target = latest_stamp<6>(st1.v, lds4u(sb + C_CAL)) + DLY1;
                if (!NOFILL) {
                    uint32_t q[4][4];
                    float d0[4], d1[4];
#pragma unroll
                    for (int i = 0; i < 4; i++) ldsm4(q[i], qx + i * 1024);
                    ldsm4(k0[0], kl + w4 * 128); ldsm4(k0[1], kl + w4 * 128 + 2048);
                    ldsm4(k1[0], sb + C_KM + l16); ldsm4(k1[1], sb + C_KM + 512 + l16);
                    tile(d1, q, k0); tile(d0, q, k1);
                    bar_sync(12, 256);
                    send(1 + w4, d1);
                    if (w4 == 0) send(0, d0);
                } else {
                    bar_sync(12, 256);
                }
                if (__builtin_expect(s == NSEG - 1, 0)) {
                    asm volatile("" : "+r"(l16));
                    if (w4 >= 2 && !NOFILL) token_softmax();
                    break;
                }
            }
        } else {
            const uint32_t lane_b = sb + C_V + w4 * 512 + ((l16 & 384) << 4) + (l16 & 112);
            auto load_values = [&](uint32_t (*vx)[4], uint32_t* vm, int ss) {
#pragma unroll
                for (int j = 0; j < 4; j++) ldsm4(vx[j], ((lane_b + (ss & 1) * 10240) ^ (j * 32)) + j * 128);
                ldsm4(vm, sb + C_V + (ss & 1) * 10240 + w4 * 512 + 8192 + (l16 ^ ((l16 >> 2) & 96)));
            };
            auto token_output = [&](int ss, bool live, auto mid) {
                uint32_t vx[4][4], vm[4];
                const uint32_t pl = sb + C_PL + (ss & 1) * 2048 + (l16 >> 2);
                auto lds_frag = [&](uint32_t a) { return make_uint4(lds1u(a), lds1u(a + 128), lds1u(a + 256), lds1u(a + 384)); };
                load_values(vx, vm, ss);
                mid();
                char* orow = reinterpret_cast<char*>(g_ox) + (ss * (32 * HD * 2) + (u_off >> 3) + (l16 >> 6) * (HD * 2) + (l16 & 48));
#pragma unroll
                for (int mh = 1; mh >= 0; mh--) {
                    __syncwarp();
                    const uint2 pm = make_uint2(lds1u(pl + mh * 768), lds1u(pl + mh * 768 + 128));
                    const uint4 p0 = lds_frag(pl + mh * 768 + 256);
                    float o[4][4];
#pragma unroll
                    for (int j = 0; j < 4; j++) { o[j][0] = o[j][1] = o[j][2] = o[j][3] = 0.f; mma8(o[j], pm.x, pm.y, vm[j]); }
#pragma unroll
                    for (int j = 0; j < 4; j++) mma16(o[j], p0.x, p0.y, p0.z, p0.w, vx[j][0], vx[j][1]);
                    if (mh) {
                        const uint4 p1 = lds_frag(pl + 1536);
#pragma unroll
                        for (int j = 0; j < 4; j++) mma16(o[j], p1.x, p1.y, p1.z, p1.w, vx[j][2], vx[j][3]);
                    }
                    st_pred4(orow + mh * (16 * HD * 2),
                             make_uint4(pack2(o[0][0], o[0][1]), pack2(o[1][0], o[1][1]), pack2(o[2][0], o[2][1]), pack2(o[3][0], o[3][1])), live);
                    st_pred4(orow + mh * (16 * HD * 2) + 8 * HD * 2,
                             make_uint4(pack2(o[0][2], o[0][3]), pack2(o[1][2], o[1][3]), pack2(o[2][2], o[2][3]), pack2(o[3][2], o[3][3])), live);
                }
            };
            const uint32_t vd = v_row + (s & 1) * 10240 + 8192 + ((l16 & 96) << 2) + ((l16 & 112) ^ v_b ^ ((l16 & 128) >> 2));
            const float4 r = lds4f(slot + (WG ^ 1) * 2048 + l16);
            __syncwarp();
            auto finish = [&]() {
                stsm2(vd, pack2(ck[0] + r.x, ck[1] + r.y), pack2(ck[2] + r.z, ck[3] + r.w));
                if (WG == 1) {
                    bar_arrive(11, 256);
                    if (w4 == 3 && l16 < 32) mbar_arrive_cluster(mapa(bar + B_VF * 8, 2 * hh + (l16 >> 4)));
                }
                TSX(3, WG == 0 && w4 == 0);
            };
            if (!NOFILL && WG == 1) {
                token_output(s - 1, s > 0, [&]() { finish(); mbar_wait(bar + (B_P0 + ((s - 1) & 1)) * 8, ((s - 1) >> 1) & 1); });
                if (w4 == 1 && l16 == 0 && s > 0) mbar_expect(bar + (B_P0 + ((s - 1) & 1)) * 8, 2048);
                mbar_wait(bar + B_XF1 * 8, s == NSEG - 1);
            } else {
                finish();
            }
            if (WG == 0) bar_sync(11, 256);
            if (__builtin_expect(s == NSEG - 1, 0)) {
                bar_sync(6, 256);
                if (!NOFILL && WG == 1) token_output(s, true, [&]() { mbar_wait(bar + (B_P0 + (s & 1)) * 8, (s >> 1) & 1); });
                mbar_wait(bar + B_SC * 8, s & 1);
                break;
            }
            if constexpr (WG == 0) {
                uint32_t vx[4][4], vm[4];
                load_values(vx, vm, s);
                const uint32_t oo = u_off + ((l16 & 48) << 3) + ((l16 >> 2) & 112);
                char* dst = reinterpret_cast<char*>(&g_xo[s & 3][0]) + oo;
                if (w4 == 3) load_tokens(s + 1, 1, 0);
                mbar_wait(bar + B_SC * 8, s & 1);
                TS(4);
                const float4 a0 = lds4f(sb + C_SL + l16), b0 = lds4f(sb + C_SL + 1280 + l16);
                const float4 a1 = lds4f(sb + C_SL + 512 + l16), b1 = lds4f(sb + C_SL + 1280 + 512 + l16);
                const float2 a2 = lds2f(sb + C_SL + 1024 + (l16 >> 1)), b2 = lds2f(sb + C_SL + 1280 + 1024 + (l16 >> 1));
                const float e[10] = {a0.x + b0.x, a0.y + b0.y, a0.z + b0.z, a0.w + b0.w, a1.x + b1.x, a1.y + b1.y, a1.z + b1.z, a1.w + b1.w,
                                     a2.x + b2.x, a2.y + b2.y};
                float m = fmaxf(fmaxf(fmaxf(e[0], e[1]), fmaxf(e[2], e[3])), fmaxf(fmaxf(e[4], e[5]), fmaxf(e[6], e[7])));
                m = fmaxf(m, fmaxf(e[8], e[9]));
                m = fmaxf(fmaxf(m, __shfl_xor_sync(~0u, m, 1)), fmaxf(__shfl_xor_sync(~0u, m, 2), __shfl_xor_sync(~0u, m, 3)));
                m *= -SM_SCALE;
                float x[10];
#pragma unroll
                for (int i = 0; i < 10; i++) x[i] = ex2(fmaf(e[i], SM_SCALE, m));
                float o[4][4];
                const uint32_t p0 = pack2(x[0], x[1]), p1 = pack2(x[2], x[3]), j0 = __float_as_uint(x[1]), j1 = __float_as_uint(x[3]);
#pragma unroll
                for (int j = 0; j < 4; j++) { o[j][0] = o[j][1] = o[j][2] = o[j][3] = 0.f; mma16(o[j], p0, j0, p1, j1, vx[j][0], vx[j][1]); }
                const uint32_t p2 = pack2(x[4], x[5]), p3 = pack2(x[6], x[7]), j2 = __float_as_uint(x[5]), j3 = __float_as_uint(x[7]);
#pragma unroll
                for (int j = 0; j < 4; j++) mma16(o[j], p2, j2, p3, j3, vx[j][2], vx[j][3]);
                const uint32_t p4 = pack2(x[8], x[9]), j4 = __float_as_uint(x[9]);
                float l = (((x[0] + x[1]) + (x[2] + x[3])) + ((x[4] + x[5]) + (x[6] + x[7]))) + (x[8] + x[9]);
                l = (l + __shfl_xor_sync(~0u, l, 1)) + (__shfl_xor_sync(~0u, l, 2) + __shfl_xor_sync(~0u, l, 3));
#pragma unroll
                for (int j = 0; j < 4; j++) mma8(o[j], p4, j4, vm[j]);
                l = rcp(l);
                st_relaxed4(reinterpret_cast<uint4*>(dst), make_uint4(pack2(o[0][0] * l, o[0][1] * l), pack2(o[1][0] * l, o[1][1] * l),
                                                                      pack2(o[2][0] * l, o[2][1] * l), pack2(o[3][0] * l, o[3][1] * l)));
                bar_arrive(3, 256);
                st_relaxed4(reinterpret_cast<uint4*>(reinterpret_cast<char*>(&g_xo[(s + 2) & 3][0]) + oo), make_uint4(~0u, ~0u, ~0u, ~0u));
                if (w4 == 0 && l16 == 0) mbar_expect(bar + B_SC * 8, 2560);
            }
        }
        windows(ic<0>{});
    }
}

__global__ void __cluster_dims__(6, 1, 1) __launch_bounds__(256, 1)
chain_kernel(const __grid_constant__ CUtensorMap tq, const __grid_constant__ CUtensorMap tk, const __grid_constant__ CUtensorMap tv,
             const __grid_constant__ CUtensorMap two, const __grid_constant__ Descs D, const __grid_constant__ Descs DV) {
    extern __shared__ __align__(1024) uint8_t smem[];
    const uint32_t sb = smem_u32(smem);
    const int rank = blockIdx.x % 6, cl = blockIdx.x / 6, role = rank >= 4 ? 2 : rank & 1;
    if (threadIdx.x == 0) {
        if ((sb & 0x3FFFF) != SB0) __trap();
        const uint32_t bar = sb + C_BAR;
        for (int i = 0; i < B_NUM; i++) mbar_init(bar + i * 8, i == B_MBF ? 12 : 1);
        mbar_expect(bar + B_MF0 * 8, 8192);
        mbar_expect(bar + B_MF1 * 8, 8192);
        if (role == 2) {
            mbar_expect(bar + B_SC * 8, 2560);
            mbar_expect(bar + B_P0 * 8, 2048);
            mbar_expect(bar + B_P1 * 8, 2048);
            mbar_expect(bar + B_OF * 8, ONKV * 256);
        } else {
            mbar_expect(bar + B_XS * 8, role ? 5120 : 3072);
            mbar_expect(bar + B_OL * 8, 3072);
            mbar_expect(bar + B_OF * 8, ONKQ * 256);
        }
        asm volatile("fence.mbarrier_init.release.cluster;" ::: "memory");
        fence_async();
    }
    __syncthreads();
    cluster_sync();
    const int wg = uni(threadIdx.x >> 7);
    if (role == 2) {
        if (wg == 0) chain_main<true, 0>(&tv, &tv, &two, sb, cl, rank, DV);
        else chain_main<true, 1>(&tv, &tv, &two, sb, cl, rank, DV);
    } else {
        if (wg == 0) chain_main<false, 0>(&tq, &tk, &two, sb, cl, rank, D);
        else chain_main<false, 1>(&tq, &tk, &two, sb, cl, rank, D);
    }
    __syncwarp();
    cluster_sync();
}

constexpr int G_STAGES = 4;
constexpr uint32_t G_STAGE = 49152, G_EPI = G_STAGES * G_STAGE, G_BAR = G_EPI + 32768, G_SMEM = G_BAR + 256;

__device__ __forceinline__ void wg256(float* d, uint32_t da, uint32_t db, uint32_t accum) {
    asm volatile("{\n.reg .b64 da, db;\n.reg .pred p;\nsetp.ne.u32 p, %130, 0;\nmov.b64 da, {%128, " DESC_HI_SW128 "};\nmov.b64 db, {%129, " DESC_HI_SW128 "};\n"
                 "wgmma.mma_async.sync.aligned.m64n256k16.f32.bf16.bf16 {"
                 "%0,%1,%2,%3,%4,%5,%6,%7,%8,%9,%10,%11,%12,%13,%14,%15,%16,%17,%18,%19,%20,%21,%22,%23,%24,%25,%26,%27,%28,%29,%30,%31,"
                 "%32,%33,%34,%35,%36,%37,%38,%39,%40,%41,%42,%43,%44,%45,%46,%47,%48,%49,%50,%51,%52,%53,%54,%55,%56,%57,%58,%59,%60,%61,%62,%63,"
                 "%64,%65,%66,%67,%68,%69,%70,%71,%72,%73,%74,%75,%76,%77,%78,%79,%80,%81,%82,%83,%84,%85,%86,%87,%88,%89,%90,%91,%92,%93,%94,%95,"
                 "%96,%97,%98,%99,%100,%101,%102,%103,%104,%105,%106,%107,%108,%109,%110,%111,%112,%113,%114,%115,%116,%117,%118,%119,%120,%121,%122,%123,%124,%125,%126,%127"
                 "}, da, db, p, 1, 1, 0, 1;\n}"
                 : ACC16(d), ACC16((d + 16)), ACC16((d + 32)), ACC16((d + 48)), ACC16((d + 64)), ACC16((d + 80)), ACC16((d + 96)), ACC16((d + 112))
                 : "r"(da), "r"(db), "r"(accum));
}
__device__ __forceinline__ float sigmoidf_(float v) { return rcp(1.f + ex2(-1.4426950408889634f * v)); }

template <int MODE>
__global__ void __cluster_dims__(2, 1, 1) __launch_bounds__(384, 1)
gemm_kernel(const __grid_constant__ CUtensorMap tA, const __grid_constant__ CUtensorMap tB0, const __grid_constant__ CUtensorMap tB1,
            const __grid_constant__ CUtensorMap tOut, const __grid_constant__ CUtensorMap tX, const __grid_constant__ CUtensorMap tY) {
    constexpr int KB = MODE == 0 ? DM / 64 : (MODE == 1 ? FF / 64 : HD / 64);
    constexpr int NT = MODE == 0 ? FF / 128 : DM / 256;
    constexpr int NTILES = NT * 8;
    extern __shared__ __align__(1024) uint8_t smem[];
    const uint32_t sb = smem_u32(smem);
    const uint32_t full = sb + G_BAR, empty = full + 64;
    const int tid = threadIdx.x, lane = tid & 31;
    const int wg = __shfl_sync(~0u, tid >> 7, 0);
    const int rank = blockIdx.x & 1, pair = blockIdx.x >> 1, npair = gridDim.x >> 1;
    if (tid == 0) {
        for (int i = 0; i < G_STAGES; i++) { mbar_init(full + i * 8, 1); mbar_init(empty + i * 8, 16); }
        asm volatile("fence.mbarrier_init.release.cluster;" ::: "memory");
        fence_async();
    }
    __syncthreads();
    cluster_sync();
    if (wg == 0) {
        asm volatile("setmaxnreg.dec.sync.aligned.u32 40;");
        if (tid == 0) {
            uint32_t st = 0, ph = 1;
            for (int tile = pair; tile < NTILES; tile += npair) {
                const int mp = tile & 7, nt = tile >> 3, row0 = (mp * 2 + rank) * 128;
                const CUtensorMap* tB = (MODE == 0 && rank) ? &tB1 : &tB0;
                const int bcol = MODE == 0 ? nt * 128 : nt * 256 + rank * 128;
                for (int kb = 0; kb < KB; kb++) {
                    mbar_wait(empty + st * 8, ph);
                    const uint32_t base = sb + st * G_STAGE;
                    mbar_expect(full + st * 8, G_STAGE);
                    tma2d(base, &tA, kb * 64, row0, full + st * 8);
                    tma2d_mc(base + 16384 + rank * 16384, tB, bcol, kb * 64, full + st * 8, 3);
                    tma2d_mc(base + 16384 + rank * 16384 + 8192, tB, bcol + 64, kb * 64, full + st * 8, 3);
                    if (++st == G_STAGES) { st = 0; ph ^= 1; }
                }
                if (MODE == 2) {
                    for (int q = 0; q < 4; q++) {
                        mbar_wait(empty + st * 8, ph);
                        const uint32_t base = sb + st * G_STAGE;
                        mbar_expect(full + st * 8, 32768);
                        tma2d(base, &tX, nt * 256 + q * 64, row0, full + st * 8);
                        tma2d(base + 16384, &tY, nt * 256 + q * 64, row0, full + st * 8);
                        if (++st == G_STAGES) { st = 0; ph ^= 1; }
                    }
                }
            }
        }
        __syncwarp();
        cluster_sync();
    } else {
        asm volatile("setmaxnreg.inc.sync.aligned.u32 232;");
        const int cw = wg - 1, w4 = (tid >> 5) & 3;
        const uint32_t empty_dst = mapa(empty, lane & 1);
        const uint32_t epi = sb + G_EPI + cw * 16384;
        const int er = w4 * 16 + (lane & 15), ec = lane >> 4;
        uint32_t st = 0, ph = 0;
        float acc[128];
        for (int tile = pair; tile < NTILES; tile += npair) {
            const int mp = tile & 7, nt = tile >> 3, row0 = (mp * 2 + rank) * 128 + cw * 64;
            uint32_t prev = 0;
#pragma unroll 1
            for (int kb = 0; kb < KB; kb++) {
                mbar_wait(full + st * 8, ph);
                const uint32_t base = sb + st * G_STAGE;
                const uint32_t da = (((base + cw * 8192) & 0x3FFFF) >> 4) | (1u << 16);
                const uint32_t db = (((base + 16384) & 0x3FFFF) >> 4) | (512u << 16);
                wg_fence();
#pragma unroll
                for (int k = 0; k < 4; k++) wg256(acc, da + k * 2, db + k * 128, (kb | k) != 0);
                wg_commit();
                if (kb > 0) {
                    wg_wait<1>();
                    if (lane < 2) mbar_arrive_cluster(empty_dst + prev * 8);
                }
                prev = st;
                if (++st == G_STAGES) { st = 0; ph ^= 1; }
            }
            wg_wait<0>();
            reg_fence<128>(acc);
            if (lane < 2) mbar_arrive_cluster(empty_dst + prev * 8);
#pragma unroll
            for (int hp = 0; hp < (MODE == 0 ? 1 : 2); hp++) {
                uint32_t o[32];
#pragma unroll
                for (int bx = 0; bx < 2; bx++) {
                    uint32_t xa = 0;
                    if (MODE == 2) {
                        mbar_wait(full + st * 8, ph);
                        xa = sb + st * G_STAGE + (cw * 64 + er) * 128;
                    }
#pragma unroll
                    for (int j = 0; j < 4; j++) {
                        const int a0 = hp * 64 + bx * 32 + j * 8;
                        uint32_t* oo = o + bx * 16 + j * 4;
                        if (MODE == 0) {
#pragma unroll
                            for (int i = 0; i < 4; i++)
                                oo[i] = pack2(sigmoidf_(acc[a0 + 2 * i]) * acc[64 + a0 + 2 * i], sigmoidf_(acc[a0 + 2 * i + 1]) * acc[64 + a0 + 2 * i + 1]);
                        } else if (MODE == 1) {
#pragma unroll
                            for (int i = 0; i < 4; i++)
                                oo[i] = pack2(sigmoidf_(acc[a0 + 2 * i]) * acc[a0 + 2 * i], sigmoidf_(acc[a0 + 2 * i + 1]) * acc[a0 + 2 * i + 1]);
                        } else {
                            uint32_t xv[4], yv[4];
                            const uint32_t ad = xa + (((2 * j + ec) ^ (er & 7)) << 4);
                            ldsm4(xv, ad); ldsm4(yv, ad + 16384);
#pragma unroll
                            for (int i = 0; i < 4; i++)
                                oo[i] = pack2(fmaf(acc[a0 + 2 * i], bf_lo(yv[i]), bf_lo(xv[i])), fmaf(acc[a0 + 2 * i + 1], bf_hi(yv[i]), bf_hi(xv[i])));
                        }
                    }
                    if (MODE == 2) {
                        __syncwarp();
                        if (lane < 2) mbar_arrive_cluster(empty_dst + st * 8);
                        if (++st == G_STAGES) { st = 0; ph ^= 1; }
                    }
                }
                if ((tid & 127) == 0) asm volatile("cp.async.bulk.wait_group.read 0;" ::: "memory");
                bar_sync(1 + cw, 128);
#pragma unroll
                for (int bx = 0; bx < 2; bx++)
#pragma unroll
                    for (int j = 0; j < 4; j++) {
                        const uint32_t* oo = o + bx * 16 + j * 4;
                        stsm4(epi + bx * 8192 + er * 128 + (((2 * j + ec) ^ (er & 7)) << 4), oo[0], oo[1], oo[2], oo[3]);
                    }
                fence_async();
                bar_sync(1 + cw, 128);
                if ((tid & 127) == 0) {
                    const int col = MODE == 0 ? nt * 128 : nt * 256 + hp * 128;
                    tma2d_store(&tOut, col, row0, epi);
                    tma2d_store(&tOut, col + 64, row0, epi + 8192);
                    asm volatile("cp.async.bulk.commit_group;" ::: "memory");
                }
            }
        }
        if ((tid & 127) == 0) asm volatile("cp.async.bulk.wait_group 0;" ::: "memory");
        __syncwarp();
        cluster_sync();
    }
}

typedef CUresult (*EncodeFn)(CUtensorMap*, CUtensorMapDataType, cuuint32_t, void*, const cuuint64_t*, const cuuint64_t*, const cuuint32_t*,
                             const cuuint32_t*, CUtensorMapInterleave, CUtensorMapSwizzle, CUtensorMapL2promotion, CUtensorMapFloatOOBfill);

CUtensorMap make_map(EncodeFn enc, const void* p, int rows, int cols, int box_rows) {
    CUtensorMap m;
    cuuint64_t dims[2] = {(cuuint64_t)cols, (cuuint64_t)rows}, strides[1] = {(cuuint64_t)cols * 2};
    cuuint32_t box[2] = {64, (cuuint32_t)box_rows}, es[2] = {1, 1};
    enc(&m, CU_TENSOR_MAP_DATA_TYPE_BFLOAT16, 2, const_cast<void*>(p), dims, strides, box, es, CU_TENSOR_MAP_INTERLEAVE_NONE,
        CU_TENSOR_MAP_SWIZZLE_128B, CU_TENSOR_MAP_L2_PROMOTION_L2_128B, CU_TENSOR_MAP_FLOAT_OOB_FILL_NONE);
    return m;
}

}

extern "C" void kernel_launch(void* const* d_in, const int* in_sizes, int n_in, void* d_out, int out_size) {
    const __nv_bfloat16* x = (const __nv_bfloat16*)d_in[0];
    const __nv_bfloat16* mem0 = (const __nv_bfloat16*)d_in[1];
    void* fn = nullptr;
    cudaDriverEntryPointQueryResult qr;
    cudaGetDriverEntryPoint("cuTensorMapEncodeTiled", &fn, cudaEnableDefault, &qr);
    EncodeFn enc = (EncodeFn)fn;
    void *xn, *ox, *h, *y;
    cudaGetSymbolAddress(&xn, g_xn); cudaGetSymbolAddress(&ox, g_ox); cudaGetSymbolAddress(&h, g_h); cudaGetSymbolAddress(&y, g_y);

    const CUtensorMap tq = make_map(enc, d_in[2], DM, HD, 128), tk = make_map(enc, d_in[3], DM, HD, 128), tv = make_map(enc, d_in[4], DM, HD, 128);
    const CUtensorMap two16 = make_map(enc, d_in[5], HD, DM, 16);
    const CUtensorMap txn128 = make_map(enc, xn, SEQ, DM, 128), tg = make_map(enc, d_in[8], DM, FF, 64), tu = make_map(enc, d_in[9], DM, FF, 64);
    const CUtensorMap th64 = make_map(enc, h, SEQ, FF, 64), th128 = make_map(enc, h, SEQ, FF, 128), td = make_map(enc, d_in[10], FF, DM, 64);
    const CUtensorMap ty64 = make_map(enc, y, SEQ, DM, 64), ty128 = make_map(enc, y, SEQ, DM, 128), tx128 = make_map(enc, x, SEQ, DM, 128);
    const CUtensorMap tox = make_map(enc, ox, SEQ, HD, 128), two64 = make_map(enc, d_in[5], HD, DM, 64), tout = make_map(enc, d_out, SEQ, DM, 64);

    cudaFuncSetAttribute(chain_kernel, cudaFuncAttributeMaxDynamicSharedMemorySize, C_SMEM);
    cudaFuncSetAttribute(gemm_kernel<0>, cudaFuncAttributeMaxDynamicSharedMemorySize, G_SMEM);
    cudaFuncSetAttribute(gemm_kernel<1>, cudaFuncAttributeMaxDynamicSharedMemorySize, G_SMEM);
    cudaFuncSetAttribute(gemm_kernel<2>, cudaFuncAttributeMaxDynamicSharedMemorySize, G_SMEM);

    cudaStream_t st = cudaStreamPerThread;
    ln_kernel<<<SEQ / 8, 256, 0, st>>>(x, mem0);
    Descs D;
    for (int i = 0; i < 4; i++) D.sw[i] = DSW;
    D.ns = DNS;
    chain_kernel<<<96, 256, C_SMEM, st>>>(tq, tk, tv, two16, D, D);
    gemm_kernel<0><<<132, 384, G_SMEM, st>>>(txn128, tg, tu, th64, th64, th64);
    gemm_kernel<1><<<64, 384, G_SMEM, st>>>(th128, td, td, ty64, ty64, ty64);
    gemm_kernel<2><<<64, 384, G_SMEM, st>>>(tox, two64, two64, tout, tx128, ty128);
}
```

```cpp
#include <cuda_runtime.h>
#include <cuda_bf16.h>
#include <cuda.h>
#include <stdint.h>
#include <type_traits>

namespace {

constexpr int SEQ = 2048, DM = 1024, HD = 4096, FF = 3584, NSEG = 64;

__device__ __align__(1024) __nv_bfloat16 g_xn[SEQ * DM];
__device__ __align__(1024) uint4 g_xc[SEQ * DM / 8];
__device__ __align__(1024) __nv_bfloat16 g_ox[SEQ * HD];
__device__ __align__(1024) __nv_bfloat16 g_h[SEQ * FF];
__device__ __align__(1024) __nv_bfloat16 g_y[SEQ * DM];
__device__ __align__(1024) uint4 g_xmem[4][1024];
__device__ __align__(1024) uint4 g_xo[4][4096];
#define FSTR 8
__device__ __align__(1024) uint32_t g_flag[2][96 * FSTR];
enum { CNT_H = 0, CNT_OX = 16, CNT_Y = 32, CNT_NUM = 160 };
__device__ __align__(1024) uint32_t g_cnt[CNT_NUM * 8];

__device__ __forceinline__ uint32_t smem_u32(const void* p) { return (uint32_t)__cvta_generic_to_shared(p); }
__device__ __forceinline__ uint32_t mapa(uint32_t a, uint32_t r) {
    uint32_t o; asm("mapa.shared::cluster.u32 %0, %1, %2;" : "=r"(o) : "r"(a), "r"(r)); return o;
}
__device__ __forceinline__ void mbar_init(uint32_t a, uint32_t cnt) {
    asm volatile("mbarrier.init.shared.b64 [%0], %1;" :: "r"(a), "r"(cnt) : "memory");
}
__device__ __forceinline__ void mbar_expect(uint32_t a, uint32_t bytes) {
    asm volatile("mbarrier.arrive.expect_tx.shared.b64 _, [%0], %1;" :: "r"(a), "r"(bytes) : "memory");
}
__device__ __forceinline__ void mbar_arrive_cluster(uint32_t a) {
    asm volatile("mbarrier.arrive.shared::cluster.b64 _, [%0];" :: "r"(a) : "memory");
}
__device__ __forceinline__ void spin_guard(uint32_t& it) {
    asm volatile("{\n.reg .pred p;\nadd.u32 %0, %0, 1;\nsetp.gt.u32 p, %0, 0x400000;\n@p st.shared.u32 [%0], %0;\n}" : "+r"(it));
}
__device__ __forceinline__ void mbar_wait(uint32_t a, uint32_t par) {
    asm volatile("{\n.reg .pred p;\n.reg .u32 i;\nmov.u32 i, 0;\n"
                 "WL:\nadd.u32 i, i, 1;\nsetp.gt.u32 p, i, 0x400000;\n@p st.shared.u32 [i], i;\n"
                 "mbarrier.try_wait.parity.shared::cta.b64 p, [%0], %1;\n@!p bra WL;\n}" :: "r"(a), "r"(par) : "memory");
}
__device__ __forceinline__ void mbar_arrive(uint32_t a) { asm volatile("mbarrier.arrive.shared.b64 _, [%0];" :: "r"(a) : "memory"); }
__device__ __forceinline__ void tma2d(uint32_t dst, const CUtensorMap* m, int c0, int c1, uint32_t bar) {
    asm volatile("cp.async.bulk.tensor.2d.shared::cluster.global.mbarrier::complete_tx::bytes [%0], [%1, {%3, %4}], [%2];"
                 :: "r"(dst), "l"(m), "r"(bar), "r"(c0), "r"(c1) : "memory");
}
__device__ __forceinline__ void tma2d_mc(uint32_t dst, const CUtensorMap* m, int c0, int c1, uint32_t bar, uint16_t mask) {
    asm volatile("cp.async.bulk.tensor.2d.shared::cluster.global.mbarrier::complete_tx::bytes.multicast::cluster [%0], [%1, {%3, %4}], [%2], %5;"
                 :: "r"(dst), "l"(m), "r"(bar), "r"(c0), "r"(c1), "h"(mask) : "memory");
}
__device__ __forceinline__ void bulk_mc(uint32_t dst, const void* src, uint32_t bytes, uint32_t bar, uint16_t mask) {
    asm volatile("cp.async.bulk.shared::cluster.global.mbarrier::complete_tx::bytes.multicast::cluster [%0], [%1], %2, [%3], %4;"
                 :: "r"(dst), "l"(src), "r"(bytes), "r"(bar), "h"(mask) : "memory");
}
__device__ __forceinline__ void bulk_ld(uint32_t dst, const void* src, uint32_t bytes, uint32_t bar) {
    asm volatile("cp.async.bulk.shared::cluster.global.mbarrier::complete_tx::bytes [%0], [%1], %2, [%3];"
                 :: "r"(dst), "l"(src), "r"(bytes), "r"(bar) : "memory");
}
__device__ __forceinline__ uint32_t gtick() { uint32_t c; asm volatile("mov.u32 %0, %%globaltimer_lo;" : "=r"(c)); return c >> 5; }
__device__ __forceinline__ uint32_t gtick_dep(uint32_t zero) {
    uint32_t c;
    asm volatile("{\n.reg .pred p;\nsetp.eq.u32 p, %1, 0;\nmov.u32 %0, 0;\n@p mov.u32 %0, %%globaltimer_lo;\n}" : "=r"(c) : "r"(zero));
    return c >> 5;
}
__device__ __forceinline__ uint32_t ld_relaxed1(const void* p) {
    uint32_t v; asm volatile("ld.relaxed.gpu.global.u32 %0, [%1];" : "=r"(v) : "l"(p) : "memory"); return v;
}
__device__ __forceinline__ bool any_nan(float a, float b) {
    uint32_t r;
    asm volatile("{\n.reg .pred p;\nsetp.nan.f32 p, %1, %2;\nvote.sync.any.pred p, p, 0xffffffff;\nselp.u32 %0, 1, 0, p;\n}" : "=r"(r) : "f"(a), "f"(b));
    return r;
}
__device__ __forceinline__ bool any_nan_unless(float a, float b, uint32_t off) {
    uint32_t r;
    asm volatile("{\n.reg .pred p, q;\nsetp.ne.u32 q, %3, 0xffffffff;\nsetp.nan.and.f32 p, %1, %2, q;\nvote.sync.any.pred p, p, 0xffffffff;\nselp.u32 %0, 1, 0, p;\n}"
                 : "=r"(r) : "f"(a), "f"(b), "r"(off));
    return r;
}
__device__ __forceinline__ bool st_async4_unless_nan(uint32_t a, uint32_t bar, const float* v) {
    uint32_t r;
    asm volatile("{\n.reg .pred p;\nsetp.nan.f32 p, %3, %4;\nvote.sync.any.pred p, p, 0xffffffff;\n"
                 "@!p st.async.shared::cluster.mbarrier::complete_tx::bytes.v4.f32 [%1], {%3,%4,%5,%6}, [%2];\nselp.u32 %0, 1, 0, p;\n}"
                 : "=r"(r) : "r"(a), "r"(bar), "f"(v[0]), "f"(v[1]), "f"(v[2]), "f"(v[3]) : "memory");
    return r;
}
__device__ __forceinline__ void bar_arrive(int id, int n) { asm volatile("bar.arrive %0, %1;" :: "r"(id), "r"(n) : "memory"); }
__device__ __forceinline__ uint32_t clk() { uint32_t c; asm volatile("mov.u32 %0, %%clock;" : "=r"(c)); return c; }
__device__ __forceinline__ void tma2d_store(const CUtensorMap* m, int c0, int c1, uint32_t src) {
    asm volatile("cp.async.bulk.tensor.2d.global.shared::cta.bulk_group [%0, {%1, %2}], [%3];"
                 :: "l"(m), "r"(c0), "r"(c1), "r"(src) : "memory");
}
__device__ __forceinline__ void bar_sync(int id, int n) { asm volatile("bar.sync %0, %1;" :: "r"(id), "r"(n) : "memory"); }
__device__ __forceinline__ void fence_async() { asm volatile("fence.proxy.async.shared::cta;" ::: "memory"); }
__device__ __forceinline__ void cluster_sync() {
    asm volatile("barrier.cluster.arrive.release.aligned;\nbarrier.cluster.wait.acquire.aligned;" ::: "memory");
}
__device__ __forceinline__ void ldsm4(uint32_t* r, uint32_t a) {
    asm volatile("ldmatrix.sync.aligned.m8n8.x4.shared.b16 {%0,%1,%2,%3}, [%4];"
                 : "=r"(r[0]), "=r"(r[1]), "=r"(r[2]), "=r"(r[3]) : "r"(a) : "memory");
}
__device__ __forceinline__ void ldsm4t(uint32_t* r, uint32_t a) {
    asm volatile("ldmatrix.sync.aligned.m8n8.x4.trans.shared.b16 {%0,%1,%2,%3}, [%4];"
                 : "=r"(r[0]), "=r"(r[1]), "=r"(r[2]), "=r"(r[3]) : "r"(a) : "memory");
}
__device__ __forceinline__ void stsm4(uint32_t a, uint32_t r0, uint32_t r1, uint32_t r2, uint32_t r3) {
    asm volatile("stmatrix.sync.aligned.m8n8.x4.shared.b16 [%0], {%1,%2,%3,%4};" :: "r"(a), "r"(r0), "r"(r1), "r"(r2), "r"(r3) : "memory");
}
__device__ __forceinline__ void stsm4t(uint32_t a, uint32_t r0, uint32_t r1, uint32_t r2, uint32_t r3) {
    asm volatile("stmatrix.sync.aligned.m8n8.x4.trans.shared.b16 [%0], {%1,%2,%3,%4};" :: "r"(a), "r"(r0), "r"(r1), "r"(r2), "r"(r3) : "memory");
}
__device__ __forceinline__ void stsm2(uint32_t a, uint32_t r0, uint32_t r1) {
    asm volatile("stmatrix.sync.aligned.m8n8.x2.shared.b16 [%0], {%1,%2};" :: "r"(a), "r"(r0), "r"(r1) : "memory");
}
__device__ __forceinline__ void stsm2t(uint32_t a, uint32_t r0, uint32_t r1) {
    asm volatile("stmatrix.sync.aligned.m8n8.x2.trans.shared.b16 [%0], {%1,%2};" :: "r"(a), "r"(r0), "r"(r1) : "memory");
}
__device__ __forceinline__ uint32_t movm(uint32_t a) {
    uint32_t d; asm volatile("movmatrix.sync.aligned.m8n8.trans.b16 %0, %1;" : "=r"(d) : "r"(a)); return d;
}
__device__ __forceinline__ void mma16(float* d, uint32_t a0, uint32_t a1, uint32_t a2, uint32_t a3, uint32_t b0, uint32_t b1) {
    asm volatile("mma.sync.aligned.m16n8k16.row.col.f32.bf16.bf16.f32 {%0,%1,%2,%3}, {%4,%5,%6,%7}, {%8,%9}, {%0,%1,%2,%3};"
                 : "+f"(d[0]), "+f"(d[1]), "+f"(d[2]), "+f"(d[3]) : "r"(a0), "r"(a1), "r"(a2), "r"(a3), "r"(b0), "r"(b1));
}
__device__ __forceinline__ void mma8(float* d, uint32_t a0, uint32_t a1, uint32_t b0) {
    asm volatile("mma.sync.aligned.m16n8k8.row.col.f32.bf16.bf16.f32 {%0,%1,%2,%3}, {%4,%5}, {%6}, {%0,%1,%2,%3};"
                 : "+f"(d[0]), "+f"(d[1]), "+f"(d[2]), "+f"(d[3]) : "r"(a0), "r"(a1), "r"(b0));
}
__device__ __forceinline__ uint32_t pack2(float lo, float hi) {
    uint32_t r; asm("cvt.rn.bf16x2.f32 %0, %1, %2;" : "=r"(r) : "f"(hi), "f"(lo)); return r;
}
__device__ __forceinline__ float bf_lo(uint32_t v) { return __uint_as_float(v << 16); }
__device__ __forceinline__ float bf_hi(uint32_t v) { return __uint_as_float(v & 0xFFFF0000u); }
__device__ __forceinline__ float ex2(float x) { float y; asm("ex2.approx.ftz.f32 %0, %1;" : "=f"(y) : "f"(x)); return y; }
__device__ __forceinline__ float rcp(float x) { float y; asm("rcp.approx.ftz.f32 %0, %1;" : "=f"(y) : "f"(x)); return y; }
__device__ __forceinline__ void sts4f(uint32_t a, float x, float y, float z, float w) {
    asm volatile("st.shared.v4.f32 [%0], {%1,%2,%3,%4};" :: "r"(a), "f"(x), "f"(y), "f"(z), "f"(w) : "memory");
}
__device__ __forceinline__ void sts4u(uint32_t a, uint4 v) {
    asm volatile("st.shared.v4.u32 [%0], {%1,%2,%3,%4};" :: "r"(a), "r"(v.x), "r"(v.y), "r"(v.z), "r"(v.w) : "memory");
}
__device__ __forceinline__ float4 lds4f(uint32_t a) {
    float4 v; asm volatile("ld.shared.v4.f32 {%0,%1,%2,%3}, [%4];" : "=f"(v.x), "=f"(v.y), "=f"(v.z), "=f"(v.w) : "r"(a) : "memory"); return v;
}
__device__ __forceinline__ float2 lds2f(uint32_t a) {
    float2 v; asm volatile("ld.shared.v2.f32 {%0,%1}, [%2];" : "=f"(v.x), "=f"(v.y) : "r"(a) : "memory"); return v;
}
__device__ __forceinline__ uint4 lds4u(uint32_t a) {
    uint4 v; asm volatile("ld.shared.v4.u32 {%0,%1,%2,%3}, [%4];" : "=r"(v.x), "=r"(v.y), "=r"(v.z), "=r"(v.w) : "r"(a) : "memory"); return v;
}
__device__ __forceinline__ uint32_t lds1u(uint32_t a) {
    uint32_t v; asm volatile("ld.shared.u32 %0, [%1];" : "=r"(v) : "r"(a) : "memory"); return v;
}
__device__ __forceinline__ uint2 lds2u(uint32_t a) {
    uint2 v; asm volatile("ld.shared.v2.u32 {%0,%1}, [%2];" : "=r"(v.x), "=r"(v.y) : "r"(a) : "memory"); return v;
}
__device__ __forceinline__ void st_async4(uint32_t a, uint32_t bar, uint32_t x, uint32_t y, uint32_t z, uint32_t w) {
    asm volatile("st.async.shared::cluster.mbarrier::complete_tx::bytes.v4.b32 [%0], {%1,%2,%3,%4}, [%5];"
                 :: "r"(a), "r"(x), "r"(y), "r"(z), "r"(w), "r"(bar) : "memory");
}
__device__ __forceinline__ void st_async2(uint32_t a, uint32_t bar, uint32_t x, uint32_t y) {
    asm volatile("st.async.shared::cluster.mbarrier::complete_tx::bytes.v2.b32 [%0], {%1,%2}, [%3];"
                 :: "r"(a), "r"(x), "r"(y), "r"(bar) : "memory");
}
__device__ __forceinline__ void st_async1(uint32_t a, uint32_t bar, uint32_t x) {
    asm volatile("st.async.shared::cluster.mbarrier::complete_tx::bytes.b32 [%0], %1, [%2];" :: "r"(a), "r"(x), "r"(bar) : "memory");
}
__device__ __forceinline__ uint4 ld_relaxed4(const uint4* p) {
    uint4 v;
    asm volatile("ld.relaxed.gpu.global.v4.u32 {%0,%1,%2,%3}, [%4];" : "=r"(v.x), "=r"(v.y), "=r"(v.z), "=r"(v.w) : "l"(p) : "memory");
    return v;
}
__device__ __forceinline__ void st_relaxed4(uint4* p, uint4 v) {
    asm volatile("st.relaxed.gpu.global.v4.u32 [%0], {%1,%2,%3,%4};" :: "l"(p), "r"(v.x), "r"(v.y), "r"(v.z), "r"(v.w) : "memory");
}
__device__ __forceinline__ void count_up(int idx) {
    asm volatile("red.release.gpu.global.add.u32 [%0], 1;" :: "l"(&g_cnt[idx * 8]) : "memory");
}
__device__ __forceinline__ void st_pred1(void* p, uint32_t v, bool on) {
    asm volatile("{\n.reg .pred p;\nsetp.ne.u32 p, %2, 0;\n@p st.relaxed.gpu.global.u32 [%0], %1;\n}" :: "l"(p), "r"(v), "r"((uint32_t)on) : "memory");
}
__device__ __forceinline__ void st_pred4(void* p, uint4 v, bool on) {
    asm volatile("{\n.reg .pred p;\nsetp.ne.u32 p, %5, 0;\n@p st.global.v4.u32 [%0], {%1,%2,%3,%4};\n}"
                 :: "l"(p), "r"(v.x), "r"(v.y), "r"(v.z), "r"(v.w), "r"((uint32_t)on) : "memory");
}
__device__ __forceinline__ void st_relaxed1(void* p, uint32_t v) {
    asm volatile("st.relaxed.gpu.global.u32 [%0], %1;" :: "l"(p), "r"(v) : "memory");
}
__device__ __forceinline__ uint32_t umax4(uint4 v) { return max(max(v.x, v.y), max(v.z, v.w)); }
__device__ __forceinline__ void wg_fence() { asm volatile("wgmma.fence.sync.aligned;" ::: "memory"); }
__device__ __forceinline__ void wg_commit() { asm volatile("wgmma.commit_group.sync.aligned;" ::: "memory"); }
template <int N> __device__ __forceinline__ void wg_wait() { asm volatile("wgmma.wait_group.sync.aligned %0;" :: "n"(N) : "memory"); }
template <int N> __device__ __forceinline__ void reg_fence(float* d) {
#pragma unroll
    for (int i = 0; i < N; i++) asm volatile("" : "+f"(d[i]) :: "memory");
}
#define ACC16(d) "+f"(d[0]), "+f"(d[1]), "+f"(d[2]), "+f"(d[3]), "+f"(d[4]), "+f"(d[5]), "+f"(d[6]), "+f"(d[7]), \
                 "+f"(d[8]), "+f"(d[9]), "+f"(d[10]), "+f"(d[11]), "+f"(d[12]), "+f"(d[13]), "+f"(d[14]), "+f"(d[15])
#define DESC_HI_SW128 "0x40000040"
#define OUT16(d) "=f"(d[0]), "=f"(d[1]), "=f"(d[2]), "=f"(d[3]), "=f"(d[4]), "=f"(d[5]), "=f"(d[6]), "=f"(d[7]), \
                 "=f"(d[8]), "=f"(d[9]), "=f"(d[10]), "=f"(d[11]), "=f"(d[12]), "=f"(d[13]), "=f"(d[14]), "=f"(d[15])
template <int ACCUM, int BOFF>
__device__ __forceinline__ void wg32_rs(float* d, const uint32_t* a, uint64_t dsw) {
    if (ACCUM)
        asm volatile("{\n.reg .b64 db;\nadd.s64 db, %20, %21;\n"
                     "wgmma.mma_async.sync.aligned.m64n32k16.f32.bf16.bf16 {%0,%1,%2,%3,%4,%5,%6,%7,%8,%9,%10,%11,%12,%13,%14,%15}, "
                     "{%16,%17,%18,%19}, db, 1, 1, 1, 0;\n}"
                     : ACC16(d) : "r"(a[0]), "r"(a[1]), "r"(a[2]), "r"(a[3]), "l"(dsw), "n"(BOFF));
    else
        asm volatile("{\n.reg .b64 db;\nadd.s64 db, %20, %21;\n"
                     "wgmma.mma_async.sync.aligned.m64n32k16.f32.bf16.bf16 {%0,%1,%2,%3,%4,%5,%6,%7,%8,%9,%10,%11,%12,%13,%14,%15}, "
                     "{%16,%17,%18,%19}, db, 0, 1, 1, 0;\n}"
                     : OUT16(d) : "r"(a[0]), "r"(a[1]), "r"(a[2]), "r"(a[3]), "l"(dsw), "n"(BOFF));
}
template <int AOFF, int BOFF>
__device__ __forceinline__ void wg32_ss(float* d, uint64_t dsw) {
    asm volatile("{\n.reg .b64 da, db;\nadd.s64 da, %16, %17;\nadd.s64 db, %16, %18;\n"
                 "wgmma.mma_async.sync.aligned.m64n32k16.f32.bf16.bf16 {%0,%1,%2,%3,%4,%5,%6,%7,%8,%9,%10,%11,%12,%13,%14,%15}, "
                 "da, db, 1, 1, 1, 1, 0;\n}"
                 : ACC16(d) : "l"(dsw), "n"(AOFF), "n"(BOFF));
}
template <int ACCUM, int AOFF, int BOFF>
__device__ __forceinline__ void wg8_ss(float* d, uint64_t dsw, uint64_t dns) {
    if (!ACCUM)
        asm volatile("{\n.reg .b64 da, db;\nadd.s64 da, %4, %6;\nadd.s64 db, %5, %7;\n"
                     "wgmma.mma_async.sync.aligned.m64n8k16.f32.bf16.bf16 {%0,%1,%2,%3}, da, db, 0, 1, 1, 1, 0;\n}"
                     : "=f"(d[0]), "=f"(d[1]), "=f"(d[2]), "=f"(d[3]) : "l"(dsw), "l"(dns), "n"(AOFF), "n"(BOFF));
    else
        asm volatile("{\n.reg .b64 da, db;\nadd.s64 da, %4, %6;\nadd.s64 db, %5, %7;\n"
                     "wgmma.mma_async.sync.aligned.m64n8k16.f32.bf16.bf16 {%0,%1,%2,%3}, da, db, 1, 1, 1, 1, 0;\n}"
                     : "+f"(d[0]), "+f"(d[1]), "+f"(d[2]), "+f"(d[3]) : "l"(dsw), "l"(dns), "n"(AOFF), "n"(BOFF));
}
template <int I0, int I1, class F>
__device__ __forceinline__ void static_for(F&& f) {
    if constexpr (I0 < I1) { f(std::integral_constant<int, I0>{}); static_for<I0 + 1, I1>(f); }
}
template <int I0, int I1, int AOFF, int BOFF>
__device__ __forceinline__ void wg8_chain(float* d, uint64_t dsw, uint64_t dns) {
    wg_fence();
    static_for<I0, I1>([&](auto i) { wg8_ss<i.value != 0, AOFF + i.value * 128, BOFF + i.value * 16>(d, dsw, dns); });
    wg_commit();
}

__global__ void __launch_bounds__(256) ln_kernel(const __nv_bfloat16* __restrict__ x, const __nv_bfloat16* __restrict__ mem0) {
    const int lane = threadIdx.x & 31, row = blockIdx.x * 8 + (threadIdx.x >> 5);
    asm volatile("griddepcontrol.launch_dependents;" ::: "memory");
    const uint4* src = reinterpret_cast<const uint4*>(x + (size_t)row * DM);
    uint4 v[4];
#pragma unroll
    for (int j = 0; j < 4; j++) v[j] = src[j * 32 + lane];
    const int gi = blockIdx.x * 256 + threadIdx.x;
    const uint4 poison = make_uint4(~0u, ~0u, ~0u, ~0u);
    if (gi < 1024) {
        uint4 m = reinterpret_cast<const uint4*>(mem0)[(gi & 7) * 128 + (gi >> 3)];
        if (m.x == ~0u) m.x = 0x7FFF7FFFu;
        if (m.y == ~0u) m.y = 0x7FFF7FFFu;
        if (m.z == ~0u) m.z = 0x7FFF7FFFu;
        if (m.w == ~0u) m.w = 0x7FFF7FFFu;
        g_xmem[0][gi] = m;
    } else if (gi < 4096) {
        (&g_xmem[0][0])[gi] = poison;
    } else if (gi < 4096 + 16384) {
        (&g_xo[0][0])[gi - 4096] = poison;
    } else if (gi < 4096 + 16384 + 48 * FSTR) {
        reinterpret_cast<uint4*>(&g_flag[0][0])[gi - 4096 - 16384] = poison;
    } else if (gi >= 32768 && gi < 32768 + CNT_NUM) {
        g_cnt[(gi - 32768) * 8] = 0;
    }
    float f[32];
#pragma unroll
    for (int j = 0; j < 4; j++) {
        f[j * 8 + 0] = bf_lo(v[j].x); f[j * 8 + 1] = bf_hi(v[j].x); f[j * 8 + 2] = bf_lo(v[j].y); f[j * 8 + 3] = bf_hi(v[j].y);
        f[j * 8 + 4] = bf_lo(v[j].z); f[j * 8 + 5] = bf_hi(v[j].z); f[j * 8 + 6] = bf_lo(v[j].w); f[j * 8 + 7] = bf_hi(v[j].w);
    }
    float s = 0.f;
#pragma unroll
    for (int i = 0; i < 32; i++) s += f[i];
#pragma unroll
    for (int o = 16; o; o >>= 1) s += __shfl_xor_sync(~0u, s, o);
    const float mean = s * (1.f / DM);
    float q = 0.f;
#pragma unroll
    for (int i = 0; i < 32; i++) { f[i] -= mean; q += f[i] * f[i]; }
#pragma unroll
    for (int o = 16; o; o >>= 1) q += __shfl_xor_sync(~0u, q, o);
    const float r = 1.f / sqrtf(q * (1.f / DM) + 1e-5f);
    uint4* dst = reinterpret_cast<uint4*>(g_xn + (size_t)row * DM);
    uint4* dst2 = g_xc + (row >> 5) * 4096 + (lane >> 3) * 256 + (row & 31) * 8 + ((lane & 7) ^ (row & 7));
#pragma unroll
    for (int j = 0; j < 4; j++) {
        const uint4 o = make_uint4(pack2(f[j * 8] * r, f[j * 8 + 1] * r), pack2(f[j * 8 + 2] * r, f[j * 8 + 3] * r),
                                   pack2(f[j * 8 + 4] * r, f[j * 8 + 5] * r), pack2(f[j * 8 + 6] * r, f[j * 8 + 7] * r));
        dst[j * 32 + lane] = o;
        dst2[(j & 1) * 2048 + (j >> 1) * 1024] = o;
    }
}

#define ONKQ 45
constexpr int ONKV = 128 - 2 * ONKQ;
constexpr uint32_t SB0 = 1024;
constexpr uint32_t C_WS = 0, C_XN = 65536, C_MB = 98304, C_WO = 114688, C_SMEM = 232448;
constexpr uint32_t C_BAR = C_SMEM - 384, C_CAL = C_BAR + 192;
constexpr uint32_t C_SLOTQ = C_WO + ONKQ * 2048, C_QM = C_SLOTQ + 4096, C_KM = C_QM + 1024, C_QX = C_SLOTQ + 8192, C_KX = C_QX + 4096,
                   C_XSL = C_KX + 4096, C_OL = C_XSL + 5120;
constexpr uint32_t C_SLOTV = C_WO + ONKV * 2048, C_V = C_SLOTV + 8192, C_PL = C_V + 20480, C_SL = C_PL + 4096;
static_assert(C_OL + 3072 <= C_BAR && C_SL + 2560 <= C_BAR, "smem overflow");
enum { B_W0 = 0, B_W1, B_W2, B_WS, B_WO, B_XF0, B_XF1, B_SC, B_P0, B_P1, B_XS, B_OL, B_MF0, B_MF1, B_OF, B_RT0, B_RT1, B_VF, B_MBF, B_NUM };
struct Descs { uint64_t sw[4], ns; };
constexpr uint64_t DSW = 0x4000004000010000ull, DNS = 0x0000001000080000ull;
template <int V> using ic = std::integral_constant<int, V>;
constexpr float SM_SCALE = 0.08838834764831845f * 1.4426950408889634f;

#define TSD(i) do {} while (0)
#define TS_FLUSH(w)
#define TSX(i, c)
#define TS(i)
#define NOFILL 0
#define DLY1 2250
#define DLY2 1350
#define STPOS 12
#define OTAIL 3
#define DLYS 450
#define DLYB 100
#define VLEAD 3

#define VEARLY 8
#define QSPLIT 20
__device__ __forceinline__ bool elect() {
    uint32_t r;
    asm volatile("{\n.reg .pred p;\nelect.sync _|p, 0xffffffff;\nselp.u32 %0, 1, 0, p;\n}" : "=r"(r));
    return r;
}
__device__ __forceinline__ int uni(int v) { return __shfl_sync(~0u, v, 0); }
__device__ __forceinline__ void calibrate(uint32_t cal, float keep) {
    const uint32_t t0 = gtick();
    uint32_t t, it = 0;
    do { t = gtick(); spin_guard(it); } while (t == t0);
    const uint32_t c = clk();
    const uint4 p = lds4u(cal);
    const float cpt = 256.f * fminf(fmaxf(__fdividef((float)(c - p.y), (float)((t - p.x) & 0x7FFFFFF)), 16.f), 128.f);
    __syncwarp();
    sts4u(cal, make_uint4(t, c, (uint32_t)(keep > 0.f ? fmaf(keep, (float)p.z - cpt, cpt) : cpt), 0));
}
struct Stamps { uint32_t v[6]; };
__device__ __forceinline__ void load_stamps2(Stamps& t, const uint32_t* f, uint32_t l16, bool on = true) {
    const char* p = reinterpret_cast<const char*>(f) + (l16 >> 2) * FSTR;
    asm volatile("{\n.reg .pred p;\nsetp.ne.u32 p, %7, 0;\nmov.u32 %0, 63;\nmov.u32 %1, 63;\nmov.u32 %2, 63;\nmov.u32 %3, 63;\nmov.u32 %4, 63;\nmov.u32 %5, 63;\n"
                 "@p ld.relaxed.gpu.global.v2.u32 {%0, %1}, [%6];\n@p ld.relaxed.gpu.global.v2.u32 {%2, %3}, [%6 + %8];\n"
                 "@p ld.relaxed.gpu.global.v2.u32 {%4, %5}, [%6 + %9];\n}"
                 : "=&r"(t.v[0]), "=&r"(t.v[1]), "=&r"(t.v[2]), "=&r"(t.v[3]), "=&r"(t.v[4]), "=&r"(t.v[5])
                 : "l"(p), "r"((uint32_t)on), "n"(128 * FSTR), "n"(256 * FSTR) : "memory");
}
__device__ __forceinline__ void load_stamps1(uint32_t* v, const uint32_t* f, uint32_t l16, bool on = true) {
    const char* p = reinterpret_cast<const char*>(f) + (l16 >> 2) * FSTR;
    asm volatile("{\n.reg .pred p;\nsetp.ne.u32 p, %4, 0;\nmov.u32 %0, 63;\nmov.u32 %1, 63;\nmov.u32 %2, 63;\n"
                 "@p ld.relaxed.gpu.global.u32 %0, [%3];\n@p ld.relaxed.gpu.global.u32 %1, [%3 + %5];\n@p ld.relaxed.gpu.global.u32 %2, [%3 + %6];\n}"
                 : "=&r"(v[0]), "=&r"(v[1]), "=&r"(v[2]) : "l"(p), "r"((uint32_t)on), "n"(128 * FSTR), "n"(256 * FSTR) : "memory");
}
template <int N>
__device__ __forceinline__ uint32_t stamps_missing(const uint32_t* v, int s) {
    uint32_t x = 0;
#pragma unroll
    for (int i = 0; i < N; i++) x |= v[i] ^ s;
    return x & 63;
}
template <int N>
__device__ __forceinline__ uint32_t latest_stamp(const uint32_t* v, const uint4 cal) {
    int late = (int)(v[0] - (cal.x << 6));
#pragma unroll
    for (int i = 1; i < N; i++) late = max(late, (int)(v[i] - (cal.x << 6)));
    return cal.y + (((late >> 6) * (int)cal.z) >> 8);
}
__device__ __forceinline__ void wait_clock(uint32_t target) {
    while (__any_sync(~0u, target - clk() < 65536u)) {}
}

template <int BYTES>
__device__ __forceinline__ bool incomplete(uint32_t buf, uint32_t l16) {
    uint32_t m = 0;
#pragma unroll 1
    for (int o = 0; o < BYTES; o += 256) m = max(m, umax4(lds4u(buf + o + (l16 & 255))));
    return __any_sync(~0u, m == ~0u);
}
__device__ __forceinline__ void refetch(uint32_t buf, const uint4* src, uint32_t bytes, uint32_t b, int w4, int barid, uint32_t& tries) {
    spin_guard(tries);
    bar_sync(barid, 128);
    if (w4 == 0 && elect()) { mbar_expect(b, bytes); bulk_ld(buf, src, bytes, b); }
    __syncwarp();
    mbar_wait(b, 0);
    bar_sync(barid, 128);
    if (w4 == 0 && elect()) mbar_arrive(b);
    __syncwarp();
}

template <bool ISV, int WG>
__device__ __forceinline__ void chain_main(const CUtensorMap* tA, const CUtensorMap* tB, const CUtensorMap* tWo,
                                           const uint32_t sb, const int cl, const int rank, const Descs& D) {
    const int tid = threadIdx.x;
    uint32_t l16 = __shfl_sync(~0u, (tid & 31) * 16, tid & 31);
    const int w4 = uni((tid >> 5) & 3);
    const int role = ISV ? 2 : uni(rank & 1), hh = ISV ? rank - 4 : rank >> 1, head = 2 * cl + hh;
    const uint32_t bar = sb + C_BAR;
    constexpr int ONK = ISV ? ONKV : ONKQ;
    const int ostart = uni(hh * 128 + role * ONKQ);

    uint32_t wk[24][4], wv[24][4];
    uint32_t a_adr;
    {
        const int colA = head * 128 + (ISV ? 0 : role * 64), colB = head * 128 + (ISV ? 64 : role * 64);
        auto load_chunk = [&](uint32_t dst, int j, uint32_t b) {
            mbar_expect(b, 65536);
            tma2d(dst, tA, colA, j * 128, b);
            tma2d(dst + 16384, tB, colB, j * 128, b);
            tma2d(dst + 32768, tB, colB, 512 + j * 128, b);
            tma2d(dst + 49152, tA, colA, 512 + j * 128, b);
        };
        if (WG == 0 && tid == 0)
            for (int j = 0; j < 3; j++) load_chunk(sb + j * 65536, j, bar + (B_W0 + j) * 8);
        if (WG == 1 && w4 == 0) calibrate(sb + C_CAL, 0.f);
        const int lane = tid & 31, kr = (lane & 7) + ((lane >> 4) << 3);
        a_adr = __shfl_sync(~0u, sb + WG * 32768 + kr * 128 + (((w4 * 2 + ((lane >> 3) & 1)) ^ (kr & 7)) << 4), lane);
#pragma unroll
        for (int j = 0; j < 3; j++) {
            mbar_wait(bar + (B_W0 + j) * 8, 0);
#pragma unroll
            for (int i = 0; i < 8; i++) {
                ldsm4t(wk[j * 8 + i], a_adr + j * 65536 + i * 2048);
                ldsm4t(wv[j * 8 + i], a_adr + j * 65536 + 16384 + i * 2048);
            }
            if (j != 1) {
                bar_sync(6, 256);
                if (WG == 0 && j == 0 && tid == 0) load_chunk(sb + C_WS, 3, bar + B_WS * 8);
                if (WG == 0 && j == 2 && w4 == 0) {
                    if (lane == 0) mbar_expect(bar + B_WO * 8, ONK * 2048);
                    __syncwarp();
                    for (int i = lane; i < ONK; i += 32) tma2d(sb + C_WO + i * 2048, tWo, cl * 64, (ostart + i) * 16, bar + B_WO * 8);
                }
                __syncwarp();
            }
        }
        if (NOFILL) { for (uint32_t o = C_WO + ONK * 2048 + tid * 16; o < C_BAR; o += 4096) sts4u(sb + o, make_uint4(0, 0, 0, 0)); bar_sync(6, 256); }
        asm volatile("griddepcontrol.wait;" ::: "memory");
        asm volatile("griddepcontrol.launch_dependents;" ::: "memory");
        if (WG == 1 && w4 == 0) calibrate(sb + C_CAL, 0.f);
    }

    constexpr uint32_t SLOT = ISV ? C_SLOTV : C_SLOTQ;
    constexpr int WS_A = (SB0 + C_WS + WG * 32768) >> 4, WO_A = (SB0 + C_WO) >> 4, MB_A = (SB0 + C_MB) >> 4;
#define XN_A(ks) (int)(((SB0 + C_XN + WG * 16384) >> 4) + ((ks) >> 2) * 256 + ((ks) & 3) * 2)
    const uint32_t slot = uni(sb + SLOT + w4 * 512), mbw = sb + C_MB + WG * 8192;
    const uint32_t sb_v = uni(mapa(sb, 4 + hh));
    const uint32_t sb_x = uni(mapa(sb, 2 * hh + WG));
    const uint32_t sb_o = uni(mapa(sb, w4));
    const uint32_t u_off = uni(ISV ? (head * 128 + w4 * 32) * 16 : (cl * 4 + rank) * 256 + (w4 & 1) * 128);
    const uint32_t v_row = uni(sb + C_V + (2 * WG + (w4 >> 1)) * 512), v_b = uni((w4 & 1) * 64);
    const uint32_t u_flag = uni(blockIdx.x * FSTR);
    const uint32_t f_bytes = uni(w4 ? ONKV * 128 : ONKQ * 256), f_bar = uni((w4 ? sb_v : sb) + C_BAR + B_OF * 8);
    const uint32_t f_dst = uni(w4 ? sb_v + C_MB + role * (ONKV * 128) : sb + C_MB);
    const uint32_t f_src = uni(w4 ? (ostart + (2 - role) * ONKQ) * 256 + role * (ONKV * 128) : ostart * 256);
    const uint32_t m_dst = uni(sb + C_MB + role * 8192), m_bar = uni(bar + (B_MF0 + role) * 8);
    uint32_t target, missing;
    int s = -1;
    uint32_t pf[4][4];
    float xk[16], xv[16];

    auto load_tokens = [&](int seg, int wina, int g) {
        const int khalf = ISV ? 1 - wina : wina;
        if (!NOFILL && elect()) {
            mbar_expect(bar + (B_XF0 + g) * 8, 16384);
            bulk_ld(sb + C_XN + g * 16384, g_xc + (seg * 4 + khalf * 2 + g) * 1024, 16384, bar + (B_XF0 + g) * 8);
        }
        __syncwarp();
    };
    auto prefetch = [&]() {
#pragma unroll
        for (int i = 0; i < 4; i++) ldsm4t(pf[i], a_adr + C_WS + (i & 1) * 16384 + (i >> 1) * 2048);
    };
    constexpr int HA = ISV ? 0 : 1;
    auto products = [&](auto give, auto half, auto init, auto i0, auto i1, const uint64_t d) {
        static_for<i0.value, i1.value>([&](auto i) {
            constexpr int ks = half.value * 16 + i.value, acc = !(init.value && i.value == 0);
            if constexpr (ks >= 24) wg32_ss<WS_A + give.value * 1024 + (ks - 24) * 128, XN_A(i.value)>(give.value ? xv : xk, d);
            else if constexpr (give.value) wg32_rs<acc, XN_A(i.value)>(xv, wv[ks], d);
            else wg32_rs<acc, XN_A(i.value)>(xk, wk[ks], d);
        });
    };
    auto stream_a = [&](const uint64_t dk, const uint64_t dv) {
        if (NOFILL) return;
        wg_fence();
        products(ic<0>{}, ic<HA>{}, ic<1>{}, ic<0>{}, ic<8>{}, dk);
        products(ic<1>{}, ic<HA>{}, ic<1>{}, ic<0>{}, ic<16>{}, dv);
        products(ic<0>{}, ic<HA>{}, ic<1>{}, ic<8>{}, ic<16>{}, dk);
        wg_commit();
    };
    auto token_softmax = [&]() {
        const int hi = w4 - 2, lane = l16 >> 4;
        const uint32_t src = sb + C_XSL + l16 + hi * 8;
        const int d0 = 16 * role + 8 * hi + (lane >> 2) - 2 * (lane & 3);
        mbar_wait(bar + B_XS * 8, s & 1);
        float e[10];
        float m = -INFINITY;
#pragma unroll
        for (int i = 0; i < 5; i++) {
            __syncwarp();
            const float2 a = lds2f(src + i * 512), b = lds2f(src + 2560 + i * 512);
            e[2 * i] = (i == 0 || d0 >= 8 * (i - 1)) ? a.x + b.x : -INFINITY;
            e[2 * i + 1] = (i == 0 || d0 > 8 * (i - 1)) ? a.y + b.y : -INFINITY;
            m = fmaxf(m, fmaxf(e[2 * i], e[2 * i + 1]));
        }
        m = fmaxf(m, __shfl_xor_sync(~0u, m, 1));
        m = fmaxf(m, __shfl_xor_sync(~0u, m, 2));
        m *= -SM_SCALE;
        float l = 0.f;
#pragma unroll
        for (int i = 0; i < 10; i++) { e[i] = ex2(fmaf(e[i], SM_SCALE, m)); l += e[i]; }
        l += __shfl_xor_sync(~0u, l, 1);
        l += __shfl_xor_sync(~0u, l, 2);
        l = rcp(l);
        const uint32_t pd = sb_v + C_PL + (s & 1) * 2048 + role * 768 + hi * 128 + (l16 >> 2), pb = sb_v + C_BAR + (B_P0 + (s & 1)) * 8;
        st_async1(pd, pb, pack2(e[0] * l, e[1] * l));
        st_async1(pd + 256, pb, pack2(e[2] * l, e[3] * l));
        st_async1(pd + 512, pb, pack2(e[4] * l, e[5] * l));
        if (role) {
            st_async1(pd + 768, pb, pack2(e[6] * l, e[7] * l));
            st_async1(pd + 1024, pb, pack2(e[8] * l, e[9] * l));
        }
        if (hi == 0 && l16 == 0) mbar_expect(bar + B_XS * 8, 3072 + role * 2048);
        __syncwarp();
    };

    auto windows = [&](auto first_) {
        constexpr bool FIRST = first_.value;
        asm volatile("" : "+r"(l16));
        const uint64_t dd[4] = {FIRST ? DSW : D.sw[0], FIRST ? DSW : D.sw[1], FIRST ? DSW : D.sw[2], FIRST ? DSW : D.sw[3]};
        TS(5);
        if constexpr (WG == 1) {
            TS(6);
            if (ISV && !FIRST) bar_sync(3, 256);
            stream_a(dd[0], dd[1]);
            if (!NOFILL) bar_arrive(7, 256);
            if (!FIRST && !ISV && w4 < 2) {
                const char* src = reinterpret_cast<const char*>(&g_xo[s & 3][0]) + f_src;
                if (__builtin_expect(__any_sync(~0u, missing), 0)) {
                    Stamps st;
                    uint32_t it = 0;
                    do { load_stamps2(st, g_flag[0], l16); spin_guard(it); } while (__any_sync(~0u, stamps_missing<6>(st.v, s)));
                    target = latest_stamp<6>(st.v, lds4u(sb + C_CAL)) + DLY1;
                }
                mbar_wait(bar + B_VF * 8, s & 1);
                TS(10);
                wait_clock(target);
                if (elect()) bulk_ld(f_dst, src, f_bytes, f_bar);
                __syncwarp();
                TS(8);
            }
            if (!NOFILL) {
                wg_wait<0>();
                reg_fence<16>(xk); reg_fence<16>(xv);
                if (w4 == 3) {
                    bar_sync(2, 128);
                    load_tokens(s + 1, 0, 1);
                    if (ISV && !FIRST && (s & 3) == 0 && s > 0 && l16 == 0) count_up(CNT_OX + (s >> 2) - 1);
                    __syncwarp();
                }
                else bar_arrive(2, 128);
            }
            TS(7);
        } else {
            if (!NOFILL) {
                mbar_wait(bar + B_XF0 * 8, 0);
                bar_sync(7, 256);
            }
            TS(6);
            stream_a(dd[0], dd[1]);
        }
        Stamps st;
        uint4 cal;
        if constexpr (WG == 0) {
            if constexpr (!FIRST) {
                const uint32_t dst = sb_o + C_OL + rank * 512 + ((l16 & 64) << 2) + ((l16 >> 1) & 192) + (l16 & 48);
                const uint32_t can = sb + C_MB + l16 * 8 + (l16 >> 2), can2 = can + (l16 < (ONK * 2 - 64) * 16 ? 8192 : 0);
                float co[4];
                uint32_t tries = 0;
                TS(7);
                mbar_wait(bar + B_OF * 8, s & 1);
                TS(8);
                auto early = [&]() { return __any_sync(~0u, max(max(lds1u(can), lds1u(can + 4096)), lds1u(can2)) == ~0u); };
                wg8_chain<0, 10, WO_A, MB_A>(co, D.sw[0], D.ns);
                if (__builtin_expect(early(), 0)) {
                    wg_wait<0>();
                    do refetch(sb + C_MB, &g_xo[s & 3][ostart * 16], ONK * 256, bar + B_RT0 * 8, w4, 1, tries); while (early());
                    wg8_chain<0, 10, WO_A, MB_A>(co, DSW, DNS);
                }
                wg_wait<1>();
                bar_arrive(4, 192);
                wg8_chain<10, ONK - OTAIL, WO_A, MB_A>(co, D.sw[0], D.ns);
                static_for<ONK - OTAIL, ONK>([&](auto i) { wg8_ss<1, WO_A + i.value * 128, MB_A + i.value * 16>(co, D.sw[0], D.ns); });
                wg_commit();
                wg_wait<1>();
                bar_arrive(5, 256);
                wg_wait<0>();
                reg_fence<4>(co);
                if (__builtin_expect(st_async4_unless_nan(dst, sb_o + C_BAR + B_OL * 8, co), 0)) {
                    while (incomplete<ONK * 256>(sb + C_MB, l16)) {
                        refetch(sb + C_MB, &g_xo[s & 3][ostart * 16], ONK * 256, bar + B_RT0 * 8, w4, 1, tries);
                        co[0] = co[1] = co[2] = co[3] = 0.f;
#pragma unroll 1
                        for (int i = 0; i < ONK; i++) {
                            wg_fence();
                            wg8_ss<1, WO_A, MB_A>(co, DSW + i * 128, DNS + i * 16);
                            wg_commit();
                            wg_wait<0>();
                        }
                        reg_fence<4>(co);
                    }
                    st_async4(dst, sb_o + C_BAR + B_OL * 8, __float_as_uint(co[0]), __float_as_uint(co[1]), __float_as_uint(co[2]), __float_as_uint(co[3]));
                }
                if (l16 < 32) mbar_arrive_cluster(mapa(bar + B_MBF * 8, 2 * hh + (l16 >> 4)));
                TS(9);
                if (l16 < 48 && w4 == 3) mbar_expect(bar + B_MF0 * 8 + (l16 >> 1), l16 == 32 ? ONK * 256 : 8192);
                if (!ISV && w4 < 2) {
                    const uint32_t off = u_off + (l16 >> 2);
                    const uint32_t src = sb + C_OL + w4 * 8 + ((l16 & 48) << 2) + ((l16 >> 3) & 48) + ((l16 >> 4) & 4);
                    char* gd = reinterpret_cast<char*>(&g_xmem[(s + 1) & 3][0]) + off;
                    st_relaxed1(reinterpret_cast<char*>(&g_xmem[(s + 3) & 3][0]) + off, ~0u);
                    mbar_wait(bar + B_OL * 8, s & 1);
                    float a[6], b[6];
#pragma unroll
                    for (int i = 0; i < 6; i++) { a[i] = __uint_as_float(lds1u(src + i * 512)); b[i] = __uint_as_float(lds1u(src + i * 512 + 256)); }
                    st_relaxed1(gd, pack2((a[0] + a[1]) + (a[2] + a[3]) + (a[4] + a[5]), (b[0] + b[1]) + (b[2] + b[3]) + (b[4] + b[5])));
                    TS(10);
                    if (w4 == 0 && l16 == 0) mbar_expect(bar + B_OL * 8, 3072);
                }
                __syncwarp();
            } else {
                wg_wait<0>();
                bar_arrive(4, 192);
                bar_arrive(5, 256);
                if (l16 < 32) mbar_arrive_cluster(mapa(bar + B_MBF * 8, 2 * hh + (l16 >> 4)));
                mbar_wait(bar + B_WO * 8, 0);
            }
            if (!NOFILL) { reg_fence<16>(xk); reg_fence<16>(xv); }
        } else {
            if (w4 < 2) {
                bar_sync(4, 192);
                const uint32_t dep = lds2u(sb + C_CAL + 8).y;
                const uint32_t v = ((gtick_dep(dep) - (ISV ? (ONKQ - ONKV) * 18 / 64 : 0)) << 6) | s, c = clk();
                if (w4 == 0) {
                    if (!FIRST) {
                        if (l16 == 0) st_relaxed1(&g_flag[1][u_flag + dep], v);
                        if (!ISV) { calibrate(sb + C_CAL, 0.75f); wait_clock(c + DLYS); }
                    }
                } else {
                    if (!FIRST) wait_clock(c + DLYB);
                    load_tokens(s + 1, 0, 0);
                }
            } else if (!ISV && !FIRST && !NOFILL) {
                token_softmax();
                TSX(9, w4 == 2);
            }
            if (!NOFILL) mbar_wait(bar + B_XF1 * 8, 1);
            if (!FIRST && !ISV) { load_stamps1(st.v, g_flag[1], l16, w4 == 0); cal = lds4u(sb + C_CAL); }
            bar_sync(5, 256);
        }
        TS(11);
        auto store_tokens = [&](const float4* r) {
            uint32_t lo[4], hi[4];
#pragma unroll
            for (int j = 0; j < 4; j++) {
                lo[j] = pack2(xk[4 * j] + r[j].x, xk[4 * j + 1] + r[j].y);
                hi[j] = pack2(xk[4 * j + 2] + r[j].z, xk[4 * j + 3] + r[j].w);
            }
            if (!ISV) {
                const uint32_t d = sb + C_QX + WG * 4096 + w4 * 1024 + l16;
                stsm4t(d, lo[0], lo[1], lo[2], lo[3]);
                stsm4t(d + 512, hi[0], hi[1], hi[2], hi[3]);
            } else {
                const uint32_t d = v_row + ((s + 1) & 1) * 10240 + ((l16 & 384) << 4) + ((l16 & 96) << 2) + ((l16 & 112) ^ v_b);
                stsm4(d, lo[0], lo[1], lo[2], lo[3]);
                stsm4(d ^ 32, hi[0], hi[1], hi[2], hi[3]);
            }
        };
        if constexpr (WG == 1) {
            if (!NOFILL) {
                wg_fence();
                products(ic<1>{}, ic<1 - HA>{}, ic<0>{}, ic<0>{}, ic<16>{}, dd[3]);
                wg_commit();
                __syncwarp();
                if (!FIRST && !ISV) load_stamps1(st.v + 3, g_flag[1], l16, w4 == 0);
                __syncwarp();
                products(ic<0>{}, ic<1 - HA>{}, ic<0>{}, ic<0>{}, ic<16>{}, dd[2]);
                wg_commit();
                bar_arrive(7, 256);
                wg_wait<1>();
                reg_fence<16>(xv);
#pragma unroll
                for (int j = 0; j < 4; j++) sts4f(slot + l16 + j * 2048, xv[4 * j], xv[4 * j + 1], xv[4 * j + 2], xv[4 * j + 3]);
                bar_arrive(8, 256);
            }
            if (!NOFILL) {
                wg_wait<0>();
                reg_fence<16>(xk);
                if (w4 != 3) bar_arrive(13, 128);
                else if (!ISV) { bar_sync(13, 128); if (s < NSEG - 2) load_tokens(s + 2, 1, 1); }
            }
            TS(13);
            if (!ISV && w4 == 0) {
                const uint4* src = &g_xmem[(s + 1) & 3][role * 512];
                mbar_wait(bar + B_MBF * 8, (s + 1) & 1);
                if (!FIRST) {
                    if (__builtin_expect(__any_sync(~0u, stamps_missing<3>(st.v, s)), 0)) {
                        uint32_t it = 0;
                        if (!NOFILL) { st.v[0] = st.v[3]; st.v[1] = st.v[4]; st.v[2] = st.v[5]; }
                        while (__any_sync(~0u, stamps_missing<3>(st.v, s))) { load_stamps1(st.v, g_flag[1], l16); spin_guard(it); }
                    }
                    target = latest_stamp<3>(st.v, cal) + DLY2;
                    TS(3);
                    wait_clock(target);
                }
                if (elect()) {
                    if (hh) bulk_mc(m_dst, src, 8192, m_bar, 0x2C);
                    else bulk_mc(m_dst, src, 8192, m_bar, 0x13);
                }
                __syncwarp();
                TS(4);
            }
            prefetch();
            if (!NOFILL) {
                bar_sync(9, 256);
                float4 r[4];
#pragma unroll
                for (int j = 0; j < 4; j++) r[j] = lds4f(slot + l16 + j * 2048);
                store_tokens(r);
                bar_arrive(10, 256);
                if (ISV && w4 == 3) bar_sync(13, 128);
            }
        } else {
            if (!NOFILL) {
                mbar_wait(bar + B_XF0 * 8, 1);
                bar_sync(7, 256);
                TS(12);
                wg_fence();
                products(ic<1>{}, ic<1 - HA>{}, ic<0>{}, ic<0>{}, ic<16>{}, dd[3]);
                wg_commit();
                products(ic<0>{}, ic<1 - HA>{}, ic<0>{}, ic<0>{}, ic<6>{}, dd[2]);
                wg_commit();
                bar_sync(8, 256);
                float4 r[4];
#pragma unroll
                for (int j = 0; j < 4; j++) r[j] = lds4f(slot + l16 + j * 2048);
                wg_wait<1>();
                reg_fence<16>(xv);
#pragma unroll
                for (int j = 0; j < 4; j++) sts4f(slot + l16 + j * 2048, xv[4 * j], xv[4 * j + 1], xv[4 * j + 2], xv[4 * j + 3]);
                bar_arrive(9, 256);
                products(ic<0>{}, ic<1 - HA>{}, ic<0>{}, ic<6>{}, ic<16>{}, dd[2]);
                wg_commit();
                wg_wait<0>();
                reg_fence<16>(xk);
                TS(13);
                prefetch();
                store_tokens(r);
            } else {
                prefetch();
            }
        }
    };

    if (w4 == 0) load_tokens(0, 1, WG);
    mbar_wait(bar + B_WS * 8, 0);
    if (WG == 1 && !NOFILL) mbar_wait(bar + B_XF1 * 8, 0);
    windows(ic<1>{});

#pragma unroll 1
    while (true) {
        s++;
        asm volatile("" : "+r"(l16), "+r"(a_adr));
        TS_FLUSH(WG);
        TS(0);
        float ck[4], cv[4];
        uint32_t k0[2][4], k1[2][4];
        Stamps st1;
        const uint32_t kl = sb + C_KX + ((l16 & 384) << 2) + (l16 & 112);
        {
            const uint32_t can = mbw + l16 * 8 + (l16 >> 2);
            uint32_t tries = 0;
            bool synced = false;
            for (;; tries |= 1) {
                asm volatile("" : "+r"(tries));
                if (__builtin_expect(tries, 0)) {
                    if (__any_sync(~0u, max(lds1u(can), lds1u(can + 4096)) == ~0u) || incomplete<8192>(mbw, l16))
                        refetch(mbw, &g_xmem[s & 3][WG * 512], 8192, bar + (B_RT0 + WG) * 8, w4, 1 + WG, tries);
                    else tries = ~0u;
                    prefetch();
                }
                mbar_wait(bar + (B_MF0 + WG) * 8, s & 1);
                TS(1);
                uint32_t b[2][4];
                float dk[4], dv[4];
                ldsm4(b[0], mbw + l16 + 12 * 512);
#pragma unroll
                for (int i = 0; i < 4; i++) ck[i] = cv[i] = dk[i] = dv[i] = 0.f;
                auto kpair = [&](auto kp_) {
                    constexpr int kp = kp_.value, grp = kp / 5, ph = kp % 5, nx = kp + 1;
                    if constexpr (nx < 16) ldsm4(b[nx & 1], mbw + l16 + ((nx % 5) ? (nx / 5) * 4 + (nx % 5) - 1 : 12 + nx / 5) * 512);
                    const uint32_t* bb = b[kp & 1];
                    if constexpr (ph != 0) {
                        constexpr int q = (grp * 4 + ph - 1) * 2, i = ph - 1;
                        ldsm4t(pf[i], a_adr + C_WS + (i & 1) * 16384 + (grp * 2 + 2 + (i >> 1)) * 2048);
                        __syncwarp();
                        mma16(cv, wv[q][0], wv[q][1], wv[q][2], wv[q][3], bb[0], bb[1]);
                        mma16(ck, wk[q][0], wk[q][1], wk[q][2], wk[q][3], bb[0], bb[1]);
                        mma16(dv, wv[q + 1][0], wv[q + 1][1], wv[q + 1][2], wv[q + 1][3], bb[2], bb[3]);
                        mma16(dk, wk[q + 1][0], wk[q + 1][1], wk[q + 1][2], wk[q + 1][3], bb[2], bb[3]);
                    } else {
                        mma16(cv, pf[1][0], pf[1][1], pf[1][2], pf[1][3], bb[0], bb[1]);
                        mma16(dv, pf[3][0], pf[3][1], pf[3][2], pf[3][3], bb[2], bb[3]);
                        mma16(ck, pf[0][0], pf[0][1], pf[0][2], pf[0][3], bb[0], bb[1]);
                        mma16(dk, pf[2][0], pf[2][1], pf[2][2], pf[2][3], bb[2], bb[3]);
                    }
                };
                kpair(ic<0>{});
                const uint32_t c0 = lds1u(can), c1 = lds1u(can + 4096);
                kpair(ic<1>{});
                if (__builtin_expect(__any_sync(~0u, max(c0, c1) == ~0u), 0)) continue;
                st_pred1(&g_flag[0][u_flag + WG + l16], ((gtick() - (ISV ? VLEAD : 0)) << 6) | s, w4 * 512 + l16 == 1536);
                if (WG == 0 && !NOFILL && !synced) bar_sync(10, 256);
                synced = true;
                static_for<2, STPOS>(kpair);
                if (!ISV && WG == 1) load_stamps2(st1, g_flag[0], l16, w4 < 2);
                static_for<STPOS, 16>(kpair);
#pragma unroll
                for (int i = 0; i < 4; i++) cv[i] += dv[i];
                sts4f(slot + WG * 2048 + l16, cv[0], cv[1], cv[2], cv[3]);
#pragma unroll
                for (int i = 0; i < 4; i++) ck[i] += dk[i];
                TS(2);
                if (__builtin_expect(!any_nan_unless(cv[0], cv[1], tries), 1)) break;
            }
            if (!ISV && WG == 0) {
                const uint32_t ka = kl + (w4 == 1 ? 256 : 0);
                ldsm4(k0[0], ka); ldsm4(k0[1], ka + 2048);
                ldsm4(k1[0], ka + 128); ldsm4(k1[1], ka + 128 + 2048);
            }
            if (ISV && WG == 1 && w4 == 3 && s < NSEG - 1) load_tokens(s + 1, 1, 1);
            bar_sync(6, 256);
        }
        if constexpr (!ISV) {
            const uint32_t lane_b = sb + C_QM + ((l16 >> 1) & 128) + ((l16 & 128) << 2) + (l16 & 112);
            const uint32_t qx = sb + C_QX + WG * 256 + l16 + (l16 & 256);
            const uint32_t xd = sb_x + C_XSL + role * 2560 + l16, xb = sb_x + C_BAR + B_XS * 8;
            {
                const float4 r = lds4f(slot + (WG ^ 1) * 2048 + l16);
                stsm2t(sb + C_QM + WG * 1024 + w4 * 256 + (l16 & 255), pack2(ck[0] + r.x, ck[1] + r.y), pack2(ck[2] + r.z, ck[3] + r.w));
            }
            auto tile = [&](float* d, const uint32_t (*q)[4], const uint32_t (*k)[4]) {
                d[0] = d[1] = d[2] = d[3] = 0.f;
#pragma unroll
                for (int i = 0; i < 4; i++) mma16(d, q[i][0], q[i][1], q[i][2], q[i][3], k[i >> 1][(i & 1) * 2], k[i >> 1][(i & 1) * 2 + 1]);
            };
            auto send = [&](int ti, const float* d) {
                st_async4(xd + ti * 512, xb, __float_as_uint(d[0]), __float_as_uint(d[1]), __float_as_uint(d[2]), __float_as_uint(d[3]));
            };
            if constexpr (WG == 0) {
                if (w4 < 2) {
                    uint32_t q0[4], q1[4];
                    const uint32_t dst = sb_v + C_SL + role * 1280 + w4 * 512 + l16;
                    bar_sync(6, 256);
                    TS(3);
                    ldsm4(q0, lane_b); ldsm4(q1, lane_b + 256);
                    float s0[4] = {0.f, 0.f, 0.f, 0.f}, s1[4] = {0.f, 0.f, 0.f, 0.f}, s2[4] = {0.f, 0.f, 0.f, 0.f}, s3[4] = {0.f, 0.f, 0.f, 0.f};
                    mma16(s0, q0[0], q0[1], q0[2], q0[3], k0[0][0], k0[0][1]);
                    mma16(s1, q0[0], q0[1], q0[2], q0[3], k0[1][0], k0[1][1]);
                    mma16(s2, q0[0], q0[1], q0[2], q0[3], k1[0][0], k1[0][1]);
                    mma16(s3, q0[0], q0[1], q0[2], q0[3], k1[1][0], k1[1][1]);
                    mma16(s0, q1[0], q1[1], q1[2], q1[3], k0[0][2], k0[0][3]);
                    mma16(s1, q1[0], q1[1], q1[2], q1[3], k0[1][2], k0[1][3]);
                    mma16(s2, q1[0], q1[1], q1[2], q1[3], k1[0][2], k1[0][3]);
                    mma16(s3, q1[0], q1[1], q1[2], q1[3], k1[1][2], k1[1][3]);
                    st_async4(dst, sb_v + C_BAR + B_SC * 8, __float_as_uint(s0[0] + s1[2]), __float_as_uint(s0[1] + s1[3]),
                              __float_as_uint(s2[0] + s3[2]), __float_as_uint(s2[1] + s3[3]));
                    bar_arrive(12, 256);
                    TS(4);
                } else if (w4 == 2) {
                    uint32_t q0[4], q1[4], m0[4], m1[4];
                    const uint32_t dst = sb_v + C_SL + role * 1280 + 1024 + (l16 >> 1);
                    bar_sync(6, 256);
                    ldsm4(q0, lane_b); ldsm4(m0, sb + C_KM + l16); ldsm4(m1, sb + C_KM + 512 + l16); ldsm4(q1, lane_b + 256);
                    float s0[4] = {0.f, 0.f, 0.f, 0.f}, s1[4] = {0.f, 0.f, 0.f, 0.f};
                    mma16(s0, q0[0], q0[1], q0[2], q0[3], m0[0], m0[1]);
                    mma16(s1, q0[0], q0[1], q0[2], q0[3], m1[0], m1[1]);
                    mma16(s0, q1[0], q1[1], q1[2], q1[3], m0[2], m0[3]);
                    mma16(s1, q1[0], q1[1], q1[2], q1[3], m1[2], m1[3]);
                    st_async2(dst, sb_v + C_BAR + B_SC * 8, __float_as_uint(s0[0] + s1[2]), __float_as_uint(s0[1] + s1[3]));
                    bar_arrive(12, 256);
                } else {
                    bar_sync(6, 256);
                    if (s < NSEG - 1) load_tokens(s + 1, 1, 0);
                    if (!NOFILL) {
                        uint32_t q[4][4], km[2][4];
                        float d0[4], d1[4], d2[4];
#pragma unroll
                        for (int i = 0; i < 4; i++) ldsm4(q[i], qx + i * 1024);
                        ldsm4(km[0], sb + C_KM + l16); ldsm4(km[1], sb + C_KM + 512 + l16);
                        tile(d1, q, k0); tile(d2, q, k1); tile(d0, q, km);
                        reg_fence<4>(d0);
                        bar_sync(12, 256);
                        send(0, d0); send(1, d1); send(2, d2);
                    } else {
                        bar_sync(12, 256);
                    }
                }
                if (__builtin_expect(s == NSEG - 1, 0)) break;
            } else {
                bar_sync(6, 256);
                if (!NOFILL) mbar_wait(bar + B_XF1 * 8, s == NSEG - 1);
                missing = stamps_missing<6>(st1.v, s);
                target = latest_stamp<6>(st1.v, lds4u(sb + C_CAL)) + DLY1;
                if (!NOFILL) {
                    uint32_t q[4][4];
                    float d0[4], d1[4];
#pragma unroll
                    for (int i = 0; i < 4; i++) ldsm4(q[i], qx + i * 1024);
                    ldsm4(k0[0], kl + w4 * 128); ldsm4(k0[1], kl + w4 * 128 + 2048);
                    ldsm4(k1[0], sb + C_KM + l16); ldsm4(k1[1], sb + C_KM + 512 + l16);
                    tile(d1, q, k0); tile(d0, q, k1);
                    bar_sync(12, 256);
                    send(1 + w4, d1);
                    if (w4 == 0) send(0, d0);
                } else {
                    bar_sync(12, 256);
                }
                if (__builtin_expect(s == NSEG - 1, 0)) {
                    asm volatile("" : "+r"(l16));
                    if (w4 >= 2 && !NOFILL) token_softmax();
                    break;
                }
            }
        } else {
            const uint32_t lane_b = sb + C_V + w4 * 512 + ((l16 & 384) << 4) + (l16 & 112);
            auto load_values = [&](uint32_t (*vx)[4], uint32_t* vm, int ss) {
#pragma unroll
                for (int j = 0; j < 4; j++) ldsm4(vx[j], ((lane_b + (ss & 1) * 10240) ^ (j * 32)) + j * 128);
                ldsm4(vm, sb + C_V + (ss & 1) * 10240 + w4 * 512 + 8192 + (l16 ^ ((l16 >> 2) & 96)));
            };
            auto token_output = [&](int ss, bool live, auto mid) {
                uint32_t vx[4][4], vm[4];
                const uint32_t pl = sb + C_PL + (ss & 1) * 2048 + (l16 >> 2);
                auto lds_frag = [&](uint32_t a) { return make_uint4(lds1u(a), lds1u(a + 128), lds1u(a + 256), lds1u(a + 384)); };
                load_values(vx, vm, ss);
                mid();
                char* orow = reinterpret_cast<char*>(g_ox) + (ss * (32 * HD * 2) + (u_off >> 3) + (l16 >> 6) * (HD * 2) + (l16 & 48));
#pragma unroll
                for (int mh = 1; mh >= 0; mh--) {
                    __syncwarp();
                    const uint2 pm = make_uint2(lds1u(pl + mh * 768), lds1u(pl + mh * 768 + 128));
                    const uint4 p0 = lds_frag(pl + mh * 768 + 256);
                    float o[4][4];
#pragma unroll
                    for (int j = 0; j < 4; j++) { o[j][0] = o[j][1] = o[j][2] = o[j][3] = 0.f; mma8(o[j], pm.x, pm.y, vm[j]); }
#pragma unroll
                    for (int j = 0; j < 4; j++) mma16(o[j], p0.x, p0.y, p0.z, p0.w, vx[j][0], vx[j][1]);
                    if (mh) {
                        const uint4 p1 = lds_frag(pl + 1536);
#pragma unroll
                        for (int j = 0; j < 4; j++) mma16(o[j], p1.x, p1.y, p1.z, p1.w, vx[j][2], vx[j][3]);
                    }
                    st_pred4(orow + mh * (16 * HD * 2),
                             make_uint4(pack2(o[0][0], o[0][1]), pack2(o[1][0], o[1][1]), pack2(o[2][0], o[2][1]), pack2(o[3][0], o[3][1])), live);
                    st_pred4(orow + mh * (16 * HD * 2) + 8 * HD * 2,
                             make_uint4(pack2(o[0][2], o[0][3]), pack2(o[1][2], o[1][3]), pack2(o[2][2], o[2][3]), pack2(o[3][2], o[3][3])), live);
                }
            };
            const uint32_t vd = v_row + (s & 1) * 10240 + 8192 + ((l16 & 96) << 2) + ((l16 & 112) ^ v_b ^ ((l16 & 128) >> 2));
            const float4 r = lds4f(slot + (WG ^ 1) * 2048 + l16);
            __syncwarp();
            auto finish = [&]() {
                stsm2(vd, pack2(ck[0] + r.x, ck[1] + r.y), pack2(ck[2] + r.z, ck[3] + r.w));
                if (WG == 1) {
                    bar_arrive(11, 256);
                    if (w4 == 3 && l16 < 32) mbar_arrive_cluster(mapa(bar + B_VF * 8, 2 * hh + (l16 >> 4)));
                }
                TSX(3, WG == 0 && w4 == 0);
            };
            if (!NOFILL && WG == 1) {
                token_output(s - 1, s > 0, [&]() { finish(); mbar_wait(bar + (B_P0 + ((s - 1) & 1)) * 8, ((s - 1) >> 1) & 1); });
                if (w4 == 1 && l16 == 0 && s > 0) mbar_expect(bar + (B_P0 + ((s - 1) & 1)) * 8, 2048);
                mbar_wait(bar + B_XF1 * 8, s == NSEG - 1);
            } else {
                finish();
            }
            if (WG == 0) bar_sync(11, 256);
            if (__builtin_expect(s == NSEG - 1, 0)) {
                bar_sync(6, 256);
                if (WG == 1) {
                    if (!NOFILL) token_output(s, true, [&]() { mbar_wait(bar + (B_P0 + (s & 1)) * 8, (s >> 1) & 1); });
                    bar_sync(2, 128);
                    if (w4 == 0 && l16 == 0) {
                        if (NOFILL) for (int i = 0; i < 15; i++) count_up(CNT_OX + i);
                        count_up(CNT_OX + 15);
                    }
                    __syncwarp();
                }
                mbar_wait(bar + B_SC * 8, s & 1);
                break;
            }
            if constexpr (WG == 0) {
                uint32_t vx[4][4], vm[4];
                load_values(vx, vm, s);
                const uint32_t oo = u_off + ((l16 & 48) << 3) + ((l16 >> 2) & 112);
                char* dst = reinterpret_cast<char*>(&g_xo[s & 3][0]) + oo;
                if (w4 == 3) load_tokens(s + 1, 1, 0);
                mbar_wait(bar + B_SC * 8, s & 1);
                TS(4);
                const float4 a0 = lds4f(sb + C_SL + l16), b0 = lds4f(sb + C_SL + 1280 + l16);
                const float4 a1 = lds4f(sb + C_SL + 512 + l16), b1 = lds4f(sb + C_SL + 1280 + 512 + l16);
                const float2 a2 = lds2f(sb + C_SL + 1024 + (l16 >> 1)), b2 = lds2f(sb + C_SL + 1280 + 1024 + (l16 >> 1));
                const float e[10] = {a0.x + b0.x, a0.y + b0.y, a0.z + b0.z, a0.w + b0.w, a1.x + b1.x, a1.y + b1.y, a1.z + b1.z, a1.w + b1.w,
                                     a2.x + b2.x, a2.y + b2.y};
                float m = fmaxf(fmaxf(fmaxf(e[0], e[1]), fmaxf(e[2], e[3])), fmaxf(fmaxf(e[4], e[5]), fmaxf(e[6], e[7])));
                m = fmaxf(m, fmaxf(e[8], e[9]));
                m = fmaxf(fmaxf(m, __shfl_xor_sync(~0u, m, 1)), fmaxf(__shfl_xor_sync(~0u, m, 2), __shfl_xor_sync(~0u, m, 3)));
                m *= -SM_SCALE;
                float x[10];
#pragma unroll
                for (int i = 0; i < 10; i++) x[i] = ex2(fmaf(e[i], SM_SCALE, m));
                float o[4][4];
                const uint32_t p0 = pack2(x[0], x[1]), p1 = pack2(x[2], x[3]), j0 = __float_as_uint(x[1]), j1 = __float_as_uint(x[3]);
#pragma unroll
                for (int j = 0; j < 4; j++) { o[j][0] = o[j][1] = o[j][2] = o[j][3] = 0.f; mma16(o[j], p0, j0, p1, j1, vx[j][0], vx[j][1]); }
                const uint32_t p2 = pack2(x[4], x[5]), p3 = pack2(x[6], x[7]), j2 = __float_as_uint(x[5]), j3 = __float_as_uint(x[7]);
#pragma unroll
                for (int j = 0; j < 4; j++) mma16(o[j], p2, j2, p3, j3, vx[j][2], vx[j][3]);
                const uint32_t p4 = pack2(x[8], x[9]), j4 = __float_as_uint(x[9]);
                float l = (((x[0] + x[1]) + (x[2] + x[3])) + ((x[4] + x[5]) + (x[6] + x[7]))) + (x[8] + x[9]);
                l = (l + __shfl_xor_sync(~0u, l, 1)) + (__shfl_xor_sync(~0u, l, 2) + __shfl_xor_sync(~0u, l, 3));
#pragma unroll
                for (int j = 0; j < 4; j++) mma8(o[j], p4, j4, vm[j]);
                l = rcp(l);
                st_relaxed4(reinterpret_cast<uint4*>(dst), make_uint4(pack2(o[0][0] * l, o[0][1] * l), pack2(o[1][0] * l, o[1][1] * l),
                                                                      pack2(o[2][0] * l, o[2][1] * l), pack2(o[3][0] * l, o[3][1] * l)));
                bar_arrive(3, 256);
                st_relaxed4(reinterpret_cast<uint4*>(reinterpret_cast<char*>(&g_xo[(s + 2) & 3][0]) + oo), make_uint4(~0u, ~0u, ~0u, ~0u));
                if (w4 == 0 && l16 == 0) mbar_expect(bar + B_SC * 8, 2560);
            }
        }
        windows(ic<0>{});
    }
}

__global__ void __cluster_dims__(6, 1, 1) __launch_bounds__(256, 1)
chain_kernel(const __grid_constant__ CUtensorMap tq, const __grid_constant__ CUtensorMap tk, const __grid_constant__ CUtensorMap tv,
             const __grid_constant__ CUtensorMap two, const __grid_constant__ Descs D, const __grid_constant__ Descs DV) {
    extern __shared__ __align__(1024) uint8_t smem[];
    const uint32_t sb = smem_u32(smem);
    const int rank = blockIdx.x % 6, cl = blockIdx.x / 6, role = rank >= 4 ? 2 : rank & 1;
    if (threadIdx.x == 0) {
        if ((sb & 0x3FFFF) != SB0) __trap();
        const uint32_t bar = sb + C_BAR;
        for (int i = 0; i < B_NUM; i++) mbar_init(bar + i * 8, i == B_MBF ? 12 : 1);
        mbar_expect(bar + B_MF0 * 8, 8192);
        mbar_expect(bar + B_MF1 * 8, 8192);
        if (role == 2) {
            mbar_expect(bar + B_SC * 8, 2560);
            mbar_expect(bar + B_P0 * 8, 2048);
            mbar_expect(bar + B_P1 * 8, 2048);
            mbar_expect(bar + B_OF * 8, ONKV * 256);
        } else {
            mbar_expect(bar + B_XS * 8, role ? 5120 : 3072);
            mbar_expect(bar + B_OL * 8, 3072);
            mbar_expect(bar + B_OF * 8, ONKQ * 256);
        }
        asm volatile("fence.mbarrier_init.release.cluster;" ::: "memory");
        fence_async();
    }
    __syncthreads();
    cluster_sync();
    const int wg = uni(threadIdx.x >> 7);
    if (role == 2) {
        if (wg == 0) chain_main<true, 0>(&tv, &tv, &two, sb, cl, rank, DV);
        else chain_main<true, 1>(&tv, &tv, &two, sb, cl, rank, DV);
    } else {
        if (wg == 0) chain_main<false, 0>(&tq, &tk, &two, sb, cl, rank, D);
        else chain_main<false, 1>(&tq, &tk, &two, sb, cl, rank, D);
    }
    __syncwarp();
    cluster_sync();
}

__device__ __forceinline__ void wg256(float* d, uint32_t da, uint32_t db, uint32_t accum) {
    asm volatile("{\n.reg .b64 da, db;\n.reg .pred p;\nsetp.ne.u32 p, %130, 0;\nmov.b64 da, {%128, " DESC_HI_SW128 "};\nmov.b64 db, {%129, " DESC_HI_SW128 "};\n"
                 "wgmma.mma_async.sync.aligned.m64n256k16.f32.bf16.bf16 {"
                 "%0,%1,%2,%3,%4,%5,%6,%7,%8,%9,%10,%11,%12,%13,%14,%15,%16,%17,%18,%19,%20,%21,%22,%23,%24,%25,%26,%27,%28,%29,%30,%31,"
                 "%32,%33,%34,%35,%36,%37,%38,%39,%40,%41,%42,%43,%44,%45,%46,%47,%48,%49,%50,%51,%52,%53,%54,%55,%56,%57,%58,%59,%60,%61,%62,%63,"
                 "%64,%65,%66,%67,%68,%69,%70,%71,%72,%73,%74,%75,%76,%77,%78,%79,%80,%81,%82,%83,%84,%85,%86,%87,%88,%89,%90,%91,%92,%93,%94,%95,"
                 "%96,%97,%98,%99,%100,%101,%102,%103,%104,%105,%106,%107,%108,%109,%110,%111,%112,%113,%114,%115,%116,%117,%118,%119,%120,%121,%122,%123,%124,%125,%126,%127"
                 "}, da, db, p, 1, 1, 0, 1;\n}"
                 : ACC16(d), ACC16((d + 16)), ACC16((d + 32)), ACC16((d + 48)), ACC16((d + 64)), ACC16((d + 80)), ACC16((d + 96)), ACC16((d + 112))
                 : "r"(da), "r"(db), "r"(accum));
}
__device__ __forceinline__ void wg128(float* d, uint32_t da, uint32_t db, uint32_t accum) {
    asm volatile("{\n.reg .b64 da, db;\n.reg .pred p;\nsetp.ne.u32 p, %66, 0;\nmov.b64 da, {%64, " DESC_HI_SW128 "};\nmov.b64 db, {%65, " DESC_HI_SW128 "};\n"
                 "wgmma.mma_async.sync.aligned.m64n128k16.f32.bf16.bf16 {"
                 "%0,%1,%2,%3,%4,%5,%6,%7,%8,%9,%10,%11,%12,%13,%14,%15,%16,%17,%18,%19,%20,%21,%22,%23,%24,%25,%26,%27,%28,%29,%30,%31,"
                 "%32,%33,%34,%35,%36,%37,%38,%39,%40,%41,%42,%43,%44,%45,%46,%47,%48,%49,%50,%51,%52,%53,%54,%55,%56,%57,%58,%59,%60,%61,%62,%63"
                 "}, da, db, p, 1, 1, 0, 1;\n}"
                 : ACC16(d), ACC16((d + 16)), ACC16((d + 32)), ACC16((d + 48))
                 : "r"(da), "r"(db), "r"(accum));
}
__device__ __forceinline__ float sigmoidf_(float v) { return rcp(1.f + ex2(-1.4426950408889634f * v)); }
__device__ __forceinline__ void wait_count(int idx, uint32_t n) {
    uint32_t v, it = 0;
    while (true) {
        asm volatile("ld.acquire.gpu.global.u32 %0, [%1];" : "=r"(v) : "l"(&g_cnt[idx * 8]) : "memory");
        if (v >= n) break;
        __nanosleep(100);
        spin_guard(it);
    }
    asm volatile("fence.proxy.async.global;" ::: "memory");
}

constexpr int G_STAGES = 4, G_PAIRS = 18;
constexpr uint32_t G_STAGE = 49152, G_EPI = G_STAGES * G_STAGE, G_BAR = G_EPI + 32768, G_SMEM = G_BAR + 256;
__device__ __forceinline__ int glu_job(int p, int j) {
    if (j < 12) return j * G_PAIRS + p;
    if (p < 14) return j == 12 ? 224 + p : (j == 13 ? 242 + p : -1);
    return j < 14 ? 216 + (j - 12) * 4 + (p - 14) : (j == 14 ? 224 + p : -1);
}

__global__ void __cluster_dims__(2, 1, 1) __launch_bounds__(384, 1)
glu_kernel(const __grid_constant__ CUtensorMap tXn, const __grid_constant__ CUtensorMap tG, const __grid_constant__ CUtensorMap tU,
           const __grid_constant__ CUtensorMap tHst, const __grid_constant__ CUtensorMap tHld, const __grid_constant__ CUtensorMap tD,
           const __grid_constant__ CUtensorMap tYst) {
    extern __shared__ __align__(1024) uint8_t smem[];
    const uint32_t sb = smem_u32(smem);
    const uint32_t full = sb + G_BAR, empty = full + 64;
    const int tid = threadIdx.x, lane = tid & 31;
    const int warp = uni(tid >> 5), wg = warp >> 2;
    const int rank = blockIdx.x & 1, pair = blockIdx.x >> 1;
    asm volatile("griddepcontrol.launch_dependents;" ::: "memory");
    if (tid == 0) {
        for (int i = 0; i < G_STAGES; i++) { mbar_init(full + i * 8, 1); mbar_init(empty + i * 8, 16); }
        asm volatile("fence.mbarrier_init.release.cluster;" ::: "memory");
        fence_async();
    }
    __syncthreads();
    cluster_sync();
    if (wg == 0) {
        asm volatile("setmaxnreg.dec.sync.aligned.u32 40;");
        if (warp == 0) {
            if (lane == 0) {
                uint32_t st = 0, ph = 1;
                for (int j = 0, job; (job = glu_job(pair, j)) >= 0; j++) {
                    const bool dn = job >= 224;
                    const int mp = dn ? (job - 224) >> 2 : job / 28, nt = dn ? job & 3 : job % 28, rb = mp * 2 + rank;
                    const CUtensorMap* tA = dn ? &tHld : &tXn;
                    const CUtensorMap* tB = dn ? &tD : (rank ? &tU : &tG);
                    const int bcol = dn ? nt * 256 + rank * 128 : nt * 128, nkb = dn ? FF / 64 : DM / 64;
                    if (dn) wait_count(CNT_H + rb, 56);
                    for (int kb = 0; kb < nkb; kb++) {
                        mbar_wait(empty + st * 8, ph);
                        const uint32_t base = sb + st * G_STAGE;
                        mbar_expect(full + st * 8, G_STAGE);
                        tma2d(base, tA, kb * 64, rb * 128, full + st * 8);
                        tma2d_mc(base + 16384 + rank * 16384, tB, bcol, kb * 64, full + st * 8, 3);
                        tma2d_mc(base + 16384 + rank * 16384 + 8192, tB, bcol + 64, kb * 64, full + st * 8, 3);
                        if (++st == G_STAGES) { st = 0; ph ^= 1; }
                    }
                }
            }
        } else if (warp < 3) {
            const int cw = warp - 1;
            const uint32_t epi = sb + G_EPI + cw * 16384;
            bar_arrive(3 + cw, 160);
            for (int j = 0, job; (job = glu_job(pair, j)) >= 0; j++) {
                const bool dn = job >= 224;
                const int mp = dn ? (job - 224) >> 2 : job / 28, nt = dn ? job & 3 : job % 28, rb = mp * 2 + rank;
                for (int hp = 0; hp <= (int)dn; hp++) {
                    bar_sync(1 + cw, 160);
                    if (lane == 0) {
                        const int col = dn ? nt * 256 + hp * 128 : nt * 128;
                        tma2d_store(dn ? &tYst : &tHst, col, rb * 128 + cw * 64, epi);
                        tma2d_store(dn ? &tYst : &tHst, col + 64, rb * 128 + cw * 64, epi + 8192);
                        asm volatile("cp.async.bulk.commit_group;\ncp.async.bulk.wait_group.read 0;" ::: "memory");
                    }
                    __syncwarp();
                    bar_arrive(3 + cw, 160);
                    if (lane == 0) {
                        asm volatile("cp.async.bulk.wait_group 0;\nfence.proxy.async.global;" ::: "memory");
                        count_up(dn ? CNT_Y + rb * 8 + nt * 2 + hp : CNT_H + rb);
                    }
                    __syncwarp();
                }
            }
        }
        cluster_sync();
    } else {
        asm volatile("setmaxnreg.inc.sync.aligned.u32 232;");
        const int cw = wg - 1, w4 = warp & 3;
        const uint32_t empty_dst = mapa(empty, lane & 1);
        const int er = w4 * 16 + (lane & 15), ec = lane >> 4;
        const uint32_t epi = sb + G_EPI + cw * 16384 + er * 128;
        uint32_t st = 0, ph = 0;
        float acc[128];
        auto put = [&](const uint32_t* o) {
            bar_sync(3 + cw, 160);
#pragma unroll
            for (int q = 0; q < 8; q++) stsm4(epi + (q >> 2) * 8192 + (((2 * (q & 3) + ec) ^ (er & 7)) << 4), o[q * 4], o[q * 4 + 1], o[q * 4 + 2], o[q * 4 + 3]);
            fence_async();
            bar_arrive(1 + cw, 160);
        };
        for (int j = 0, job; (job = glu_job(pair, j)) >= 0; j++) {
            const bool dn = job >= 224;
            const int nkb = dn ? FF / 64 : DM / 64;
            uint32_t prev = 0;
#pragma unroll 1
            for (int kb = 0; kb < nkb; kb++) {
                mbar_wait(full + st * 8, ph);
                const uint32_t base = sb + st * G_STAGE;
                const uint32_t da = (((base + cw * 8192) & 0x3FFFF) >> 4) | (1u << 16);
                const uint32_t db = (((base + 16384) & 0x3FFFF) >> 4) | (512u << 16);
                wg_fence();
#pragma unroll
                for (int k = 0; k < 4; k++) wg256(acc, da + k * 2, db + k * 128, (kb | k) != 0);
                wg_commit();
                if (kb > 0) {
                    wg_wait<1>();
                    if (lane < 2) mbar_arrive_cluster(empty_dst + prev * 8);
                }
                prev = st;
                if (++st == G_STAGES) { st = 0; ph ^= 1; }
            }
            wg_wait<0>();
            reg_fence<128>(acc);
            if (lane < 2) mbar_arrive_cluster(empty_dst + prev * 8);
            uint32_t o[32];
            if (!dn) {
#pragma unroll
                for (int i = 0; i < 32; i++) o[i] = pack2(sigmoidf_(acc[2 * i]) * acc[64 + 2 * i], sigmoidf_(acc[2 * i + 1]) * acc[65 + 2 * i]);
                put(o);
            } else {
#pragma unroll
                for (int hp = 0; hp < 2; hp++) {
#pragma unroll
                    for (int i = 0; i < 32; i++) {
                        const float a = acc[hp * 64 + 2 * i], b = acc[hp * 64 + 2 * i + 1];
                        o[i] = pack2(sigmoidf_(a) * a, sigmoidf_(b) * b);
                    }
                    put(o);
                }
            }
        }
        bar_sync(3 + cw, 160);
        cluster_sync();
    }
}

constexpr int O_STAGES = 7;
constexpr uint32_t O_STAGE = 32768, O_BAR = O_STAGES * O_STAGE, O_SMEM = O_BAR + 256;

__global__ void __cluster_dims__(2, 1, 1) __launch_bounds__(384, 1)
out_kernel(const __grid_constant__ CUtensorMap tOx, const __grid_constant__ CUtensorMap tWo, const __grid_constant__ CUtensorMap tX,
           const __grid_constant__ CUtensorMap tY, const __grid_constant__ CUtensorMap tOut) {
    extern __shared__ __align__(1024) uint8_t smem[];
    const uint32_t sb = smem_u32(smem);
    const uint32_t full = sb + O_BAR, empty = full + 64;
    const int tid = threadIdx.x, lane = tid & 31;
    const int warp = uni(tid >> 5), wg = warp >> 2;
    const int rank = blockIdx.x & 1, nt = (blockIdx.x >> 1) & 7, rb = (blockIdx.x >> 4) * 2 + rank;
    constexpr int NKB = HD / 64;
    if (tid == 0) {
        for (int i = 0; i < O_STAGES; i++) { mbar_init(full + i * 8, 1); mbar_init(empty + i * 8, 16); }
        asm volatile("fence.mbarrier_init.release.cluster;" ::: "memory");
        fence_async();
    }
    __syncthreads();
    cluster_sync();
    if (wg == 0) {
        if (tid == 0) {
            uint32_t st = 0, ph = 1;
            for (int kb = 0; kb < O_STAGES; kb++) {
                mbar_expect(full + kb * 8, O_STAGE);
                tma2d_mc(sb + kb * O_STAGE + 16384 + rank * 8192, &tWo, nt * 128 + rank * 64, kb * 64, full + kb * 8, 3);
            }
            wait_count(CNT_OX + rb, 32);
            for (int kb = 0; kb < NKB + 2; kb++) {
                const uint32_t base = sb + st * O_STAGE;
                if (kb >= O_STAGES) {
                    mbar_wait(empty + st * 8, ph);
                    mbar_expect(full + st * 8, O_STAGE);
                }
                if (kb < NKB) {
                    tma2d(base, &tOx, kb * 64, rb * 128, full + st * 8);
                    if (kb >= O_STAGES) tma2d_mc(base + 16384 + rank * 8192, &tWo, nt * 128 + rank * 64, kb * 64, full + st * 8, 3);
                } else {
                    if (kb == NKB) wait_count(CNT_Y + rb * 8 + nt, 2);
                    tma2d(base, &tX, nt * 128 + (kb - NKB) * 64, rb * 128, full + st * 8);
                    tma2d(base + 16384, &tY, nt * 128 + (kb - NKB) * 64, rb * 128, full + st * 8);
                }
                if (++st == O_STAGES) { st = 0; ph ^= 1; }
            }
        }
        __syncwarp();
    } else {
        const int cw = wg - 1, w4 = warp & 3;
        const uint32_t empty_dst = mapa(empty, lane & 1);
        const int er = cw * 64 + w4 * 16 + (lane & 15), ec = lane >> 4;
        uint32_t st = 0, ph = 0, prev = 0;
        float acc[64];
#pragma unroll 1
        for (int kb = 0; kb < NKB; kb++) {
            mbar_wait(full + st * 8, ph);
            const uint32_t base = sb + st * O_STAGE;
            const uint32_t da = (((base + cw * 8192) & 0x3FFFF) >> 4) | (1u << 16);
            const uint32_t db = (((base + 16384) & 0x3FFFF) >> 4) | (512u << 16);
            wg_fence();
#pragma unroll
            for (int k = 0; k < 4; k++) wg128(acc, da + k * 2, db + k * 128, (kb | k) != 0);
            wg_commit();
            if (kb > 0) {
                wg_wait<1>();
                if (lane < 2) mbar_arrive_cluster(empty_dst + prev * 8);
            }
            prev = st;
            if (++st == O_STAGES) { st = 0; ph ^= 1; }
        }
        wg_wait<0>();
        reg_fence<64>(acc);
#pragma unroll
        for (int bx = 0; bx < 2; bx++) {
            mbar_wait(full + st * 8, ph);
            const uint32_t base = sb + st * O_STAGE;
#pragma unroll
            for (int j = 0; j < 4; j++) {
                uint32_t xv[4], yv[4];
                const uint32_t ad = base + er * 128 + (((2 * j + ec) ^ (er & 7)) << 4);
                ldsm4(xv, ad); ldsm4(yv, ad + 16384);
                const float* a = acc + bx * 32 + j * 8;
#pragma unroll
                for (int i = 0; i < 4; i++)
                    xv[i] = pack2(fmaf(a[2 * i], bf_lo(yv[i]), bf_lo(xv[i])), fmaf(a[2 * i + 1], bf_hi(yv[i]), bf_hi(xv[i])));
                stsm4(ad, xv[0], xv[1], xv[2], xv[3]);
            }
            fence_async();
            bar_sync(1 + cw, 128);
            if ((tid & 127) == 0) {
                tma2d_store(&tOut, nt * 128 + bx * 64, rb * 128 + cw * 64, base + cw * 8192);
                asm volatile("cp.async.bulk.commit_group;" ::: "memory");
            }
            if (++st == O_STAGES) { st = 0; ph ^= 1; }
        }
        if ((tid & 127) == 0) asm volatile("cp.async.bulk.wait_group 0;" ::: "memory");
        __syncwarp();
    }
    cluster_sync();
}

typedef CUresult (*EncodeFn)(CUtensorMap*, CUtensorMapDataType, cuuint32_t, void*, const cuuint64_t*, const cuuint64_t*, const cuuint32_t*,
                             const cuuint32_t*, CUtensorMapInterleave, CUtensorMapSwizzle, CUtensorMapL2promotion, CUtensorMapFloatOOBfill);

CUtensorMap make_map(EncodeFn enc, const void* p, int rows, int cols, int box_rows) {
    CUtensorMap m;
    cuuint64_t dims[2] = {(cuuint64_t)cols, (cuuint64_t)rows}, strides[1] = {(cuuint64_t)cols * 2};
    cuuint32_t box[2] = {64, (cuuint32_t)box_rows}, es[2] = {1, 1};
    enc(&m, CU_TENSOR_MAP_DATA_TYPE_BFLOAT16, 2, const_cast<void*>(p), dims, strides, box, es, CU_TENSOR_MAP_INTERLEAVE_NONE,
        CU_TENSOR_MAP_SWIZZLE_128B, CU_TENSOR_MAP_L2_PROMOTION_L2_128B, CU_TENSOR_MAP_FLOAT_OOB_FILL_NONE);
    return m;
}

}

#define PDL 7
extern "C" void kernel_launch(void* const* d_in, const int* in_sizes, int n_in, void* d_out, int out_size) {
    const __nv_bfloat16* x = (const __nv_bfloat16*)d_in[0];
    const __nv_bfloat16* mem0 = (const __nv_bfloat16*)d_in[1];
    void* fn = nullptr;
    cudaDriverEntryPointQueryResult qr;
    cudaGetDriverEntryPoint("cuTensorMapEncodeTiled", &fn, cudaEnableDefault, &qr);
    EncodeFn enc = (EncodeFn)fn;
    void *xn, *ox, *h, *y;
    cudaGetSymbolAddress(&xn, g_xn); cudaGetSymbolAddress(&ox, g_ox); cudaGetSymbolAddress(&h, g_h); cudaGetSymbolAddress(&y, g_y);

    const CUtensorMap tq = make_map(enc, d_in[2], DM, HD, 128), tk = make_map(enc, d_in[3], DM, HD, 128), tv = make_map(enc, d_in[4], DM, HD, 128);
    const CUtensorMap two16 = make_map(enc, d_in[5], HD, DM, 16);
    const CUtensorMap txn128 = make_map(enc, xn, SEQ, DM, 128), tg = make_map(enc, d_in[8], DM, FF, 64), tu = make_map(enc, d_in[9], DM, FF, 64);
    const CUtensorMap th64 = make_map(enc, h, SEQ, FF, 64), th128 = make_map(enc, h, SEQ, FF, 128), td = make_map(enc, d_in[10], FF, DM, 64);
    const CUtensorMap ty64 = make_map(enc, y, SEQ, DM, 64), ty128 = make_map(enc, y, SEQ, DM, 128), tx128 = make_map(enc, x, SEQ, DM, 128);
    const CUtensorMap tox = make_map(enc, ox, SEQ, HD, 128), two64 = make_map(enc, d_in[5], HD, DM, 64), tout = make_map(enc, d_out, SEQ, DM, 64);

    cudaFuncSetAttribute(chain_kernel, cudaFuncAttributeMaxDynamicSharedMemorySize, C_SMEM);
    cudaFuncSetAttribute(glu_kernel, cudaFuncAttributeMaxDynamicSharedMemorySize, G_SMEM);
    cudaFuncSetAttribute(out_kernel, cudaFuncAttributeMaxDynamicSharedMemorySize, O_SMEM);

    Descs D;
    for (int i = 0; i < 4; i++) D.sw[i] = DSW;
    D.ns = DNS;
    cudaStream_t st = cudaStreamPerThread;
    ln_kernel<<<SEQ / 8, 256, 0, st>>>(x, mem0);
    cudaLaunchAttribute at;
    at.id = cudaLaunchAttributeProgrammaticStreamSerialization;
    at.val.programmaticStreamSerializationAllowed = 1;
    cudaLaunchConfig_t cfg = {};
    cfg.stream = st; cfg.attrs = &at; cfg.numAttrs = PDL & 1;
    cfg.gridDim = dim3(96); cfg.blockDim = dim3(256); cfg.dynamicSmemBytes = C_SMEM;
    cudaLaunchKernelEx(&cfg, chain_kernel, tq, tk, tv, two16, D, D);
    cfg.gridDim = dim3(2 * G_PAIRS); cfg.blockDim = dim3(384); cfg.dynamicSmemBytes = G_SMEM; cfg.numAttrs = (PDL >> 1) & 1;
    cudaLaunchKernelEx(&cfg, glu_kernel, txn128, tg, tu, th64, th128, td, ty64);
    cfg.gridDim = dim3(128); cfg.dynamicSmemBytes = O_SMEM; cfg.numAttrs = (PDL >> 2) & 1;
    cudaLaunchKernelEx(&cfg, out_kernel, tox, two64, tx128, ty128, tout);
}
```

```cpp
#include <cuda_runtime.h>
#include <cuda_bf16.h>
#include <cuda.h>
#include <stdint.h>
#include <type_traits>

namespace {

constexpr int SEQ = 2048, DM = 1024, HD = 4096, FF = 3584, NSEG = 64;

__device__ __align__(1024) __nv_bfloat16 g_xn[SEQ * DM];
__device__ __align__(1024) uint4 g_xc[SEQ * DM / 8];
__device__ __align__(1024) __nv_bfloat16 g_ox[SEQ * HD];
__device__ __align__(1024) __nv_bfloat16 g_h[SEQ * FF];
__device__ __align__(1024) __nv_bfloat16 g_y[SEQ * DM];
__device__ __align__(1024) uint4 g_xmem[4][1024];
__device__ __align__(1024) uint4 g_xo[4][4096];
#define FSTR 8
__device__ __align__(1024) uint32_t g_flag[2][96 * FSTR];
enum { CNT_H = 0, CNT_OX = 16, CNT_Y = 32, CNT_NUM = 160 };
__device__ __align__(1024) uint32_t g_cnt[CNT_NUM * 8];
__device__ __align__(128) uint32_t g_epoch;
#define TL(k, i)
#define TLSM(k)

__device__ __forceinline__ uint32_t smem_u32(const void* p) { return (uint32_t)__cvta_generic_to_shared(p); }
__device__ __forceinline__ uint32_t mapa(uint32_t a, uint32_t r) {
    uint32_t o; asm("mapa.shared::cluster.u32 %0, %1, %2;" : "=r"(o) : "r"(a), "r"(r)); return o;
}
__device__ __forceinline__ void mbar_init(uint32_t a, uint32_t cnt) {
    asm volatile("mbarrier.init.shared.b64 [%0], %1;" :: "r"(a), "r"(cnt) : "memory");
}
__device__ __forceinline__ void mbar_expect(uint32_t a, uint32_t bytes) {
    asm volatile("mbarrier.arrive.expect_tx.shared.b64 _, [%0], %1;" :: "r"(a), "r"(bytes) : "memory");
}
__device__ __forceinline__ void mbar_arrive_cluster(uint32_t a) {
    asm volatile("mbarrier.arrive.shared::cluster.b64 _, [%0];" :: "r"(a) : "memory");
}
__device__ __forceinline__ void spin_guard(uint32_t& it) {
    asm volatile("{\n.reg .pred p;\nadd.u32 %0, %0, 1;\nsetp.gt.u32 p, %0, 0x400000;\n@p st.shared.u32 [%0], %0;\n}" : "+r"(it));
}
__device__ __forceinline__ void mbar_wait(uint32_t a, uint32_t par) {
    asm volatile("{\n.reg .pred p;\n.reg .u32 i;\nmov.u32 i, 0;\n"
                 "WL:\nadd.u32 i, i, 1;\nsetp.gt.u32 p, i, 0x400000;\n@p st.shared.u32 [i], i;\n"
                 "mbarrier.try_wait.parity.shared::cta.b64 p, [%0], %1;\n@!p bra WL;\n}" :: "r"(a), "r"(par) : "memory");
}
__device__ __forceinline__ void mbar_arrive(uint32_t a) { asm volatile("mbarrier.arrive.shared.b64 _, [%0];" :: "r"(a) : "memory"); }
__device__ __forceinline__ void tma2d(uint32_t dst, const CUtensorMap* m, int c0, int c1, uint32_t bar) {
    asm volatile("cp.async.bulk.tensor.2d.shared::cluster.global.mbarrier::complete_tx::bytes [%0], [%1, {%3, %4}], [%2];"
                 :: "r"(dst), "l"(m), "r"(bar), "r"(c0), "r"(c1) : "memory");
}
__device__ __forceinline__ void tma2d_mc(uint32_t dst, const CUtensorMap* m, int c0, int c1, uint32_t bar, uint16_t mask) {
    asm volatile("cp.async.bulk.tensor.2d.shared::cluster.global.mbarrier::complete_tx::bytes.multicast::cluster [%0], [%1, {%3, %4}], [%2], %5;"
                 :: "r"(dst), "l"(m), "r"(bar), "r"(c0), "r"(c1), "h"(mask) : "memory");
}
__device__ __forceinline__ void bulk_mc(uint32_t dst, const void* src, uint32_t bytes, uint32_t bar, uint16_t mask) {
    asm volatile("cp.async.bulk.shared::cluster.global.mbarrier::complete_tx::bytes.multicast::cluster [%0], [%1], %2, [%3], %4;"
                 :: "r"(dst), "l"(src), "r"(bytes), "r"(bar), "h"(mask) : "memory");
}
__device__ __forceinline__ void bulk_ld(uint32_t dst, const void* src, uint32_t bytes, uint32_t bar) {
    asm volatile("cp.async.bulk.shared::cluster.global.mbarrier::complete_tx::bytes [%0], [%1], %2, [%3];"
                 :: "r"(dst), "l"(src), "r"(bytes), "r"(bar) : "memory");
}
__device__ __forceinline__ uint32_t gtick() { uint64_t c; asm volatile("mov.u64 %0, %%globaltimer;" : "=l"(c)); return (uint32_t)c >> 5; }
__device__ __forceinline__ uint32_t gtick_dep(uint32_t zero) {
    uint32_t c;
    asm volatile("{\n.reg .pred p;\nsetp.eq.u32 p, %1, 0;\nmov.u32 %0, 0;\n@p mov.u32 %0, %%globaltimer_lo;\n}" : "=r"(c) : "r"(zero));
    return c >> 5;
}
__device__ __forceinline__ uint32_t ld_relaxed1(const void* p) {
    uint32_t v; asm volatile("ld.relaxed.gpu.global.u32 %0, [%1];" : "=r"(v) : "l"(p) : "memory"); return v;
}
__device__ __forceinline__ bool any_nan(float a, float b) {
    uint32_t r;
    asm volatile("{\n.reg .pred p;\nsetp.nan.f32 p, %1, %2;\nvote.sync.any.pred p, p, 0xffffffff;\nselp.u32 %0, 1, 0, p;\n}" : "=r"(r) : "f"(a), "f"(b));
    return r;
}
__device__ __forceinline__ bool any_nan_unless(float a, float b, uint32_t off) {
    uint32_t r;
    asm volatile("{\n.reg .pred p, q;\nsetp.ne.u32 q, %3, 0xffffffff;\nsetp.nan.and.f32 p, %1, %2, q;\nvote.sync.any.pred p, p, 0xffffffff;\nselp.u32 %0, 1, 0, p;\n}"
                 : "=r"(r) : "f"(a), "f"(b), "r"(off));
    return r;
}
__device__ __forceinline__ bool st_async4_unless_nan(uint32_t a, uint32_t bar, const float* v) {
    uint32_t r;
    asm volatile("{\n.reg .pred p;\nsetp.nan.f32 p, %3, %4;\nvote.sync.any.pred p, p, 0xffffffff;\n"
                 "@!p st.async.shared::cluster.mbarrier::complete_tx::bytes.v4.f32 [%1], {%3,%4,%5,%6}, [%2];\nselp.u32 %0, 1, 0, p;\n}"
                 : "=r"(r) : "r"(a), "r"(bar), "f"(v[0]), "f"(v[1]), "f"(v[2]), "f"(v[3]) : "memory");
    return r;
}
__device__ __forceinline__ void bar_arrive(int id, int n) { asm volatile("bar.arrive %0, %1;" :: "r"(id), "r"(n) : "memory"); }
__device__ __forceinline__ uint32_t clk() { uint64_t c; asm volatile("mov.u64 %0, %%clock64;" : "=l"(c)); return (uint32_t)c; }
__device__ __forceinline__ void tma2d_store(const CUtensorMap* m, int c0, int c1, uint32_t src) {
    asm volatile("cp.async.bulk.tensor.2d.global.shared::cta.bulk_group [%0, {%1, %2}], [%3];"
                 :: "l"(m), "r"(c0), "r"(c1), "r"(src) : "memory");
}
__device__ __forceinline__ void bar_sync(int id, int n) { asm volatile("bar.sync %0, %1;" :: "r"(id), "r"(n) : "memory"); }
__device__ __forceinline__ void fence_async() { asm volatile("fence.proxy.async.shared::cta;" ::: "memory"); }
__device__ __forceinline__ void cluster_sync() {
    asm volatile("barrier.cluster.arrive.release.aligned;\nbarrier.cluster.wait.acquire.aligned;" ::: "memory");
}
__device__ __forceinline__ void ldsm4(uint32_t* r, uint32_t a) {
    asm volatile("ldmatrix.sync.aligned.m8n8.x4.shared.b16 {%0,%1,%2,%3}, [%4];"
                 : "=r"(r[0]), "=r"(r[1]), "=r"(r[2]), "=r"(r[3]) : "r"(a) : "memory");
}
__device__ __forceinline__ void ldsm4t(uint32_t* r, uint32_t a) {
    asm volatile("ldmatrix.sync.aligned.m8n8.x4.trans.shared.b16 {%0,%1,%2,%3}, [%4];"
                 : "=r"(r[0]), "=r"(r[1]), "=r"(r[2]), "=r"(r[3]) : "r"(a) : "memory");
}
__device__ __forceinline__ void stsm4(uint32_t a, uint32_t r0, uint32_t r1, uint32_t r2, uint32_t r3) {
    asm volatile("stmatrix.sync.aligned.m8n8.x4.shared.b16 [%0], {%1,%2,%3,%4};" :: "r"(a), "r"(r0), "r"(r1), "r"(r2), "r"(r3) : "memory");
}
__device__ __forceinline__ void stsm4t(uint32_t a, uint32_t r0, uint32_t r1, uint32_t r2, uint32_t r3) {
    asm volatile("stmatrix.sync.aligned.m8n8.x4.trans.shared.b16 [%0], {%1,%2,%3,%4};" :: "r"(a), "r"(r0), "r"(r1), "r"(r2), "r"(r3) : "memory");
}
__device__ __forceinline__ void stsm2(uint32_t a, uint32_t r0, uint32_t r1) {
    asm volatile("stmatrix.sync.aligned.m8n8.x2.shared.b16 [%0], {%1,%2};" :: "r"(a), "r"(r0), "r"(r1) : "memory");
}
__device__ __forceinline__ void stsm2t(uint32_t a, uint32_t r0, uint32_t r1) {
    asm volatile("stmatrix.sync.aligned.m8n8.x2.trans.shared.b16 [%0], {%1,%2};" :: "r"(a), "r"(r0), "r"(r1) : "memory");
}
__device__ __forceinline__ uint32_t movm(uint32_t a) {
    uint32_t d; asm volatile("movmatrix.sync.aligned.m8n8.trans.b16 %0, %1;" : "=r"(d) : "r"(a)); return d;
}
__device__ __forceinline__ void mma16(float* d, uint32_t a0, uint32_t a1, uint32_t a2, uint32_t a3, uint32_t b0, uint32_t b1) {
    asm volatile("mma.sync.aligned.m16n8k16.row.col.f32.bf16.bf16.f32 {%0,%1,%2,%3}, {%4,%5,%6,%7}, {%8,%9}, {%0,%1,%2,%3};"
                 : "+f"(d[0]), "+f"(d[1]), "+f"(d[2]), "+f"(d[3]) : "r"(a0), "r"(a1), "r"(a2), "r"(a3), "r"(b0), "r"(b1));
}
__device__ __forceinline__ void mma8(float* d, uint32_t a0, uint32_t a1, uint32_t b0) {
    asm volatile("mma.sync.aligned.m16n8k8.row.col.f32.bf16.bf16.f32 {%0,%1,%2,%3}, {%4,%5}, {%6}, {%0,%1,%2,%3};"
                 : "+f"(d[0]), "+f"(d[1]), "+f"(d[2]), "+f"(d[3]) : "r"(a0), "r"(a1), "r"(b0));
}
__device__ __forceinline__ uint32_t pack2(float lo, float hi) {
    uint32_t r; asm("cvt.rn.bf16x2.f32 %0, %1, %2;" : "=r"(r) : "f"(hi), "f"(lo)); return r;
}
__device__ __forceinline__ float bf_lo(uint32_t v) { return __uint_as_float(v << 16); }
__device__ __forceinline__ float bf_hi(uint32_t v) { return __uint_as_float(v & 0xFFFF0000u); }
__device__ __forceinline__ float ex2(float x) { float y; asm("ex2.approx.ftz.f32 %0, %1;" : "=f"(y) : "f"(x)); return y; }
__device__ __forceinline__ float rcp(float x) { float y; asm("rcp.approx.ftz.f32 %0, %1;" : "=f"(y) : "f"(x)); return y; }
__device__ __forceinline__ void sts4f(uint32_t a, float x, float y, float z, float w) {
    asm volatile("st.shared.v4.f32 [%0], {%1,%2,%3,%4};" :: "r"(a), "f"(x), "f"(y), "f"(z), "f"(w) : "memory");
}
__device__ __forceinline__ void sts1u(uint32_t a, uint32_t v) { asm volatile("st.shared.u32 [%0], %1;" :: "r"(a), "r"(v) : "memory"); }
__device__ __forceinline__ void sts4u(uint32_t a, uint4 v) {
    asm volatile("st.shared.v4.u32 [%0], {%1,%2,%3,%4};" :: "r"(a), "r"(v.x), "r"(v.y), "r"(v.z), "r"(v.w) : "memory");
}
__device__ __forceinline__ float4 lds4f(uint32_t a) {
    float4 v; asm volatile("ld.shared.v4.f32 {%0,%1,%2,%3}, [%4];" : "=f"(v.x), "=f"(v.y), "=f"(v.z), "=f"(v.w) : "r"(a) : "memory"); return v;
}
__device__ __forceinline__ float2 lds2f(uint32_t a) {
    float2 v; asm volatile("ld.shared.v2.f32 {%0,%1}, [%2];" : "=f"(v.x), "=f"(v.y) : "r"(a) : "memory"); return v;
}
__device__ __forceinline__ uint4 lds4u(uint32_t a) {
    uint4 v; asm volatile("ld.shared.v4.u32 {%0,%1,%2,%3}, [%4];" : "=r"(v.x), "=r"(v.y), "=r"(v.z), "=r"(v.w) : "r"(a) : "memory"); return v;
}
__device__ __forceinline__ uint32_t lds1u(uint32_t a) {
    uint32_t v; asm volatile("ld.shared.u32 %0, [%1];" : "=r"(v) : "r"(a) : "memory"); return v;
}
__device__ __forceinline__ uint2 lds2u(uint32_t a) {
    uint2 v; asm volatile("ld.shared.v2.u32 {%0,%1}, [%2];" : "=r"(v.x), "=r"(v.y) : "r"(a) : "memory"); return v;
}
__device__ __forceinline__ void st_async4(uint32_t a, uint32_t bar, uint32_t x, uint32_t y, uint32_t z, uint32_t w) {
    asm volatile("st.async.shared::cluster.mbarrier::complete_tx::bytes.v4.b32 [%0], {%1,%2,%3,%4}, [%5];"
                 :: "r"(a), "r"(x), "r"(y), "r"(z), "r"(w), "r"(bar) : "memory");
}
__device__ __forceinline__ void st_async2(uint32_t a, uint32_t bar, uint32_t x, uint32_t y) {
    asm volatile("st.async.shared::cluster.mbarrier::complete_tx::bytes.v2.b32 [%0], {%1,%2}, [%3];"
                 :: "r"(a), "r"(x), "r"(y), "r"(bar) : "memory");
}
__device__ __forceinline__ void st_async1(uint32_t a, uint32_t bar, uint32_t x) {
    asm volatile("st.async.shared::cluster.mbarrier::complete_tx::bytes.b32 [%0], %1, [%2];" :: "r"(a), "r"(x), "r"(bar) : "memory");
}
__device__ __forceinline__ uint4 ld_relaxed4(const uint4* p) {
    uint4 v;
    asm volatile("ld.relaxed.gpu.global.v4.u32 {%0,%1,%2,%3}, [%4];" : "=r"(v.x), "=r"(v.y), "=r"(v.z), "=r"(v.w) : "l"(p) : "memory");
    return v;
}
__device__ __forceinline__ void st_relaxed4(uint4* p, uint4 v) {
    asm volatile("st.relaxed.gpu.global.v4.u32 [%0], {%1,%2,%3,%4};" :: "l"(p), "r"(v.x), "r"(v.y), "r"(v.z), "r"(v.w) : "memory");
}
__device__ __forceinline__ void count_up(int idx) {
    asm volatile("red.release.gpu.global.add.u32 [%0], 1;" :: "l"(&g_cnt[idx * 8]) : "memory");
}
__device__ __forceinline__ void st_pred1(void* p, uint32_t v, bool on) {
    asm volatile("{\n.reg .pred p;\nsetp.ne.u32 p, %2, 0;\n@p st.relaxed.gpu.global.u32 [%0], %1;\n}" :: "l"(p), "r"(v), "r"((uint32_t)on) : "memory");
}
__device__ __forceinline__ void st_pred4(void* p, uint4 v, bool on) {
    asm volatile("{\n.reg .pred p;\nsetp.ne.u32 p, %5, 0;\n@p st.global.v4.u32 [%0], {%1,%2,%3,%4};\n}"
                 :: "l"(p), "r"(v.x), "r"(v.y), "r"(v.z), "r"(v.w), "r"((uint32_t)on) : "memory");
}
__device__ __forceinline__ void st_relaxed1(void* p, uint32_t v) {
    asm volatile("st.relaxed.gpu.global.u32 [%0], %1;" :: "l"(p), "r"(v) : "memory");
}
__device__ __forceinline__ uint32_t umax4(uint4 v) { return max(max(v.x, v.y), max(v.z, v.w)); }
__device__ __forceinline__ void wg_fence() { asm volatile("wgmma.fence.sync.aligned;" ::: "memory"); }
__device__ __forceinline__ void wg_commit() { asm volatile("wgmma.commit_group.sync.aligned;" ::: "memory"); }
template <int N> __device__ __forceinline__ void wg_wait() { asm volatile("wgmma.wait_group.sync.aligned %0;" :: "n"(N) : "memory"); }
template <int N> __device__ __forceinline__ void reg_fence(float* d) {
#pragma unroll
    for (int i = 0; i < N; i++) asm volatile("" : "+f"(d[i]) :: "memory");
}
#define ACC16(d) "+f"(d[0]), "+f"(d[1]), "+f"(d[2]), "+f"(d[3]), "+f"(d[4]), "+f"(d[5]), "+f"(d[6]), "+f"(d[7]), \
                 "+f"(d[8]), "+f"(d[9]), "+f"(d[10]), "+f"(d[11]), "+f"(d[12]), "+f"(d[13]), "+f"(d[14]), "+f"(d[15])
#define DESC_HI_SW128 "0x40000040"
#define OUT16(d) "=f"(d[0]), "=f"(d[1]), "=f"(d[2]), "=f"(d[3]), "=f"(d[4]), "=f"(d[5]), "=f"(d[6]), "=f"(d[7]), \
                 "=f"(d[8]), "=f"(d[9]), "=f"(d[10]), "=f"(d[11]), "=f"(d[12]), "=f"(d[13]), "=f"(d[14]), "=f"(d[15])
template <int ACCUM, int BOFF>
__device__ __forceinline__ void wg32_rs(float* d, const uint32_t* a, uint64_t dsw) {
    if (ACCUM)
        asm volatile("{\n.reg .b64 db;\nadd.s64 db, %20, %21;\n"
                     "wgmma.mma_async.sync.aligned.m64n32k16.f32.bf16.bf16 {%0,%1,%2,%3,%4,%5,%6,%7,%8,%9,%10,%11,%12,%13,%14,%15}, "
                     "{%16,%17,%18,%19}, db, 1, 1, 1, 0;\n}"
                     : ACC16(d) : "r"(a[0]), "r"(a[1]), "r"(a[2]), "r"(a[3]), "l"(dsw), "n"(BOFF));
    else
        asm volatile("{\n.reg .b64 db;\nadd.s64 db, %20, %21;\n"
                     "wgmma.mma_async.sync.aligned.m64n32k16.f32.bf16.bf16 {%0,%1,%2,%3,%4,%5,%6,%7,%8,%9,%10,%11,%12,%13,%14,%15}, "
                     "{%16,%17,%18,%19}, db, 0, 1, 1, 0;\n}"
                     : OUT16(d) : "r"(a[0]), "r"(a[1]), "r"(a[2]), "r"(a[3]), "l"(dsw), "n"(BOFF));
}
template <int AOFF, int BOFF>
__device__ __forceinline__ void wg32_ss(float* d, uint64_t dsw) {
    asm volatile("{\n.reg .b64 da, db;\nadd.s64 da, %16, %17;\nadd.s64 db, %16, %18;\n"
                 "wgmma.mma_async.sync.aligned.m64n32k16.f32.bf16.bf16 {%0,%1,%2,%3,%4,%5,%6,%7,%8,%9,%10,%11,%12,%13,%14,%15}, "
                 "da, db, 1, 1, 1, 1, 0;\n}"
                 : ACC16(d) : "l"(dsw), "n"(AOFF), "n"(BOFF));
}
template <int ACCUM, int AOFF, int BOFF>
__device__ __forceinline__ void wg8_ss(float* d, uint64_t dsw, uint64_t dns) {
    if (!ACCUM)
        asm volatile("{\n.reg .b64 da, db;\nadd.s64 da, %4, %6;\nadd.s64 db, %5, %7;\n"
                     "wgmma.mma_async.sync.aligned.m64n8k16.f32.bf16.bf16 {%0,%1,%2,%3}, da, db, 0, 1, 1, 1, 0;\n}"
                     : "=f"(d[0]), "=f"(d[1]), "=f"(d[2]), "=f"(d[3]) : "l"(dsw), "l"(dns), "n"(AOFF), "n"(BOFF));
    else
        asm volatile("{\n.reg .b64 da, db;\nadd.s64 da, %4, %6;\nadd.s64 db, %5, %7;\n"
                     "wgmma.mma_async.sync.aligned.m64n8k16.f32.bf16.bf16 {%0,%1,%2,%3}, da, db, 1, 1, 1, 1, 0;\n}"
                     : "+f"(d[0]), "+f"(d[1]), "+f"(d[2]), "+f"(d[3]) : "l"(dsw), "l"(dns), "n"(AOFF), "n"(BOFF));
}
template <int I0, int I1, class F>
__device__ __forceinline__ void static_for(F&& f) {
    if constexpr (I0 < I1) { f(std::integral_constant<int, I0>{}); static_for<I0 + 1, I1>(f); }
}
template <int I0, int I1, int AOFF, int BOFF>
__device__ __forceinline__ void wg8_chain(float* d, uint64_t dsw, uint64_t dns) {
    wg_fence();
    static_for<I0, I1>([&](auto i) { wg8_ss<i.value != 0, AOFF + i.value * 128, BOFF + i.value * 16>(d, dsw, dns); });
    wg_commit();
}

__device__ __forceinline__ void ln_row(const uint4* v, int row, int lane) {
    float f[32];
#pragma unroll
    for (int j = 0; j < 4; j++) {
        f[j * 8 + 0] = bf_lo(v[j].x); f[j * 8 + 1] = bf_hi(v[j].x); f[j * 8 + 2] = bf_lo(v[j].y); f[j * 8 + 3] = bf_hi(v[j].y);
        f[j * 8 + 4] = bf_lo(v[j].z); f[j * 8 + 5] = bf_hi(v[j].z); f[j * 8 + 6] = bf_lo(v[j].w); f[j * 8 + 7] = bf_hi(v[j].w);
    }
    float s = 0.f;
#pragma unroll
    for (int i = 0; i < 32; i++) s += f[i];
#pragma unroll
    for (int o = 16; o; o >>= 1) s += __shfl_xor_sync(~0u, s, o);
    const float mean = s * (1.f / DM);
    float q = 0.f;
#pragma unroll
    for (int i = 0; i < 32; i++) { f[i] -= mean; q += f[i] * f[i]; }
#pragma unroll
    for (int o = 16; o; o >>= 1) q += __shfl_xor_sync(~0u, q, o);
    const float r = 1.f / sqrtf(q * (1.f / DM) + 1e-5f);
    uint4* dst = reinterpret_cast<uint4*>(g_xn + (size_t)row * DM);
    uint4* dst2 = g_xc + (row >> 5) * 4096 + (lane >> 3) * 256 + (row & 31) * 8 + ((lane & 7) ^ (row & 7));
#pragma unroll
    for (int j = 0; j < 4; j++) {
        const uint4 o = make_uint4(pack2(f[j * 8] * r, f[j * 8 + 1] * r), pack2(f[j * 8 + 2] * r, f[j * 8 + 3] * r),
                                   pack2(f[j * 8 + 4] * r, f[j * 8 + 5] * r), pack2(f[j * 8 + 6] * r, f[j * 8 + 7] * r));
        dst[j * 32 + lane] = o;
        dst2[(j & 1) * 2048 + (j >> 1) * 1024] = o;
    }
}
__device__ __forceinline__ void reset_exchange(const __nv_bfloat16* __restrict__ mem0) {
    const int gi = blockIdx.x * 256 + threadIdx.x;
    const uint4 poison = make_uint4(~0u, ~0u, ~0u, ~0u);
    if (gi < 1024) {
        uint4 m = reinterpret_cast<const uint4*>(mem0)[(gi & 7) * 128 + (gi >> 3)];
        if (m.x == ~0u) m.x = 0x7FFF7FFFu;
        if (m.y == ~0u) m.y = 0x7FFF7FFFu;
        if (m.z == ~0u) m.z = 0x7FFF7FFFu;
        if (m.w == ~0u) m.w = 0x7FFF7FFFu;
        g_xmem[0][gi] = m;
    } else if (gi < 4096) {
        (&g_xmem[0][0])[gi] = poison;
    } else if (gi < 4096 + 16384) {
        (&g_xo[0][0])[gi - 4096] = poison;
    } else if (gi < 4096 + 16384 + 48 * FSTR) {
        reinterpret_cast<uint4*>(&g_flag[0][0])[gi - 4096 - 16384] = poison;
    } else if (gi >= 24576 - CNT_NUM) {
        g_cnt[(24575 - gi) * 8] = 0;
    }
}

#define ONKQ 45
constexpr int ONKV = 128 - 2 * ONKQ;
constexpr uint32_t SB0 = 1024;
constexpr uint32_t C_WS = 0, C_XN = 65536, C_MB = 98304, C_WO = 114688, C_SMEM = 232448;
constexpr uint32_t C_BAR = C_SMEM - 384, C_CAL = C_BAR + 192;
constexpr uint32_t C_SLOTQ = C_WO + ONKQ * 2048, C_QX = C_SLOTQ + 8192, C_KX = C_QX + 4096,
                   C_XSL = C_KX + 4096, C_OL = C_XSL + 5120;
constexpr uint32_t C_SLOTV = C_WO + ONKV * 2048, C_V = C_SLOTV + 8192, C_PL = C_V + 20480, C_SL = C_PL + 4096;
static_assert(C_OL + 3072 <= C_BAR && C_SL + 2560 <= C_BAR, "smem overflow");
enum { B_W0 = 0, B_W1, B_W2, B_WS, B_XF0, B_XF1, B_SC, B_P0, B_P1, B_XS, B_OL, B_MF0, B_MF1, B_OF, B_RT0, B_RT1, B_VF, B_MBF, B_GO, B_NUM };
struct Descs { uint64_t sw[4], ns; };
constexpr uint64_t DSW = 0x4000004000010000ull, DNS = 0x0000001000080000ull;
template <int V> using ic = std::integral_constant<int, V>;
constexpr float SM_SCALE = 0.08838834764831845f * 1.4426950408889634f;

#define TSD(i) do {} while (0)
#define TS_FLUSH(w)
#define TSX(i, c)
#define TS(i)
#define NOFILL 0
#define DLY1 2160
#define DLY2 1320
#define RB1 0
#define QK1 10
#define RFPOS 8
#define STPOS 14
#define OTAIL 3
#define DLYS 450
#define DLYB 1
#define VLEAD 1

#define VEARLY 8
#define QSPLIT 20
__device__ __forceinline__ bool elect() {
    uint32_t r;
    asm volatile("{\n.reg .pred p;\nelect.sync _|p, 0xffffffff;\nselp.u32 %0, 1, 0, p;\n}" : "=r"(r));
    return r;
}
__device__ __forceinline__ int uni(int v) { return __shfl_sync(~0u, v, 0); }
__device__ __forceinline__ void calibrate(uint32_t cal, float keep) {
    const uint32_t t0 = gtick();
    uint32_t t, it = 0;
    do { t = gtick(); spin_guard(it); } while (__any_sync(~0u, t == t0));
    const uint32_t c = clk();
    const uint4 p = lds4u(cal);
    const float cpt = 256.f * fminf(fmaxf(__fdividef((float)(c - p.y), (float)((t - p.x) & 0x7FFFFFF)), 16.f), 128.f);
    __syncwarp();
    sts4u(cal, make_uint4(t, c, (uint32_t)(keep > 0.f ? fmaf(keep, (float)p.z - cpt, cpt) : cpt), 0));
}
struct Stamps { uint32_t v[6]; };
__device__ __forceinline__ void load_stamps2(Stamps& t, const uint32_t* f, uint32_t l16, bool on = true) {
    const char* p = reinterpret_cast<const char*>(f) + (l16 >> 2) * FSTR;
    asm volatile("{\n.reg .pred p;\nsetp.ne.u32 p, %7, 0;\nmov.u32 %0, 63;\nmov.u32 %1, 63;\nmov.u32 %2, 63;\nmov.u32 %3, 63;\nmov.u32 %4, 63;\nmov.u32 %5, 63;\n"
                 "@p ld.relaxed.gpu.global.v2.u32 {%0, %1}, [%6];\n@p ld.relaxed.gpu.global.v2.u32 {%2, %3}, [%6 + %8];\n"
                 "@p ld.relaxed.gpu.global.v2.u32 {%4, %5}, [%6 + %9];\n}"
                 : "=&r"(t.v[0]), "=&r"(t.v[1]), "=&r"(t.v[2]), "=&r"(t.v[3]), "=&r"(t.v[4]), "=&r"(t.v[5])
                 : "l"(p), "r"((uint32_t)on), "n"(128 * FSTR), "n"(256 * FSTR) : "memory");
}
__device__ __forceinline__ void load_stamps1(uint32_t* v, const uint32_t* f, uint32_t l16, bool on = true) {
    const char* p = reinterpret_cast<const char*>(f) + (l16 >> 2) * FSTR;
    asm volatile("{\n.reg .pred p;\nsetp.ne.u32 p, %4, 0;\nmov.u32 %0, 63;\nmov.u32 %1, 63;\nmov.u32 %2, 63;\n"
                 "@p ld.relaxed.gpu.global.u32 %0, [%3];\n@p ld.relaxed.gpu.global.u32 %1, [%3 + %5];\n@p ld.relaxed.gpu.global.u32 %2, [%3 + %6];\n}"
                 : "=&r"(v[0]), "=&r"(v[1]), "=&r"(v[2]) : "l"(p), "r"((uint32_t)on), "n"(128 * FSTR), "n"(256 * FSTR) : "memory");
}
template <int N>
__device__ __forceinline__ uint32_t stamps_missing(const uint32_t* v, int s) {
    uint32_t x = 0;
#pragma unroll
    for (int i = 0; i < N; i++) x |= v[i] ^ s;
    return x & 63;
}
template <int N>
__device__ __forceinline__ uint32_t latest_stamp(const uint32_t* v, const uint4 cal) {
    int late = (int)(v[0] - (cal.x << 6));
#pragma unroll
    for (int i = 1; i < N; i++) late = max(late, (int)(v[i] - (cal.x << 6)));
    return cal.y + (((late >> 6) * (int)cal.z) >> 8);
}
__device__ __forceinline__ void wait_clock(uint32_t target) {
    while (__any_sync(~0u, target - clk() < 65536u)) {}
}

template <int BYTES>
__device__ __forceinline__ bool incomplete(uint32_t buf, uint32_t l16) {
    uint32_t m = 0;
#pragma unroll 1
    for (int o = 0; o < BYTES; o += 256) m = max(m, umax4(lds4u(buf + o + (l16 & 255))));
    return __any_sync(~0u, m == ~0u);
}
__device__ __forceinline__ void refetch(uint32_t buf, const uint4* src, uint32_t bytes, uint32_t b, int w4, int barid, uint32_t& tries) {
    spin_guard(tries);
    bar_sync(barid, 128);
    if (w4 == 0 && elect()) { mbar_expect(b, bytes); bulk_ld(buf, src, bytes, b); }
    __syncwarp();
    mbar_wait(b, 0);
    bar_sync(barid, 128);
    if (w4 == 0 && elect()) mbar_arrive(b);
    __syncwarp();
}

__device__ __forceinline__ void load_chunk(const CUtensorMap* tA, const CUtensorMap* tB, int cl, int rank, uint32_t dst, int j, uint32_t b) {
    const int colA = cl * 256 + (rank >= 4 ? (rank - 4) * 128 : rank * 64), colB = colA + (rank >= 4 ? 64 : 0);
    mbar_expect(b, 65536);
    tma2d(dst, tA, colA, j * 128, b);
    tma2d(dst + 16384, tB, colB, j * 128, b);
    tma2d(dst + 32768, tB, colB, 512 + j * 128, b);
    tma2d(dst + 49152, tA, colA, 512 + j * 128, b);
}

template <bool ISV, int WG>
__device__ __forceinline__ void chain_main(const CUtensorMap* tA, const CUtensorMap* tB, const CUtensorMap* tWo,
                                           const uint32_t sb, const int cl, const int rank, const Descs& D, const uint32_t goal) {
    const int tid = threadIdx.x;
    uint32_t l16 = __shfl_sync(~0u, (tid & 31) * 16, tid & 31);
    int w4 = uni((tid >> 5) & 3);
    const int role = ISV ? 2 : (rank & 1), hh = ISV ? rank - 4 : rank >> 1, head = 2 * cl + hh;
    const uint32_t bar = sb + C_BAR;
    constexpr int ONK = ISV ? ONKV : ONKQ;
    const int ostart = (hh * 128 + role * ONKQ);

    uint32_t wk[24][4], wv[24][4];
    uint32_t a_adr;
    {
        if (WG == 1 && w4 == 0) calibrate(sb + C_CAL, 0.f);
        const int lane = tid & 31, kr = (lane & 7) + ((lane >> 4) << 3);
        a_adr = __shfl_sync(~0u, sb + WG * 32768 + kr * 128 + (((w4 * 2 + ((lane >> 3) & 1)) ^ (kr & 7)) << 4), lane);
#pragma unroll
        for (int j = 0; j < 3; j++) {
            mbar_wait(bar + (B_W0 + j) * 8, 0);
#pragma unroll
            for (int i = 0; i < 8; i++) {
                ldsm4t(wk[j * 8 + i], a_adr + j * 65536 + i * 2048);
                ldsm4t(wv[j * 8 + i], a_adr + j * 65536 + 16384 + i * 2048);
            }
            if (j != 1) {
                bar_sync(6, 256);
                if (j == 0 && tid == 0) TL(1, 6);
                if (WG == 0 && j == 0 && w4 == 0 && elect()) load_chunk(tA, tB, cl, rank, sb + C_WS, 3, bar + B_WS * 8);
                if (WG == 0 && j == 2) {
                    if (elect())
                        for (int i = w4; i < ONK; i += 4) tma2d(sb + C_WO + i * 2048, tWo, cl * 64, (ostart + i) * 16, bar + B_OF * 8);
                }
                __syncwarp();
            }
        }
        if (NOFILL) { for (uint32_t o = C_WO + ONK * 2048 + tid * 16; o < C_BAR; o += 4096) sts4u(sb + o, make_uint4(0, 0, 0, 0)); bar_sync(6, 256); }
        if (WG == 1 && w4 == 1) {
            uint32_t v, it = 0;
            do {
                asm volatile("ld.acquire.gpu.global.u32 %0, [%1];" : "=r"(v) : "l"(&g_epoch) : "memory");
                spin_guard(it);
            } while (__any_sync(~0u, (int)(v - goal) < 0));
        }
        if (WG == 1 && w4 == 0) calibrate(sb + C_CAL, 0.f);
        __syncwarp();
        bar_sync(6, 256);
        asm volatile("fence.proxy.async.global;" ::: "memory");
    }

    constexpr uint32_t SLOT = ISV ? C_SLOTV : C_SLOTQ;
    constexpr int WS_A = (SB0 + C_WS + WG * 32768) >> 4, WO_A = (SB0 + C_WO) >> 4, MB_A = (SB0 + C_MB) >> 4;
#define XN_A(ks) (int)(((SB0 + C_XN + WG * 16384) >> 4) + ((ks) >> 2) * 256 + ((ks) & 3) * 2)
    const uint32_t slot = (sb + SLOT + w4 * 512), mbw = sb + C_MB + WG * 8192;
    const uint32_t sb_v = (mapa(sb, 4 + hh));
    const uint32_t sb_x = uni(mapa(sb, 2 * hh + (WG ? 1 : (~w4 & 1))));
    const uint32_t sb_o = (mapa(sb, w4));
    const uint32_t u_off = (ISV ? (head * 128 + w4 * 32) * 16 : (cl * 4 + rank) * 256 + (w4 & 1) * 128);
    const uint32_t v_row = (sb + C_V + (2 * WG + (w4 >> 1)) * 512), v_b = ((w4 & 1) * 64);
    const uint32_t u_flag = (blockIdx.x * FSTR);
    const uint32_t f_half = (w4 & 1) * role * (ONKV * 128), f_sb = uni(mapa(sb, rank + (w4 & 1) * (4 + hh - rank)));
    const uint32_t f_src = uni((ostart + (w4 & 1) * (2 - role) * ONKQ) * 256 + f_half), f_dst = uni(f_sb + C_MB + f_half);
    const uint32_t m_dst = (sb + C_MB + role * 8192), m_bar = (bar + (B_MF0 + role) * 8);
    uint32_t target, missing;
    int s = -1;
    uint32_t pf[4][4];
    float xk[16], xv[16];

    auto load_tokens = [&](int seg, int wina, int g) {
        const int khalf = ISV ? 1 - wina : wina;
        if (!NOFILL && elect()) {
            mbar_expect(bar + (B_XF0 + g) * 8, 16384);
            bulk_ld(sb + C_XN + g * 16384, g_xc + (seg * 4 + khalf * 2 + g) * 1024, 16384, bar + (B_XF0 + g) * 8);
        }
        __syncwarp();
    };
    auto prefetch = [&]() {
#pragma unroll
        for (int i = 0; i < 4; i++) ldsm4t(pf[i], a_adr + C_WS + (i & 1) * 16384 + (i >> 1) * 2048);
    };
    constexpr int HA = ISV ? 0 : 1, NK1 = ISV ? 0 : QK1;
    auto products = [&](auto give, auto half, auto init, auto i0, auto i1, const uint64_t d) {
        static_for<i0.value, i1.value>([&](auto i) {
            constexpr int ks = half.value * 16 + i.value, acc = !(init.value && i.value == 0);
            if constexpr (ks >= 24) wg32_ss<WS_A + give.value * 1024 + (ks - 24) * 128, XN_A(i.value)>(give.value ? xv : xk, d);
            else if constexpr (give.value) wg32_rs<acc, XN_A(i.value)>(xv, wv[ks], d);
            else wg32_rs<acc, XN_A(i.value)>(xk, wk[ks], d);
        });
    };
    auto stream_a = [&](const uint64_t dk, const uint64_t dv) {
        if (NOFILL) return;
        wg_fence();
        products(ic<0>{}, ic<HA>{}, ic<1>{}, ic<0>{}, ic<8>{}, dk);
        products(ic<1>{}, ic<HA>{}, ic<1>{}, ic<0>{}, ic<16>{}, dv);
        products(ic<0>{}, ic<HA>{}, ic<1>{}, ic<8>{}, ic<16>{}, dk);
        wg_commit();
    };
    auto token_softmax = [&]() {
        const int hi = w4 - 2, lane = l16 >> 4;
        const uint32_t src = sb + C_XSL + l16 + hi * 8;
        const int d0 = 16 * role + 8 * hi + (lane >> 2) - 2 * (lane & 3);
        mbar_wait(bar + B_XS * 8, s & 1);
        float e[10];
        float m = -INFINITY;
#pragma unroll
        for (int i = 0; i < 5; i++) {
            __syncwarp();
            const float2 a = lds2f(src + i * 512), b = lds2f(src + 2560 + i * 512);
            e[2 * i] = (i == 0 || d0 >= 8 * (i - 1)) ? a.x + b.x : -INFINITY;
            e[2 * i + 1] = (i == 0 || d0 > 8 * (i - 1)) ? a.y + b.y : -INFINITY;
            m = fmaxf(m, fmaxf(e[2 * i], e[2 * i + 1]));
        }
        m = fmaxf(m, __shfl_xor_sync(~0u, m, 1));
        m = fmaxf(m, __shfl_xor_sync(~0u, m, 2));
        m *= -SM_SCALE;
        float l = 0.f;
#pragma unroll
        for (int i = 0; i < 10; i++) { e[i] = ex2(fmaf(e[i], SM_SCALE, m)); l += e[i]; }
        l += __shfl_xor_sync(~0u, l, 1);
        l += __shfl_xor_sync(~0u, l, 2);
        l = rcp(l);
        const uint32_t pd = sb_v + C_PL + (s & 1) * 2048 + role * 768 + hi * 128 + (l16 >> 2), pb = sb_v + C_BAR + (B_P0 + (s & 1)) * 8;
        st_async1(pd, pb, pack2(e[0] * l, e[1] * l));
        st_async1(pd + 256, pb, pack2(e[2] * l, e[3] * l));
        st_async1(pd + 512, pb, pack2(e[4] * l, e[5] * l));
        if (role) {
            st_async1(pd + 768, pb, pack2(e[6] * l, e[7] * l));
            st_async1(pd + 1024, pb, pack2(e[8] * l, e[9] * l));
        }
        if (hi == 0 && l16 == 0) mbar_expect(bar + B_XS * 8, 3072 + role * 2048);
        __syncwarp();
    };

    auto windows = [&](auto first_) {
        constexpr bool FIRST = first_.value;
        asm volatile("" : "+r"(l16), "+r"(w4));
        const uint64_t dd[4] = {FIRST ? DSW : D.sw[0], FIRST ? DSW : D.sw[1], FIRST ? DSW : D.sw[2], FIRST ? DSW : D.sw[3]};
        TS(5);
        if constexpr (WG == 1) {
            TS(6);
            if (ISV && !FIRST) bar_sync(3, 256);
            Stamps st2;
            if (!ISV && !FIRST) load_stamps2(st2, g_flag[0], l16, __any_sync(~0u, missing) && w4 < 2);
            stream_a(dd[0], dd[1]);
            if (!NOFILL) bar_arrive(7, 256);
            if (!FIRST && !ISV && w4 < 2) {
                const char* src = reinterpret_cast<const char*>(&g_xo[s & 3][0]) + f_src;
                if (__builtin_expect(__any_sync(~0u, missing), 0)) {
                    uint32_t it = 0;
                    while (__any_sync(~0u, stamps_missing<6>(st2.v, s))) { load_stamps2(st2, g_flag[0], l16); spin_guard(it); }
                    target = latest_stamp<6>(st2.v, lds4u(sb + C_CAL)) + DLY1;
                }
                mbar_wait(bar + B_VF * 8, s & 1);
                TS(10);
                wait_clock(target);
                if (elect()) bulk_ld(f_dst, src, ONKQ * 256 - w4 * (ONKQ * 256 - ONKV * 128), f_sb + C_BAR + B_OF * 8);
                __syncwarp();
                TS(8);
            }
            if (!NOFILL) {
                wg_wait<0>();
                reg_fence<16>(xk); reg_fence<16>(xv);
                if (w4 == 3) {
                    bar_sync(2, 128);
                    if (RB1 == 0 || FIRST) load_tokens(s + 1, 0, 1);
                    if (ISV && !FIRST && (s & 3) == 0 && s > 0 && l16 == 0) count_up(CNT_OX + (s >> 2) - 1);
                    __syncwarp();
                }
                else bar_arrive(2, 128);
            }
            TS(7);
        } else {
            if (!NOFILL) {
                mbar_wait(bar + B_XF0 * 8, 0);
                bar_sync(7, 256);
            }
            TS(6);
            stream_a(dd[0], dd[1]);
        }
        uint32_t st[6];
        uint4 cal;
        if constexpr (WG == 0) {
            if constexpr (!FIRST) {
                const uint32_t dst = sb_o + C_OL + rank * 512 + l16;
                const uint32_t can = sb + C_MB + l16 * 8 + (l16 >> 2), can2 = can + (l16 < (ONK * 2 - 64) * 16 ? 8192 : 0);
                float co[4];
                TS(7);
                uint32_t tries = 0;
                for (;; tries |= 1) {
                    asm volatile("" : "+r"(tries));
                    if (__builtin_expect(tries, 0)) {
                        wg_wait<0>();
                        refetch(sb + C_MB, &g_xo[s & 3][ostart * 16], ONK * 256, bar + B_RT0 * 8, w4, 1, tries);
                    }
                    mbar_wait(bar + B_OF * 8, s & 1);
                    TS(8);
                    wg8_chain<0, 8, WO_A, MB_A>(co, D.sw[0], D.ns);
                    if (__builtin_expect(!__any_sync(~0u, max(max(lds1u(can), lds1u(can + 4096)), lds1u(can2)) == ~0u), 1)) break;
                }
                wg_wait<1>();
                if (l16 == 0) mbar_arrive(bar + B_GO * 8);
                wg8_chain<8, ONK - OTAIL, WO_A, MB_A>(co, D.sw[0], D.ns);
                static_for<ONK - OTAIL, ONK>([&](auto i) { wg8_ss<1, WO_A + i.value * 128, MB_A + i.value * 16>(co, D.sw[0], D.ns); });
                wg_commit();
                wg_wait<1>();
                bar_arrive(5, 256);
                wg_wait<0>();
                reg_fence<4>(co);
                if (__builtin_expect(st_async4_unless_nan(dst, sb_o + C_BAR + B_OL * 8, co), 0)) {
                    while (incomplete<ONK * 256>(sb + C_MB, l16)) {
                        refetch(sb + C_MB, &g_xo[s & 3][ostart * 16], ONK * 256, bar + B_RT0 * 8, w4, 1, tries);
                        co[0] = co[1] = co[2] = co[3] = 0.f;
#pragma unroll 1
                        for (int i = 0; i < ONK; i++) {
                            wg_fence();
                            wg8_ss<1, WO_A, MB_A>(co, DSW + i * 128, DNS + i * 16);
                            wg_commit();
                            wg_wait<0>();
                        }
                        reg_fence<4>(co);
                    }
                    st_async4(dst, sb_o + C_BAR + B_OL * 8, __float_as_uint(co[0]), __float_as_uint(co[1]), __float_as_uint(co[2]), __float_as_uint(co[3]));
                }
                TS(9);
                if (l16 < 48 && w4 == 3) mbar_expect(bar + B_MF0 * 8 + (l16 >> 1), l16 == 32 ? ONK * 256 : 8192);
            } else {
                wg_wait<0>();
                if (l16 == 0) mbar_arrive(bar + B_GO * 8);
                bar_arrive(5, 256);
            }
            if (l16 < 32) mbar_arrive_cluster(mapa(bar + B_MBF * 8, 2 * hh + (l16 >> 4)));
            __syncwarp();
            if (!NOFILL) { reg_fence<16>(xk); reg_fence<16>(xv); }
        } else {
            if (w4 < 2) {
                mbar_wait(bar + B_GO * 8, (s + 1) & 1);
                const uint32_t v = ((gtick() - (ISV ? (ONKQ - ONKV) * 18 / 64 : 0)) << 6) | s, c = clk();
                if (w4 == 0) {
                    if (!FIRST) {
                        if (l16 == 0) st_relaxed1(&g_flag[1][u_flag + (l16 >> 1)], v);
                        if (!ISV) calibrate(sb + C_CAL, 0.75f);
                    }
                } else {
                    if (!FIRST) wait_clock(c + DLYB);
                    load_tokens(s + 1, 0, 0);
                }
                if (!ISV && !FIRST) st_relaxed1(reinterpret_cast<char*>(&g_xmem[(s + 3) & 3][0]) + (u_off + (l16 >> 2)), ~0u);
            } else if (!FIRST && !NOFILL) {
                if (RB1 == 1 && w4 == 3) { mbar_wait(bar + B_OF * 8, s & 1); load_tokens(s + 1, 0, 1); }
                if (!ISV) token_softmax();
                TSX(9, w4 == 2);
            }
            if (!NOFILL) mbar_wait(bar + B_XF1 * 8, 1);
            if (!ISV && !FIRST) cal = lds4u(sb + C_CAL);
            bar_sync(5, 256);
            if (!ISV && !FIRST) load_stamps1(st, g_flag[1], l16, w4 == 0);
        }
        asm volatile("" : "+r"(l16), "+r"(w4));
        TSX(11, w4 == 0 && (WG || ISV));
        auto store_tokens = [&](const float4* r) {
            uint32_t lo[4], hi[4];
#pragma unroll
            for (int j = 0; j < 4; j++) {
                lo[j] = pack2(xk[4 * j] + r[j].x, xk[4 * j + 1] + r[j].y);
                hi[j] = pack2(xk[4 * j + 2] + r[j].z, xk[4 * j + 3] + r[j].w);
            }
            if (!ISV) {
                const uint32_t d = sb + C_QX + WG * 4096 + w4 * 1024 + l16;
                stsm4t(d, lo[0], lo[1], lo[2], lo[3]);
                stsm4t(d + 512, hi[0], hi[1], hi[2], hi[3]);
            } else {
                const uint32_t d = v_row + ((s + 1) & 1) * 10240 + ((l16 & 384) << 4) + ((l16 & 96) << 2) + ((l16 & 112) ^ v_b);
                stsm4(d, lo[0], lo[1], lo[2], lo[3]);
                stsm4(d ^ 32, hi[0], hi[1], hi[2], hi[3]);
            }
        };
        if constexpr (WG == 1) {
            if (!NOFILL) {
                wg_fence();
                products(ic<1>{}, ic<1 - HA>{}, ic<0>{}, ic<0>{}, ic<16>{}, dd[3]);
                products(ic<0>{}, ic<1 - HA>{}, ic<0>{}, ic<0>{}, ic<NK1>{}, dd[2]);
                wg_commit();
                if (ISV) bar_arrive(7, 256);
                else {
                    if (!FIRST) load_stamps1(st + 3, g_flag[1], l16, w4 == 0);
                    mbar_wait(bar + B_MBF * 8, (s + 1) & 1);
                    bar_sync(7, 256);
                }
                wg_wait<0>();
                reg_fence<16>(xv); reg_fence<16>(xk);
#pragma unroll
                for (int j = 0; j < 4; j++) sts4f(slot + l16 + j * 2048, xv[4 * j], xv[4 * j + 1], xv[4 * j + 2], xv[4 * j + 3]);
                bar_arrive(8, 256);
            }
            TS(12);
            if (!ISV && w4 == 0) {
                const uint4* src = &g_xmem[(s + 1) & 3][role * 512];
                if (NOFILL) mbar_wait(bar + B_MBF * 8, (s + 1) & 1);
                if (!FIRST) {
                    if (__builtin_expect(__any_sync(~0u, stamps_missing<3>(st, s)), 0)) {
                        uint32_t it = 0;
                        if (!NOFILL) { st[0] = st[3]; st[1] = st[4]; st[2] = st[5]; }
                        while (__any_sync(~0u, stamps_missing<3>(st, s))) { load_stamps1(st, g_flag[1], l16); spin_guard(it); }
                    }
                    TS(3);
                    wait_clock(latest_stamp<3>(st, cal) + DLY2);
                }
                if (hh) { if (elect()) bulk_mc(m_dst, src, 8192, m_bar, 0x2C); }
                else if (elect()) bulk_mc(m_dst, src, 8192, m_bar, 0x13);
                __syncwarp();
                TS(4);
            }
            prefetch();
            if (!NOFILL) {
                bar_sync(9, 256);
                float4 r[4];
#pragma unroll
                for (int j = 0; j < 4; j++) r[j] = lds4f(slot + l16 + j * 2048);
                bar_sync(14, 256);
                wg_fence();
                products(ic<0>{}, ic<1 - HA>{}, ic<0>{}, ic<NK1>{}, ic<16>{}, dd[2]);
                wg_commit();
                wg_wait<0>();
                reg_fence<16>(xk);
                TS(13);
                store_tokens(r);
                bar_arrive(10, 256);
                if (w4 != 3) bar_arrive(13, 128);
            }
        } else {
            float4 r[4];
            if (!NOFILL) mbar_wait(bar + B_XF0 * 8, 1);
            if (!ISV && !FIRST && w4 < 2) {
                char* gd = reinterpret_cast<char*>(&g_xmem[(s + 1) & 3][0]) + (u_off + (l16 >> 2));
                mbar_wait(bar + B_OL * 8, s & 1);
                TSD(3);
                float2 a[6];
#pragma unroll
                for (int i = 0; i < 6; i++) a[i] = lds2f(sb + C_OL + w4 * 8 + l16 + i * 512);
                st_relaxed1(gd, movm(pack2((a[0].x + a[1].x) + (a[2].x + a[3].x) + (a[4].x + a[5].x),
                                           (a[0].y + a[1].y) + (a[2].y + a[3].y) + (a[4].y + a[5].y))));
                TS(11);
                if (w4 == 0 && l16 == 0) mbar_expect(bar + B_OL * 8, 3072);
                __syncwarp();
            }
            if (!NOFILL) {
                bar_sync(7, 256);
                TS(12);
                wg_fence();
                products(ic<1>{}, ic<1 - HA>{}, ic<0>{}, ic<0>{}, ic<16>{}, dd[3]);
                wg_commit();
                products(ic<0>{}, ic<1 - HA>{}, ic<0>{}, ic<0>{}, ic<6>{}, dd[2]);
                wg_commit();
                bar_sync(8, 256);
#pragma unroll
                for (int j = 0; j < 4; j++) r[j] = lds4f(slot + l16 + j * 2048);
                wg_wait<1>();
                reg_fence<16>(xv);
#pragma unroll
                for (int j = 0; j < 4; j++) sts4f(slot + l16 + j * 2048, xv[4 * j], xv[4 * j + 1], xv[4 * j + 2], xv[4 * j + 3]);
                bar_arrive(9, 256);
                products(ic<0>{}, ic<1 - HA>{}, ic<0>{}, ic<6>{}, ic<16>{}, dd[2]);
                wg_commit();
                bar_arrive(14, 256);
                wg_wait<0>();
                reg_fence<16>(xk);
            }
            TS(13);
            if (!NOFILL) store_tokens(r);
            prefetch();
        }
    };

    if (tid == 0) TL(1, 2);
    if (w4 == 0) load_tokens(0, 1, WG);
    mbar_wait(bar + B_WS * 8, 0);
    if (WG == 1 && !NOFILL) mbar_wait(bar + B_XF1 * 8, 0);
    windows(ic<1>{});
    if (tid == 0) TL(1, 3);

#pragma unroll 1
    while (true) {
        s++;
        asm volatile("" : "+r"(l16), "+r"(a_adr), "+r"(w4));
        TS_FLUSH(WG);
        TS(0);
        float ck[4], cv[4];
        Stamps st1;
        {
            const uint32_t can = mbw + l16 * 8 + (l16 >> 2);
            uint32_t tries = 0;
            bool synced = false;
            for (;; tries |= 1) {
                asm volatile("" : "+r"(tries));
                if (__builtin_expect(tries, 0)) {
                    if (__any_sync(~0u, max(lds1u(can), lds1u(can + 4096)) == ~0u) || incomplete<8192>(mbw, l16))
                        refetch(mbw, &g_xmem[s & 3][WG * 512], 8192, bar + (B_RT0 + WG) * 8, w4, 1 + WG, tries);
                    else tries = ~0u;
                    prefetch();
                }
                mbar_wait(bar + (B_MF0 + WG) * 8, s & 1);
                TS(1);
                uint32_t b[2][4];
                float dk[4], dv[4];
                ldsm4(b[0], mbw + l16 + 12 * 512);
#pragma unroll
                for (int i = 0; i < 4; i++) ck[i] = cv[i] = dk[i] = dv[i] = 0.f;
                auto kpair = [&](auto kp_) {
                    constexpr int kp = kp_.value, grp = kp / 5, ph = kp % 5, nx = kp + 1;
                    if constexpr (nx < 16) ldsm4(b[nx & 1], mbw + l16 + ((nx % 5) ? (nx / 5) * 4 + (nx % 5) - 1 : 12 + nx / 5) * 512);
                    const uint32_t* bb = b[kp & 1];
                    if constexpr (ph != 0) {
                        constexpr int q = (grp * 4 + ph - 1) * 2, i = ph - 1;
                        ldsm4t(pf[i], a_adr + C_WS + (i & 1) * 16384 + (grp * 2 + 2 + (i >> 1)) * 2048);
                        __syncwarp();
                        mma16(cv, wv[q][0], wv[q][1], wv[q][2], wv[q][3], bb[0], bb[1]);
                        mma16(ck, wk[q][0], wk[q][1], wk[q][2], wk[q][3], bb[0], bb[1]);
                        mma16(dv, wv[q + 1][0], wv[q + 1][1], wv[q + 1][2], wv[q + 1][3], bb[2], bb[3]);
                        mma16(dk, wk[q + 1][0], wk[q + 1][1], wk[q + 1][2], wk[q + 1][3], bb[2], bb[3]);
                    } else {
                        mma16(cv, pf[1][0], pf[1][1], pf[1][2], pf[1][3], bb[0], bb[1]);
                        mma16(dv, pf[3][0], pf[3][1], pf[3][2], pf[3][3], bb[2], bb[3]);
                        mma16(ck, pf[0][0], pf[0][1], pf[0][2], pf[0][3], bb[0], bb[1]);
                        mma16(dk, pf[2][0], pf[2][1], pf[2][2], pf[2][3], bb[2], bb[3]);
                    }
                };
                kpair(ic<0>{});
                const uint32_t c0 = lds1u(can), c1 = lds1u(can + 4096);
                kpair(ic<1>{});
                if (__builtin_expect(__any_sync(~0u, max(c0, c1) == ~0u), 0)) continue;
                st_pred1(&g_flag[0][u_flag + WG + l16], ((gtick() - (ISV ? VLEAD : 0)) << 6) | s, w4 * 512 + l16 == 1536);
                if (WG == 0 && !NOFILL && !synced) bar_sync(10, 256);
                static_for<2, RFPOS>(kpair);
                if (WG == 1 && !NOFILL && w4 == 3 && !synced) {
                    bar_sync(13, 128);
                    if (s < NSEG - 1) load_tokens(s + 1, 1, 1);
                }
                synced = true;
                static_for<RFPOS, STPOS>(kpair);
                if (!ISV && WG == 1) load_stamps2(st1, g_flag[0], l16, w4 < 2);
                static_for<STPOS, 16>(kpair);
#pragma unroll
                for (int i = 0; i < 4; i++) { cv[i] += dv[i]; ck[i] += dk[i]; }
                if (ISV) {
                    sts4f(slot + WG * 2048 + l16, cv[0], cv[1], cv[2], cv[3]);
                } else {
                    const float *q = WG ? cv : ck, *k = WG ? ck : cv;
                    stsm4t(slot + WG * 2048 + l16, pack2(q[0], q[1]), pack2(q[2], q[3]), pack2(k[0], k[1]), pack2(k[2], k[3]));
                }
                TS(2);
                if (__builtin_expect(!any_nan_unless(cv[0], cv[1], tries), 1)) break;
            }
            if (ISV) bar_sync(6, 256);
        }
        if constexpr (!ISV) {
            const uint32_t kl = sb + C_KX + ((l16 & 384) << 2) + (l16 & 112);
            const uint32_t qa = sb + C_SLOTQ + ((l16 >> 1) & 128) + ((l16 & 128) << 3) + (l16 & 112);
            const uint32_t ma = sb + C_SLOTQ + 256 + l16 + (l16 & 256);
            const uint32_t qx = sb + C_QX + l16 + (l16 & 256);
            auto ldsm_sum = [&](uint32_t* r, uint32_t a) {
                uint32_t t[4];
                ldsm4(r, a); ldsm4(t, a + 2048);
#pragma unroll
                for (int i = 0; i < 4; i++) asm("add.rn.bf16x2 %0, %0, %1;" : "+r"(r[i]) : "r"(t[i]));
            };
            auto tile = [&](float* d, const uint32_t (*q)[4], const uint32_t (*k)[4]) {
                d[0] = d[1] = d[2] = d[3] = 0.f;
#pragma unroll
                for (int i = 0; i < 4; i++) mma16(d, q[i][0], q[i][1], q[i][2], q[i][3], k[i >> 1][(i & 1) * 2], k[i >> 1][(i & 1) * 2 + 1]);
            };
            auto send = [&](int ti, const float* d) {
                st_async4(sb_x + C_XSL + role * 2560 + ti * 512 + l16, sb_x + C_BAR + B_XS * 8,
                          __float_as_uint(d[0]), __float_as_uint(d[1]), __float_as_uint(d[2]), __float_as_uint(d[3]));
            };
            if constexpr (WG == 0) {
                if (w4 < 2) {
                    uint32_t k0[2][4], k1[2][4], q0[4], q1[4];
                    const uint32_t ka = kl + w4 * 256, dst = sb_v + C_SL + role * 1280 + w4 * 512 + l16;
                    ldsm4(k0[0], ka); ldsm4(k0[1], ka + 2048);
                    ldsm4(k1[0], ka + 128); ldsm4(k1[1], ka + 128 + 2048);
                    bar_sync(6, 256);
                    TS(3);
                    ldsm_sum(q0, qa); ldsm_sum(q1, qa + 512);
                    float s0[4] = {0.f, 0.f, 0.f, 0.f}, s1[4] = {0.f, 0.f, 0.f, 0.f}, s2[4] = {0.f, 0.f, 0.f, 0.f}, s3[4] = {0.f, 0.f, 0.f, 0.f};
                    mma16(s0, q0[0], q0[1], q0[2], q0[3], k0[0][0], k0[0][1]);
                    mma16(s1, q0[0], q0[1], q0[2], q0[3], k0[1][0], k0[1][1]);
                    mma16(s2, q0[0], q0[1], q0[2], q0[3], k1[0][0], k1[0][1]);
                    mma16(s3, q0[0], q0[1], q0[2], q0[3], k1[1][0], k1[1][1]);
                    mma16(s0, q1[0], q1[1], q1[2], q1[3], k0[0][2], k0[0][3]);
                    mma16(s1, q1[0], q1[1], q1[2], q1[3], k0[1][2], k0[1][3]);
                    mma16(s2, q1[0], q1[1], q1[2], q1[3], k1[0][2], k1[0][3]);
                    mma16(s3, q1[0], q1[1], q1[2], q1[3], k1[1][2], k1[1][3]);
                    st_async4(dst, sb_v + C_BAR + B_SC * 8, __float_as_uint(s0[0] + s1[2]), __float_as_uint(s0[1] + s1[3]),
                              __float_as_uint(s2[0] + s3[2]), __float_as_uint(s2[1] + s3[3]));
                    bar_arrive(12, 256);
                    TS(4);
                } else if (w4 == 2) {
                    uint32_t q0[4], q1[4], km[2][4], q[4][4];
                    const uint32_t dst = sb_v + C_SL + role * 1280 + 1024 + (l16 >> 1);
                    bar_sync(6, 256);
                    ldsm_sum(q0, qa); ldsm_sum(km[0], ma); ldsm_sum(km[1], ma + 1024); ldsm_sum(q1, qa + 512);
                    __syncwarp();
#pragma unroll
                    for (int i = 0; i < 4; i++) ldsm4(q[i], qx + 256 + i * 1024);
                    float s0[4] = {0.f, 0.f, 0.f, 0.f}, s1[4] = {0.f, 0.f, 0.f, 0.f}, d0[4];
                    mma16(s0, q0[0], q0[1], q0[2], q0[3], km[0][0], km[0][1]);
                    mma16(s1, q0[0], q0[1], q0[2], q0[3], km[1][0], km[1][1]);
                    mma16(s0, q1[0], q1[1], q1[2], q1[3], km[0][2], km[0][3]);
                    mma16(s1, q1[0], q1[1], q1[2], q1[3], km[1][2], km[1][3]);
                    st_async2(dst, sb_v + C_BAR + B_SC * 8, __float_as_uint(s0[0] + s1[2]), __float_as_uint(s0[1] + s1[3]));
                    if (!NOFILL) tile(d0, q, km);
                    bar_sync(12, 256);
                    if (!NOFILL) send(0, d0);
                } else {
                    bar_sync(6, 256);
                    if (s < NSEG - 1) load_tokens(s + 1, 1, 0);
                    if (!NOFILL) {
                        uint32_t q[4][4], k0[2][4], k1[2][4], km[2][4];
                        float d0[4], d1[4], d2[4];
#pragma unroll
                        for (int i = 0; i < 4; i++) ldsm4(q[i], qx + i * 1024);
                        ldsm4(k0[0], kl); ldsm4(k0[1], kl + 2048);
                        ldsm4(k1[0], kl + 128); ldsm4(k1[1], kl + 128 + 2048);
                        tile(d1, q, k0); tile(d2, q, k1);
                        ldsm_sum(km[0], ma); ldsm_sum(km[1], ma + 1024);
                        tile(d0, q, km);
                        bar_sync(12, 256);
                        send(0, d0); send(1, d1); send(2, d2);
                    } else {
                        bar_sync(12, 256);
                    }
                }
                if (__builtin_expect(s == NSEG - 1, 0)) break;
            } else {
                bar_sync(6, 256);
                mbar_wait(bar + B_WS * 8, 0);
                missing = stamps_missing<6>(st1.v, s);
                target = latest_stamp<6>(st1.v, lds4u(sb + C_CAL)) + DLY1;
                if (!NOFILL) {
                    uint32_t q[4][4], k0[2][4];
                    float d1[4];
#pragma unroll
                    for (int i = 0; i < 4; i++) ldsm4(q[i], qx + 256 + i * 1024);
                    ldsm4(k0[0], kl + w4 * 128); ldsm4(k0[1], kl + w4 * 128 + 2048);
                    tile(d1, q, k0);
                    mbar_wait(bar + B_XF1 * 8, s == NSEG - 1);
                    bar_sync(12, 256);
                    send(1 + w4, d1);
                } else {
                    bar_sync(12, 256);
                }
                if (__builtin_expect(s == NSEG - 1, 0)) {
                    asm volatile("" : "+r"(l16));
                    if (w4 >= 2 && !NOFILL) token_softmax();
                    break;
                }
            }
        } else {
            const uint32_t lane_b = sb + C_V + w4 * 512 + ((l16 & 384) << 4) + (l16 & 112);
            auto load_values = [&](uint32_t (*vx)[4], uint32_t* vm, int ss) {
#pragma unroll
                for (int j = 0; j < 4; j++) ldsm4(vx[j], ((lane_b + (ss & 1) * 10240) ^ (j * 32)) + j * 128);
                ldsm4(vm, sb + C_V + (ss & 1) * 10240 + w4 * 512 + 8192 + (l16 ^ ((l16 >> 2) & 96)));
            };
            auto token_output = [&](int ss, bool live, auto mid) {
                uint32_t vx[4][4], vm[4];
                const uint32_t pl = sb + C_PL + (ss & 1) * 2048 + (l16 >> 2);
                auto lds_frag = [&](uint32_t a) { return make_uint4(lds1u(a), lds1u(a + 128), lds1u(a + 256), lds1u(a + 384)); };
                load_values(vx, vm, ss);
                mid();
                char* orow = reinterpret_cast<char*>(g_ox) + (ss * (32 * HD * 2) + (u_off >> 3) + (l16 >> 6) * (HD * 2) + (l16 & 48));
#pragma unroll
                for (int mh = 1; mh >= 0; mh--) {
                    __syncwarp();
                    const uint2 pm = make_uint2(lds1u(pl + mh * 768), lds1u(pl + mh * 768 + 128));
                    const uint4 p0 = lds_frag(pl + mh * 768 + 256);
                    float o[4][4];
#pragma unroll
                    for (int j = 0; j < 4; j++) { o[j][0] = o[j][1] = o[j][2] = o[j][3] = 0.f; mma8(o[j], pm.x, pm.y, vm[j]); }
#pragma unroll
                    for (int j = 0; j < 4; j++) mma16(o[j], p0.x, p0.y, p0.z, p0.w, vx[j][0], vx[j][1]);
                    if (mh) {
                        const uint4 p1 = lds_frag(pl + 1536);
#pragma unroll
                        for (int j = 0; j < 4; j++) mma16(o[j], p1.x, p1.y, p1.z, p1.w, vx[j][2], vx[j][3]);
                    }
                    st_pred4(orow + mh * (16 * HD * 2),
                             make_uint4(pack2(o[0][0], o[0][1]), pack2(o[1][0], o[1][1]), pack2(o[2][0], o[2][1]), pack2(o[3][0], o[3][1])), live);
                    st_pred4(orow + mh * (16 * HD * 2) + 8 * HD * 2,
                             make_uint4(pack2(o[0][2], o[0][3]), pack2(o[1][2], o[1][3]), pack2(o[2][2], o[2][3]), pack2(o[3][2], o[3][3])), live);
                }
            };
            const uint32_t vd = v_row + (s & 1) * 10240 + 8192 + ((l16 & 96) << 2) + ((l16 & 112) ^ v_b ^ ((l16 & 128) >> 2));
            const float4 r = lds4f(slot + (WG ^ 1) * 2048 + l16);
            __syncwarp();
            auto finish = [&]() {
                stsm2(vd, pack2(ck[0] + r.x, ck[1] + r.y), pack2(ck[2] + r.z, ck[3] + r.w));
                if (WG == 1) {
                    bar_arrive(11, 256);
                    if (w4 == 3 && l16 < 32) mbar_arrive_cluster(mapa(bar + B_VF * 8, 2 * hh + (l16 >> 4)));
                }
                TSX(3, WG == 0 && w4 == 0);
            };
            if (!NOFILL && WG == 1) {
                token_output(s - 1, s > 0, [&]() { finish(); mbar_wait(bar + (B_P0 + ((s - 1) & 1)) * 8, ((s - 1) >> 1) & 1); });
                if (w4 == 1 && l16 == 0 && s > 0) mbar_expect(bar + (B_P0 + ((s - 1) & 1)) * 8, 2048);
                mbar_wait(bar + B_XF1 * 8, s == NSEG - 1);
            } else {
                finish();
            }
            if (WG == 0) bar_sync(11, 256);
            if (__builtin_expect(s == NSEG - 1, 0)) {
                bar_sync(6, 256);
                if (WG == 1) {
                    if (!NOFILL) token_output(s, true, [&]() { mbar_wait(bar + (B_P0 + (s & 1)) * 8, (s >> 1) & 1); });
                    bar_sync(2, 128);
                    if (w4 == 0 && l16 == 0) {
                        if (NOFILL) for (int i = 0; i < 15; i++) count_up(CNT_OX + i);
                        count_up(CNT_OX + 15);
                    }
                    __syncwarp();
                }
                mbar_wait(bar + B_SC * 8, s & 1);
                break;
            }
            if constexpr (WG == 0) {
                uint32_t vx[4][4], vm[4];
                load_values(vx, vm, s);
                const uint32_t oo = u_off + ((l16 & 48) << 3) + ((l16 >> 2) & 112);
                char* dst = reinterpret_cast<char*>(&g_xo[s & 3][0]) + oo;
                if (w4 == 3) load_tokens(s + 1, 1, 0);
                mbar_wait(bar + B_SC * 8, s & 1);
                TS(4);
                const float4 a0 = lds4f(sb + C_SL + l16), b0 = lds4f(sb + C_SL + 1280 + l16);
                const float4 a1 = lds4f(sb + C_SL + 512 + l16), b1 = lds4f(sb + C_SL + 1280 + 512 + l16);
                const float2 a2 = lds2f(sb + C_SL + 1024 + (l16 >> 1)), b2 = lds2f(sb + C_SL + 1280 + 1024 + (l16 >> 1));
                const float e[10] = {a0.x + b0.x, a0.y + b0.y, a0.z + b0.z, a0.w + b0.w, a1.x + b1.x, a1.y + b1.y, a1.z + b1.z, a1.w + b1.w,
                                     a2.x + b2.x, a2.y + b2.y};
                float m = fmaxf(fmaxf(fmaxf(e[0], e[1]), fmaxf(e[2], e[3])), fmaxf(fmaxf(e[4], e[5]), fmaxf(e[6], e[7])));
                m = fmaxf(m, fmaxf(e[8], e[9]));
                m = fmaxf(fmaxf(m, __shfl_xor_sync(~0u, m, 1)), fmaxf(__shfl_xor_sync(~0u, m, 2), __shfl_xor_sync(~0u, m, 3)));
                m *= -SM_SCALE;
                float x[10];
#pragma unroll
                for (int i = 0; i < 10; i++) x[i] = ex2(fmaf(e[i], SM_SCALE, m));
                float o[4][4];
                const uint32_t p0 = pack2(x[0], x[1]), p1 = pack2(x[2], x[3]), j0 = __float_as_uint(x[1]), j1 = __float_as_uint(x[3]);
#pragma unroll
                for (int j = 0; j < 4; j++) { o[j][0] = o[j][1] = o[j][2] = o[j][3] = 0.f; mma16(o[j], p0, j0, p1, j1, vx[j][0], vx[j][1]); }
                const uint32_t p2 = pack2(x[4], x[5]), p3 = pack2(x[6], x[7]), j2 = __float_as_uint(x[5]), j3 = __float_as_uint(x[7]);
#pragma unroll
                for (int j = 0; j < 4; j++) mma16(o[j], p2, j2, p3, j3, vx[j][2], vx[j][3]);
                const uint32_t p4 = pack2(x[8], x[9]), j4 = __float_as_uint(x[9]);
                float l = (((x[0] + x[1]) + (x[2] + x[3])) + ((x[4] + x[5]) + (x[6] + x[7]))) + (x[8] + x[9]);
                l = (l + __shfl_xor_sync(~0u, l, 1)) + (__shfl_xor_sync(~0u, l, 2) + __shfl_xor_sync(~0u, l, 3));
#pragma unroll
                for (int j = 0; j < 4; j++) mma8(o[j], p4, j4, vm[j]);
                l = rcp(l);
                st_relaxed4(reinterpret_cast<uint4*>(dst), make_uint4(pack2(o[0][0] * l, o[0][1] * l), pack2(o[1][0] * l, o[1][1] * l),
                                                                      pack2(o[2][0] * l, o[2][1] * l), pack2(o[3][0] * l, o[3][1] * l)));
                bar_arrive(3, 256);
                st_relaxed4(reinterpret_cast<uint4*>(reinterpret_cast<char*>(&g_xo[(s + 2) & 3][0]) + oo), make_uint4(~0u, ~0u, ~0u, ~0u));
                if (w4 == 0 && l16 == 0) mbar_expect(bar + B_SC * 8, 2560);
            }
        }
        windows(ic<0>{});
    }
}

__global__ void __cluster_dims__(6, 1, 1) __launch_bounds__(256, 1)
chain_kernel(const __grid_constant__ CUtensorMap tq, const __grid_constant__ CUtensorMap tk, const __grid_constant__ CUtensorMap tv,
             const __grid_constant__ CUtensorMap two, const __grid_constant__ Descs D, const __grid_constant__ Descs DV,
             const __nv_bfloat16* __restrict__ x, const __nv_bfloat16* __restrict__ mem0) {
    extern __shared__ __align__(1024) uint8_t smem[];
    const uint32_t sb = smem_u32(smem);
    const int rank = blockIdx.x % 6, cl = blockIdx.x / 6, role = rank >= 4 ? 2 : rank & 1;
    const int tid = threadIdx.x, lane = tid & 31, gw = blockIdx.x * 8 + uni(tid >> 5);
    const CUtensorMap *tA = role == 2 ? &tv : &tq, *tB = role == 2 ? &tv : &tk;
    uint4 cur[4], nxt[4];
#pragma unroll
    for (int j = 0; j < 4; j++) {
        cur[j] = reinterpret_cast<const uint4*>(x)[gw * 128 + j * 32 + lane];
        nxt[j] = reinterpret_cast<const uint4*>(x)[(gw + 768) * 128 + j * 32 + lane];
    }
    if (gw < 512 && lane < 16) asm volatile("prefetch.global.L2 [%0];" :: "l"(x + (gw + 1536) * DM + lane * 64));
    if (threadIdx.x == 0) {
        TL(1, 0); TLSM(1);
        if ((sb & 0x3FFFF) != SB0) __trap();
        const uint32_t bar = sb + C_BAR;
        for (int i = 0; i < B_NUM; i++) mbar_init(bar + i * 8, i == B_MBF ? 12 : (i == B_GO ? 4 : 1));
        mbar_expect(bar + B_MF0 * 8, 8192);
        mbar_expect(bar + B_MF1 * 8, 8192);
        if (role == 2) {
            mbar_expect(bar + B_SC * 8, 2560);
            mbar_expect(bar + B_P0 * 8, 2048);
            mbar_expect(bar + B_P1 * 8, 2048);
            mbar_expect(bar + B_OF * 8, ONKV * (256 + 2048));
        } else {
            mbar_expect(bar + B_XS * 8, role ? 5120 : 3072);
            mbar_expect(bar + B_OL * 8, 3072);
            mbar_expect(bar + B_OF * 8, ONKQ * (256 + 2048));
        }
        asm volatile("fence.mbarrier_init.release.cluster;" ::: "memory");
        fence_async();
        for (int j = 0; j < 3; j++) load_chunk(tA, tB, cl, rank, sb + j * 65536, j, bar + (B_W0 + j) * 8);
    }
    __syncwarp();
    asm volatile("barrier.cluster.arrive.release.aligned;" ::: "memory");
    reset_exchange(mem0);
#pragma unroll 1
    for (int row = gw; row < SEQ; row += 768) {
        uint4 v[4];
#pragma unroll
        for (int j = 0; j < 4; j++) {
            v[j] = cur[j]; cur[j] = nxt[j];
            if (row + 1536 < SEQ) nxt[j] = reinterpret_cast<const uint4*>(x)[(row + 1536) * 128 + j * 32 + lane];
        }
        ln_row(v, row, lane);
    }
    if (tid == 0) TL(1, 5);
    __syncthreads();
    uint32_t goal = 0;
    if (tid == 160) {
        __threadfence();
        goal = (atomicAdd(&g_epoch, 1u) / 96 + 1) * 96;
        asm volatile("griddepcontrol.launch_dependents;" ::: "memory");
        TL(1, 4);
    }
    __syncwarp();
    asm volatile("barrier.cluster.wait.acquire.aligned;" ::: "memory");
    goal = uni(goal);
    const int wg = uni(threadIdx.x >> 7);
    if (role == 2) {
        if (wg == 0) chain_main<true, 0>(&tv, &tv, &two, sb, cl, rank, DV, goal);
        else chain_main<true, 1>(&tv, &tv, &two, sb, cl, rank, DV, goal);
    } else {
        if (wg == 0) chain_main<false, 0>(&tq, &tk, &two, sb, cl, rank, D, goal);
        else chain_main<false, 1>(&tq, &tk, &two, sb, cl, rank, D, goal);
    }
    __syncwarp();
    cluster_sync();
    if (threadIdx.x == 0) TL(1, 1);
}

__device__ __forceinline__ void wg256(float* d, uint32_t da, uint32_t db, uint32_t accum) {
    asm volatile("{\n.reg .b64 da, db;\n.reg .pred p;\nsetp.ne.u32 p, %130, 0;\nmov.b64 da, {%128, " DESC_HI_SW128 "};\nmov.b64 db, {%129, " DESC_HI_SW128 "};\n"
                 "wgmma.mma_async.sync.aligned.m64n256k16.f32.bf16.bf16 {"
                 "%0,%1,%2,%3,%4,%5,%6,%7,%8,%9,%10,%11,%12,%13,%14,%15,%16,%17,%18,%19,%20,%21,%22,%23,%24,%25,%26,%27,%28,%29,%30,%31,"
                 "%32,%33,%34,%35,%36,%37,%38,%39,%40,%41,%42,%43,%44,%45,%46,%47,%48,%49,%50,%51,%52,%53,%54,%55,%56,%57,%58,%59,%60,%61,%62,%63,"
                 "%64,%65,%66,%67,%68,%69,%70,%71,%72,%73,%74,%75,%76,%77,%78,%79,%80,%81,%82,%83,%84,%85,%86,%87,%88,%89,%90,%91,%92,%93,%94,%95,"
                 "%96,%97,%98,%99,%100,%101,%102,%103,%104,%105,%106,%107,%108,%109,%110,%111,%112,%113,%114,%115,%116,%117,%118,%119,%120,%121,%122,%123,%124,%125,%126,%127"
                 "}, da, db, p, 1, 1, 0, 1;\n}"
                 : ACC16(d), ACC16((d + 16)), ACC16((d + 32)), ACC16((d + 48)), ACC16((d + 64)), ACC16((d + 80)), ACC16((d + 96)), ACC16((d + 112))
                 : "r"(da), "r"(db), "r"(accum));
}
__device__ __forceinline__ void wg128(float* d, uint32_t da, uint32_t db, uint32_t accum) {
    asm volatile("{\n.reg .b64 da, db;\n.reg .pred p;\nsetp.ne.u32 p, %66, 0;\nmov.b64 da, {%64, " DESC_HI_SW128 "};\nmov.b64 db, {%65, " DESC_HI_SW128 "};\n"
                 "wgmma.mma_async.sync.aligned.m64n128k16.f32.bf16.bf16 {"
                 "%0,%1,%2,%3,%4,%5,%6,%7,%8,%9,%10,%11,%12,%13,%14,%15,%16,%17,%18,%19,%20,%21,%22,%23,%24,%25,%26,%27,%28,%29,%30,%31,"
                 "%32,%33,%34,%35,%36,%37,%38,%39,%40,%41,%42,%43,%44,%45,%46,%47,%48,%49,%50,%51,%52,%53,%54,%55,%56,%57,%58,%59,%60,%61,%62,%63"
                 "}, da, db, p, 1, 1, 0, 1;\n}"
                 : ACC16(d), ACC16((d + 16)), ACC16((d + 32)), ACC16((d + 48))
                 : "r"(da), "r"(db), "r"(accum));
}
__device__ __forceinline__ float sigmoidf_(float v) { return rcp(1.f + ex2(-1.4426950408889634f * v)); }
__device__ __forceinline__ void wait_count(int idx, uint32_t n) {
    uint32_t v, it = 0;
    while (true) {
        asm volatile("ld.acquire.gpu.global.u32 %0, [%1];" : "=r"(v) : "l"(&g_cnt[idx * 8]) : "memory");
        if (v >= n) break;
        __nanosleep(100);
        spin_guard(it);
    }
    asm volatile("fence.proxy.async.global;" ::: "memory");
}

constexpr int G_STAGES = 4, G_PAIRS = 18;
constexpr uint32_t G_STAGE = 49152, G_EPI = G_STAGES * G_STAGE, G_BAR = G_EPI + 32768, G_SMEM = G_BAR + 256;
__device__ __forceinline__ int glu_job(int p, int j) {
    if (j < 12) return j * G_PAIRS + p;
    if (p < 14) return j == 12 ? 224 + p : (j == 13 ? 242 + p : -1);
    return j < 14 ? 216 + (j - 12) * 4 + (p - 14) : (j == 14 ? 224 + p : -1);
}

__global__ void __cluster_dims__(2, 1, 1) __launch_bounds__(384, 1)
glu_kernel(const __grid_constant__ CUtensorMap tXn, const __grid_constant__ CUtensorMap tG, const __grid_constant__ CUtensorMap tU,
           const __grid_constant__ CUtensorMap tHst, const __grid_constant__ CUtensorMap tHld, const __grid_constant__ CUtensorMap tD,
           const __grid_constant__ CUtensorMap tYst) {
    extern __shared__ __align__(1024) uint8_t smem[];
    const uint32_t sb = smem_u32(smem);
    const uint32_t full = sb + G_BAR, empty = full + 64;
    const int tid = threadIdx.x, lane = tid & 31;
    const int warp = uni(tid >> 5), wg = warp >> 2;
    const int rank = blockIdx.x & 1, pair = blockIdx.x >> 1;
    asm volatile("griddepcontrol.launch_dependents;" ::: "memory");
    if (tid == 0) {
        TL(2, 0); TLSM(2);
        for (int i = 0; i < G_STAGES; i++) { mbar_init(full + i * 8, 1); mbar_init(empty + i * 8, 16); }
        asm volatile("fence.mbarrier_init.release.cluster;" ::: "memory");
        fence_async();
    }
    __syncthreads();
    cluster_sync();
    if (wg == 0) {
        asm volatile("setmaxnreg.dec.sync.aligned.u32 40;");
        if (warp == 0) {
            if (lane == 0) {
                uint32_t st = 0, ph = 1;
                asm volatile("fence.acq_rel.gpu;\nfence.proxy.async.global;" ::: "memory");
                for (int j = 0, job; (job = glu_job(pair, j)) >= 0; j++) {
                    const bool dn = job >= 224;
                    const int mp = dn ? (job - 224) >> 2 : job / 28, nt = dn ? job & 3 : job % 28, rb = mp * 2 + rank;
                    const CUtensorMap* tA = dn ? &tHld : &tXn;
                    const CUtensorMap* tB = dn ? &tD : (rank ? &tU : &tG);
                    const int bcol = dn ? nt * 256 + rank * 128 : nt * 128, nkb = dn ? FF / 64 : DM / 64;
                    if (j == 12) TL(2, 2);
                    if (dn) wait_count(CNT_H + rb, 56);
                    for (int kb = 0; kb < nkb; kb++) {
                        mbar_wait(empty + st * 8, ph);
                        const uint32_t base = sb + st * G_STAGE;
                        mbar_expect(full + st * 8, G_STAGE);
                        tma2d(base, tA, kb * 64, rb * 128, full + st * 8);
                        tma2d_mc(base + 16384 + rank * 16384, tB, bcol, kb * 64, full + st * 8, 3);
                        tma2d_mc(base + 16384 + rank * 16384 + 8192, tB, bcol + 64, kb * 64, full + st * 8, 3);
                        if (++st == G_STAGES) { st = 0; ph ^= 1; }
                    }
                }
            }
        } else if (warp < 3) {
            const int cw = warp - 1;
            const uint32_t epi = sb + G_EPI + cw * 16384;
            bar_arrive(3 + cw, 160);
            for (int j = 0, job; (job = glu_job(pair, j)) >= 0; j++) {
                const bool dn = job >= 224;
                const int mp = dn ? (job - 224) >> 2 : job / 28, nt = dn ? job & 3 : job % 28, rb = mp * 2 + rank;
                for (int hp = 0; hp <= (int)dn; hp++) {
                    bar_sync(1 + cw, 160);
                    if (lane == 0) {
                        const int col = dn ? nt * 256 + hp * 128 : nt * 128;
                        tma2d_store(dn ? &tYst : &tHst, col, rb * 128 + cw * 64, epi);
                        tma2d_store(dn ? &tYst : &tHst, col + 64, rb * 128 + cw * 64, epi + 8192);
                        asm volatile("cp.async.bulk.commit_group;\ncp.async.bulk.wait_group.read 0;" ::: "memory");
                    }
                    __syncwarp();
                    bar_arrive(3 + cw, 160);
                    if (lane == 0) {
                        asm volatile("cp.async.bulk.wait_group 0;\nfence.proxy.async.global;" ::: "memory");
                        count_up(dn ? CNT_Y + rb * 8 + nt * 2 + hp : CNT_H + rb);
                    }
                    __syncwarp();
                }
            }
        }
        cluster_sync();
    } else {
        asm volatile("setmaxnreg.inc.sync.aligned.u32 232;");
        const int cw = wg - 1, w4 = warp & 3;
        const uint32_t empty_dst = mapa(empty, lane & 1);
        const int er = w4 * 16 + (lane & 15), ec = lane >> 4;
        const uint32_t epi = sb + G_EPI + cw * 16384 + er * 128;
        uint32_t st = 0, ph = 0;
        float acc[128];
        auto put = [&](const uint32_t* o) {
            bar_sync(3 + cw, 160);
#pragma unroll
            for (int q = 0; q < 8; q++) stsm4(epi + (q >> 2) * 8192 + (((2 * (q & 3) + ec) ^ (er & 7)) << 4), o[q * 4], o[q * 4 + 1], o[q * 4 + 2], o[q * 4 + 3]);
            fence_async();
            bar_arrive(1 + cw, 160);
        };
        for (int j = 0, job; (job = glu_job(pair, j)) >= 0; j++) {
            const bool dn = job >= 224;
            const int nkb = dn ? FF / 64 : DM / 64;
            uint32_t prev = 0;
#pragma unroll 1
            for (int kb = 0; kb < nkb; kb++) {
                mbar_wait(full + st * 8, ph);
                const uint32_t base = sb + st * G_STAGE;
                const uint32_t da = (((base + cw * 8192) & 0x3FFFF) >> 4) | (1u << 16);
                const uint32_t db = (((base + 16384) & 0x3FFFF) >> 4) | (512u << 16);
                wg_fence();
#pragma unroll
                for (int k = 0; k < 4; k++) wg256(acc, da + k * 2, db + k * 128, (kb | k) != 0);
                wg_commit();
                if (kb > 0) {
                    wg_wait<1>();
                    if (lane < 2) mbar_arrive_cluster(empty_dst + prev * 8);
                }
                prev = st;
                if (++st == G_STAGES) { st = 0; ph ^= 1; }
            }
            wg_wait<0>();
            reg_fence<128>(acc);
            if (lane < 2) mbar_arrive_cluster(empty_dst + prev * 8);
            uint32_t o[32];
            if (!dn) {
#pragma unroll
                for (int i = 0; i < 32; i++) o[i] = pack2(sigmoidf_(acc[2 * i]) * acc[64 + 2 * i], sigmoidf_(acc[2 * i + 1]) * acc[65 + 2 * i]);
                put(o);
            } else {
#pragma unroll
                for (int hp = 0; hp < 2; hp++) {
#pragma unroll
                    for (int i = 0; i < 32; i++) {
                        const float a = acc[hp * 64 + 2 * i], b = acc[hp * 64 + 2 * i + 1];
                        o[i] = pack2(sigmoidf_(a) * a, sigmoidf_(b) * b);
                    }
                    put(o);
                }
            }
        }
        bar_sync(3 + cw, 160);
        if (tid == 128) TL(2, 1);
        cluster_sync();
    }
}

constexpr int O_STAGES = 7;
constexpr uint32_t O_STAGE = 32768, O_BAR = O_STAGES * O_STAGE, O_SMEM = O_BAR + 256;

__global__ void __cluster_dims__(2, 1, 1) __launch_bounds__(384, 1)
out_kernel(const __grid_constant__ CUtensorMap tOx, const __grid_constant__ CUtensorMap tWo, const __grid_constant__ CUtensorMap tX,
           const __grid_constant__ CUtensorMap tY, const __grid_constant__ CUtensorMap tOut) {
    extern __shared__ __align__(1024) uint8_t smem[];
    const uint32_t sb = smem_u32(smem);
    const uint32_t full = sb + O_BAR, empty = full + 64;
    const int tid = threadIdx.x, lane = tid & 31;
    const int warp = uni(tid >> 5), wg = warp >> 2;
    const int rank = blockIdx.x & 1, nt = (blockIdx.x >> 1) & 7, rb = (blockIdx.x >> 4) * 2 + rank;
    constexpr int NKB = HD / 64;
    if (tid == 0) {
        TL(3, 0); TLSM(3);
        for (int i = 0; i < O_STAGES; i++) { mbar_init(full + i * 8, 1); mbar_init(empty + i * 8, 16); }
        asm volatile("fence.mbarrier_init.release.cluster;" ::: "memory");
        fence_async();
    }
    __syncthreads();
    cluster_sync();
    if (wg == 0) {
        if (tid == 0) {
            uint32_t st = 0, ph = 1;
            for (int kb = 0; kb < O_STAGES; kb++) {
                mbar_expect(full + kb * 8, O_STAGE);
                tma2d_mc(sb + kb * O_STAGE + 16384 + rank * 8192, &tWo, nt * 128 + rank * 64, kb * 64, full + kb * 8, 3);
            }
            wait_count(CNT_OX + rb, 32);
            TL(3, 2);
            for (int kb = 0; kb < NKB + 2; kb++) {
                const uint32_t base = sb + st * O_STAGE;
                if (kb >= O_STAGES) {
                    mbar_wait(empty + st * 8, ph);
                    mbar_expect(full + st * 8, O_STAGE);
                }
                if (kb < NKB) {
                    tma2d(base, &tOx, kb * 64, rb * 128, full + st * 8);
                    if (kb >= O_STAGES) tma2d_mc(base + 16384 + rank * 8192, &tWo, nt * 128 + rank * 64, kb * 64, full + st * 8, 3);
                } else {
                    if (kb == NKB) wait_count(CNT_Y + rb * 8 + nt, 2);
                    tma2d(base, &tX, nt * 128 + (kb - NKB) * 64, rb * 128, full + st * 8);
                    tma2d(base + 16384, &tY, nt * 128 + (kb - NKB) * 64, rb * 128, full + st * 8);
                }
                if (++st == O_STAGES) { st = 0; ph ^= 1; }
            }
        }
        __syncwarp();
    } else {
        const int cw = wg - 1, w4 = warp & 3;
        const uint32_t empty_dst = mapa(empty, lane & 1);
        const int er = cw * 64 + w4 * 16 + (lane & 15), ec = lane >> 4;
        uint32_t st = 0, ph = 0, prev = 0;
        float acc[64];
#pragma unroll 1
        for (int kb = 0; kb < NKB; kb++) {
            mbar_wait(full + st * 8, ph);
            const uint32_t base = sb + st * O_STAGE;
            const uint32_t da = (((base + cw * 8192) & 0x3FFFF) >> 4) | (1u << 16);
            const uint32_t db = (((base + 16384) & 0x3FFFF) >> 4) | (512u << 16);
            wg_fence();
#pragma unroll
            for (int k = 0; k < 4; k++) wg128(acc, da + k * 2, db + k * 128, (kb | k) != 0);
            wg_commit();
            if (kb > 0) {
                wg_wait<1>();
                if (lane < 2) mbar_arrive_cluster(empty_dst + prev * 8);
            }
            prev = st;
            if (++st == O_STAGES) { st = 0; ph ^= 1; }
        }
        wg_wait<0>();
        reg_fence<64>(acc);
#pragma unroll
        for (int bx = 0; bx < 2; bx++) {
            mbar_wait(full + st * 8, ph);
            const uint32_t base = sb + st * O_STAGE;
#pragma unroll
            for (int j = 0; j < 4; j++) {
                uint32_t xv[4], yv[4];
                const uint32_t ad = base + er * 128 + (((2 * j + ec) ^ (er & 7)) << 4);
                ldsm4(xv, ad); ldsm4(yv, ad + 16384);
                const float* a = acc + bx * 32 + j * 8;
#pragma unroll
                for (int i = 0; i < 4; i++)
                    xv[i] = pack2(fmaf(a[2 * i], bf_lo(yv[i]), bf_lo(xv[i])), fmaf(a[2 * i + 1], bf_hi(yv[i]), bf_hi(xv[i])));
                stsm4(ad, xv[0], xv[1], xv[2], xv[3]);
            }
            fence_async();
            bar_sync(1 + cw, 128);
            if ((tid & 127) == 0) {
                tma2d_store(&tOut, nt * 128 + bx * 64, rb * 128 + cw * 64, base + cw * 8192);
                asm volatile("cp.async.bulk.commit_group;" ::: "memory");
            }
            if (++st == O_STAGES) { st = 0; ph ^= 1; }
        }
        if ((tid & 127) == 0) asm volatile("cp.async.bulk.wait_group 0;" ::: "memory");
        if (tid == 128) TL(3, 1);
        __syncwarp();
    }
    cluster_sync();
}

typedef CUresult (*EncodeFn)(CUtensorMap*, CUtensorMapDataType, cuuint32_t, void*, const cuuint64_t*, const cuuint64_t*, const cuuint32_t*,
                             const cuuint32_t*, CUtensorMapInterleave, CUtensorMapSwizzle, CUtensorMapL2promotion, CUtensorMapFloatOOBfill);

CUtensorMap make_map(EncodeFn enc, const void* p, int rows, int cols, int box_rows) {
    CUtensorMap m;
    cuuint64_t dims[2] = {(cuuint64_t)cols, (cuuint64_t)rows}, strides[1] = {(cuuint64_t)cols * 2};
    cuuint32_t box[2] = {64, (cuuint32_t)box_rows}, es[2] = {1, 1};
    enc(&m, CU_TENSOR_MAP_DATA_TYPE_BFLOAT16, 2, const_cast<void*>(p), dims, strides, box, es, CU_TENSOR_MAP_INTERLEAVE_NONE,
        CU_TENSOR_MAP_SWIZZLE_128B, CU_TENSOR_MAP_L2_PROMOTION_L2_128B, CU_TENSOR_MAP_FLOAT_OOB_FILL_NONE);
    return m;
}

}

#define PDL 7
extern "C" void kernel_launch(void* const* d_in, const int* in_sizes, int n_in, void* d_out, int out_size) {
    const __nv_bfloat16* x = (const __nv_bfloat16*)d_in[0];
    const __nv_bfloat16* mem0 = (const __nv_bfloat16*)d_in[1];
    void* fn = nullptr;
    cudaDriverEntryPointQueryResult qr;
    cudaGetDriverEntryPoint("cuTensorMapEncodeTiled", &fn, cudaEnableDefault, &qr);
    EncodeFn enc = (EncodeFn)fn;
    void *xn, *ox, *h, *y;
    cudaGetSymbolAddress(&xn, g_xn); cudaGetSymbolAddress(&ox, g_ox); cudaGetSymbolAddress(&h, g_h); cudaGetSymbolAddress(&y, g_y);

    const CUtensorMap tq = make_map(enc, d_in[2], DM, HD, 128), tk = make_map(enc, d_in[3], DM, HD, 128), tv = make_map(enc, d_in[4], DM, HD, 128);
    const CUtensorMap two16 = make_map(enc, d_in[5], HD, DM, 16);
    const CUtensorMap txn128 = make_map(enc, xn, SEQ, DM, 128), tg = make_map(enc, d_in[8], DM, FF, 64), tu = make_map(enc, d_in[9], DM, FF, 64);
    const CUtensorMap th64 = make_map(enc, h, SEQ, FF, 64), th128 = make_map(enc, h, SEQ, FF, 128), td = make_map(enc, d_in[10], FF, DM, 64);
    const CUtensorMap ty64 = make_map(enc, y, SEQ, DM, 64), ty128 = make_map(enc, y, SEQ, DM, 128), tx128 = make_map(enc, x, SEQ, DM, 128);
    const CUtensorMap tox = make_map(enc, ox, SEQ, HD, 128), two64 = make_map(enc, d_in[5], HD, DM, 64), tout = make_map(enc, d_out, SEQ, DM, 64);

    cudaFuncSetAttribute(chain_kernel, cudaFuncAttributeMaxDynamicSharedMemorySize, C_SMEM);
    cudaFuncSetAttribute(glu_kernel, cudaFuncAttributeMaxDynamicSharedMemorySize, G_SMEM);
    cudaFuncSetAttribute(out_kernel, cudaFuncAttributeMaxDynamicSharedMemorySize, O_SMEM);

    Descs D;
    for (int i = 0; i < 4; i++) D.sw[i] = DSW;
    D.ns = DNS;
    cudaStream_t st = cudaStreamPerThread;
    cudaLaunchAttribute at;
    at.id = cudaLaunchAttributeProgrammaticStreamSerialization;
    at.val.programmaticStreamSerializationAllowed = 1;
    cudaLaunchConfig_t cfg = {};
    cfg.stream = st; cfg.attrs = &at; cfg.numAttrs = 0;
    cfg.gridDim = dim3(96); cfg.blockDim = dim3(256); cfg.dynamicSmemBytes = C_SMEM;
    cudaLaunchKernelEx(&cfg, chain_kernel, tq, tk, tv, two16, D, D, x, mem0);
    cfg.gridDim = dim3(2 * G_PAIRS); cfg.blockDim = dim3(384); cfg.dynamicSmemBytes = G_SMEM; cfg.numAttrs = (PDL >> 1) & 1;
    cudaLaunchKernelEx(&cfg, glu_kernel, txn128, tg, tu, th64, th128, td, ty64);
    cfg.gridDim = dim3(128); cfg.dynamicSmemBytes = O_SMEM; cfg.numAttrs = (PDL >> 2) & 1;
    cudaLaunchKernelEx(&cfg, out_kernel, tox, two64, tx128, ty128, tout);
}
```

```cpp
#include <cuda_runtime.h>
#include <cuda_bf16.h>
#include <cuda.h>
#include <stdint.h>
#include <type_traits>

namespace {

constexpr int SEQ = 2048, DM = 1024, HD = 4096, FF = 3584, NSEG = 64;

__device__ __align__(1024) __nv_bfloat16 g_xn[SEQ * DM];
__device__ __align__(1024) uint4 g_xc[SEQ * DM / 8];
__device__ __align__(1024) __nv_bfloat16 g_ox[SEQ * HD];
__device__ __align__(1024) __nv_bfloat16 g_h[SEQ * FF];
__device__ __align__(1024) __nv_bfloat16 g_y[SEQ * DM];
__device__ __align__(1024) uint4 g_xmem[4][1024];
__device__ __align__(1024) uint4 g_xo[4][4096];
#define FSTR 8
__device__ __align__(1024) uint32_t g_flag[2][96 * FSTR];
enum { CNT_H = 0, CNT_OX = 16, CNT_Y = 32, CNT_NUM = 160 };
__device__ __align__(1024) uint32_t g_cnt[CNT_NUM * 8];
__device__ __align__(128) uint32_t g_epoch;
#define TL(k, i)
#define TLSM(k)

__device__ __forceinline__ uint32_t smem_u32(const void* p) { return (uint32_t)__cvta_generic_to_shared(p); }
__device__ __forceinline__ uint32_t mapa(uint32_t a, uint32_t r) {
    uint32_t o; asm("mapa.shared::cluster.u32 %0, %1, %2;" : "=r"(o) : "r"(a), "r"(r)); return o;
}
__device__ __forceinline__ void mbar_init(uint32_t a, uint32_t cnt) {
    asm volatile("mbarrier.init.shared.b64 [%0], %1;" :: "r"(a), "r"(cnt) : "memory");
}
__device__ __forceinline__ void mbar_expect(uint32_t a, uint32_t bytes) {
    asm volatile("mbarrier.arrive.expect_tx.shared.b64 _, [%0], %1;" :: "r"(a), "r"(bytes) : "memory");
}
__device__ __forceinline__ void mbar_arrive_cluster(uint32_t a) {
    asm volatile("mbarrier.arrive.shared::cluster.b64 _, [%0];" :: "r"(a) : "memory");
}
__device__ __forceinline__ void spin_guard(uint32_t& it) {
    asm volatile("{\n.reg .pred p;\nadd.u32 %0, %0, 1;\nsetp.gt.u32 p, %0, 0x400000;\n@p st.shared.u32 [%0], %0;\n}" : "+r"(it));
}
__device__ __forceinline__ void mbar_wait(uint32_t a, uint32_t par) {
    asm volatile("{\n.reg .pred p;\n.reg .u32 i;\nmov.u32 i, 0;\n"
                 "WL:\nadd.u32 i, i, 1;\nsetp.gt.u32 p, i, 0x400000;\n@p st.shared.u32 [i], i;\n"
                 "mbarrier.try_wait.parity.shared::cta.b64 p, [%0], %1;\n@!p bra WL;\n}" :: "r"(a), "r"(par) : "memory");
}
__device__ __forceinline__ void mbar_arrive(uint32_t a) { asm volatile("mbarrier.arrive.shared.b64 _, [%0];" :: "r"(a) : "memory"); }
__device__ __forceinline__ void tma2d(uint32_t dst, const CUtensorMap* m, int c0, int c1, uint32_t bar) {
    asm volatile("cp.async.bulk.tensor.2d.shared::cluster.global.mbarrier::complete_tx::bytes [%0], [%1, {%3, %4}], [%2];"
                 :: "r"(dst), "l"(m), "r"(bar), "r"(c0), "r"(c1) : "memory");
}
__device__ __forceinline__ void tma2d_mc(uint32_t dst, const CUtensorMap* m, int c0, int c1, uint32_t bar, uint16_t mask) {
    asm volatile("cp.async.bulk.tensor.2d.shared::cluster.global.mbarrier::complete_tx::bytes.multicast::cluster [%0], [%1, {%3, %4}], [%2], %5;"
                 :: "r"(dst), "l"(m), "r"(bar), "r"(c0), "r"(c1), "h"(mask) : "memory");
}
__device__ __forceinline__ void bulk_mc(uint32_t dst, const void* src, uint32_t bytes, uint32_t bar, uint16_t mask) {
    asm volatile("cp.async.bulk.shared::cluster.global.mbarrier::complete_tx::bytes.multicast::cluster [%0], [%1], %2, [%3], %4;"
                 :: "r"(dst), "l"(src), "r"(bytes), "r"(bar), "h"(mask) : "memory");
}
__device__ __forceinline__ void bulk_ld(uint32_t dst, const void* src, uint32_t bytes, uint32_t bar) {
    asm volatile("cp.async.bulk.shared::cluster.global.mbarrier::complete_tx::bytes [%0], [%1], %2, [%3];"
                 :: "r"(dst), "l"(src), "r"(bytes), "r"(bar) : "memory");
}
__device__ __forceinline__ uint32_t gtick() { uint64_t c; asm volatile("mov.u64 %0, %%globaltimer;" : "=l"(c)); return (uint32_t)c >> 5; }
__device__ __forceinline__ uint32_t gtick_dep(uint32_t zero) {
    uint32_t c;
    asm volatile("{\n.reg .pred p;\nsetp.eq.u32 p, %1, 0;\nmov.u32 %0, 0;\n@p mov.u32 %0, %%globaltimer_lo;\n}" : "=r"(c) : "r"(zero));
    return c >> 5;
}
__device__ __forceinline__ uint32_t ld_relaxed1(const void* p) {
    uint32_t v; asm volatile("ld.relaxed.gpu.global.u32 %0, [%1];" : "=r"(v) : "l"(p) : "memory"); return v;
}
__device__ __forceinline__ bool any_nan(float a, float b) {
    uint32_t r;
    asm volatile("{\n.reg .pred p;\nsetp.nan.f32 p, %1, %2;\nvote.sync.any.pred p, p, 0xffffffff;\nselp.u32 %0, 1, 0, p;\n}" : "=r"(r) : "f"(a), "f"(b));
    return r;
}
__device__ __forceinline__ bool bar_sync_any_nan(float a, float b) {
    uint32_t r;
    asm volatile("{\n.reg .pred p;\nsetp.nan.f32 p, %1, %2;\nbarrier.cta.red.or.aligned.pred p, 6, 256, p;\nselp.u32 %0, 1, 0, p;\n}"
                 : "=r"(r) : "f"(a), "f"(b) : "memory");
    return r;
}
__device__ __forceinline__ void bar_arrive(int id, int n) { asm volatile("bar.arrive %0, %1;" :: "r"(id), "r"(n) : "memory"); }
__device__ __forceinline__ uint32_t clk() { uint64_t c; asm volatile("mov.u64 %0, %%clock64;" : "=l"(c)); return (uint32_t)c; }
__device__ __forceinline__ void tma2d_store(const CUtensorMap* m, int c0, int c1, uint32_t src) {
    asm volatile("cp.async.bulk.tensor.2d.global.shared::cta.bulk_group [%0, {%1, %2}], [%3];"
                 :: "l"(m), "r"(c0), "r"(c1), "r"(src) : "memory");
}
__device__ __forceinline__ void bar_sync(int id, int n) { asm volatile("bar.sync %0, %1;" :: "r"(id), "r"(n) : "memory"); }
__device__ __forceinline__ void fence_async() { asm volatile("fence.proxy.async.shared::cta;" ::: "memory"); }
__device__ __forceinline__ void cluster_sync() {
    asm volatile("barrier.cluster.arrive.release.aligned;\nbarrier.cluster.wait.acquire.aligned;" ::: "memory");
}
__device__ __forceinline__ void ldsm4(uint32_t* r, uint32_t a) {
    asm volatile("ldmatrix.sync.aligned.m8n8.x4.shared.b16 {%0,%1,%2,%3}, [%4];"
                 : "=r"(r[0]), "=r"(r[1]), "=r"(r[2]), "=r"(r[3]) : "r"(a) : "memory");
}
__device__ __forceinline__ void ldsm4t(uint32_t* r, uint32_t a) {
    asm volatile("ldmatrix.sync.aligned.m8n8.x4.trans.shared.b16 {%0,%1,%2,%3}, [%4];"
                 : "=r"(r[0]), "=r"(r[1]), "=r"(r[2]), "=r"(r[3]) : "r"(a) : "memory");
}
__device__ __forceinline__ void stsm4(uint32_t a, uint32_t r0, uint32_t r1, uint32_t r2, uint32_t r3) {
    asm volatile("stmatrix.sync.aligned.m8n8.x4.shared.b16 [%0], {%1,%2,%3,%4};" :: "r"(a), "r"(r0), "r"(r1), "r"(r2), "r"(r3) : "memory");
}
__device__ __forceinline__ void stsm4t(uint32_t a, uint32_t r0, uint32_t r1, uint32_t r2, uint32_t r3) {
    asm volatile("stmatrix.sync.aligned.m8n8.x4.trans.shared.b16 [%0], {%1,%2,%3,%4};" :: "r"(a), "r"(r0), "r"(r1), "r"(r2), "r"(r3) : "memory");
}
__device__ __forceinline__ void stsm2(uint32_t a, uint32_t r0, uint32_t r1) {
    asm volatile("stmatrix.sync.aligned.m8n8.x2.shared.b16 [%0], {%1,%2};" :: "r"(a), "r"(r0), "r"(r1) : "memory");
}
__device__ __forceinline__ void stsm2t(uint32_t a, uint32_t r0, uint32_t r1) {
    asm volatile("stmatrix.sync.aligned.m8n8.x2.trans.shared.b16 [%0], {%1,%2};" :: "r"(a), "r"(r0), "r"(r1) : "memory");
}
__device__ __forceinline__ uint32_t movm(uint32_t a) {
    uint32_t d; asm volatile("movmatrix.sync.aligned.m8n8.trans.b16 %0, %1;" : "=r"(d) : "r"(a)); return d;
}
__device__ __forceinline__ void mma16(float* d, uint32_t a0, uint32_t a1, uint32_t a2, uint32_t a3, uint32_t b0, uint32_t b1) {
    asm volatile("mma.sync.aligned.m16n8k16.row.col.f32.bf16.bf16.f32 {%0,%1,%2,%3}, {%4,%5,%6,%7}, {%8,%9}, {%0,%1,%2,%3};"
                 : "+f"(d[0]), "+f"(d[1]), "+f"(d[2]), "+f"(d[3]) : "r"(a0), "r"(a1), "r"(a2), "r"(a3), "r"(b0), "r"(b1));
}
__device__ __forceinline__ void mma8(float* d, uint32_t a0, uint32_t a1, uint32_t b0) {
    asm volatile("mma.sync.aligned.m16n8k8.row.col.f32.bf16.bf16.f32 {%0,%1,%2,%3}, {%4,%5}, {%6}, {%0,%1,%2,%3};"
                 : "+f"(d[0]), "+f"(d[1]), "+f"(d[2]), "+f"(d[3]) : "r"(a0), "r"(a1), "r"(b0));
}
__device__ __forceinline__ uint32_t pack2(float lo, float hi) {
    uint32_t r; asm("cvt.rn.bf16x2.f32 %0, %1, %2;" : "=r"(r) : "f"(hi), "f"(lo)); return r;
}
__device__ __forceinline__ float bf_lo(uint32_t v) { return __uint_as_float(v << 16); }
__device__ __forceinline__ float bf_hi(uint32_t v) { return __uint_as_float(v & 0xFFFF0000u); }
__device__ __forceinline__ float ex2(float x) { float y; asm("ex2.approx.ftz.f32 %0, %1;" : "=f"(y) : "f"(x)); return y; }
__device__ __forceinline__ float rcp(float x) { float y; asm("rcp.approx.ftz.f32 %0, %1;" : "=f"(y) : "f"(x)); return y; }
__device__ __forceinline__ void sts4f(uint32_t a, float x, float y, float z, float w) {
    asm volatile("st.shared.v4.f32 [%0], {%1,%2,%3,%4};" :: "r"(a), "f"(x), "f"(y), "f"(z), "f"(w) : "memory");
}
__device__ __forceinline__ void sts1u(uint32_t a, uint32_t v) { asm volatile("st.shared.u32 [%0], %1;" :: "r"(a), "r"(v) : "memory"); }
__device__ __forceinline__ void sts4u(uint32_t a, uint4 v) {
    asm volatile("st.shared.v4.u32 [%0], {%1,%2,%3,%4};" :: "r"(a), "r"(v.x), "r"(v.y), "r"(v.z), "r"(v.w) : "memory");
}
__device__ __forceinline__ float4 lds4f(uint32_t a) {
    float4 v; asm volatile("ld.shared.v4.f32 {%0,%1,%2,%3}, [%4];" : "=f"(v.x), "=f"(v.y), "=f"(v.z), "=f"(v.w) : "r"(a) : "memory"); return v;
}
__device__ __forceinline__ float2 lds2f(uint32_t a) {
    float2 v; asm volatile("ld.shared.v2.f32 {%0,%1}, [%2];" : "=f"(v.x), "=f"(v.y) : "r"(a) : "memory"); return v;
}
__device__ __forceinline__ uint4 lds4u(uint32_t a) {
    uint4 v; asm volatile("ld.shared.v4.u32 {%0,%1,%2,%3}, [%4];" : "=r"(v.x), "=r"(v.y), "=r"(v.z), "=r"(v.w) : "r"(a) : "memory"); return v;
}
__device__ __forceinline__ uint32_t lds1u(uint32_t a) {
    uint32_t v; asm volatile("ld.shared.u32 %0, [%1];" : "=r"(v) : "r"(a) : "memory"); return v;
}
__device__ __forceinline__ uint2 lds2u(uint32_t a) {
    uint2 v; asm volatile("ld.shared.v2.u32 {%0,%1}, [%2];" : "=r"(v.x), "=r"(v.y) : "r"(a) : "memory"); return v;
}
__device__ __forceinline__ void st_async4(uint32_t a, uint32_t bar, float x, float y, float z, float w) {
    asm volatile("st.async.shared::cluster.mbarrier::complete_tx::bytes.v4.f32 [%0], {%1,%2,%3,%4}, [%5];"
                 :: "r"(a), "f"(x), "f"(y), "f"(z), "f"(w), "r"(bar) : "memory");
}
__device__ __forceinline__ void st_async2(uint32_t a, uint32_t bar, float x, float y) {
    asm volatile("st.async.shared::cluster.mbarrier::complete_tx::bytes.v2.f32 [%0], {%1,%2}, [%3];"
                 :: "r"(a), "f"(x), "f"(y), "r"(bar) : "memory");
}
__device__ __forceinline__ void st_async1(uint32_t a, uint32_t bar, uint32_t x) {
    asm volatile("st.async.shared::cluster.mbarrier::complete_tx::bytes.b32 [%0], %1, [%2];" :: "r"(a), "r"(x), "r"(bar) : "memory");
}
__device__ __forceinline__ uint4 ld_relaxed4(const uint4* p) {
    uint4 v;
    asm volatile("ld.relaxed.gpu.global.v4.u32 {%0,%1,%2,%3}, [%4];" : "=r"(v.x), "=r"(v.y), "=r"(v.z), "=r"(v.w) : "l"(p) : "memory");
    return v;
}
__device__ __forceinline__ void st_relaxed4(uint4* p, uint4 v) {
    asm volatile("st.relaxed.gpu.global.v4.u32 [%0], {%1,%2,%3,%4};" :: "l"(p), "r"(v.x), "r"(v.y), "r"(v.z), "r"(v.w) : "memory");
}
__device__ __forceinline__ void count_up(int idx) {
    asm volatile("red.release.gpu.global.add.u32 [%0], 1;" :: "l"(&g_cnt[idx * 8]) : "memory");
}
__device__ __forceinline__ void st_pred1(void* p, uint32_t v, bool on) {
    asm volatile("{\n.reg .pred p;\nsetp.ne.u32 p, %2, 0;\n@p st.relaxed.gpu.global.u32 [%0], %1;\n}" :: "l"(p), "r"(v), "r"((uint32_t)on) : "memory");
}
__device__ __forceinline__ void st_pred4(void* p, uint4 v, bool on) {
    asm volatile("{\n.reg .pred p;\nsetp.ne.u32 p, %5, 0;\n@p st.global.v4.u32 [%0], {%1,%2,%3,%4};\n}"
                 :: "l"(p), "r"(v.x), "r"(v.y), "r"(v.z), "r"(v.w), "r"((uint32_t)on) : "memory");
}
__device__ __forceinline__ void st_relaxed1(void* p, uint32_t v) {
    asm volatile("st.relaxed.gpu.global.u32 [%0], %1;" :: "l"(p), "r"(v) : "memory");
}
__device__ __forceinline__ uint32_t umax4(uint4 v) { return max(max(v.x, v.y), max(v.z, v.w)); }
__device__ __forceinline__ void wg_fence() { asm volatile("wgmma.fence.sync.aligned;" ::: "memory"); }
__device__ __forceinline__ void wg_commit() { asm volatile("wgmma.commit_group.sync.aligned;" ::: "memory"); }
template <int N> __device__ __forceinline__ void wg_wait() { asm volatile("wgmma.wait_group.sync.aligned %0;" :: "n"(N) : "memory"); }
template <int N> __device__ __forceinline__ void reg_fence(float* d) {
#pragma unroll
    for (int i = 0; i < N; i++) asm volatile("" : "+f"(d[i]) :: "memory");
}
#define ACC16(d) "+f"(d[0]), "+f"(d[1]), "+f"(d[2]), "+f"(d[3]), "+f"(d[4]), "+f"(d[5]), "+f"(d[6]), "+f"(d[7]), \
                 "+f"(d[8]), "+f"(d[9]), "+f"(d[10]), "+f"(d[11]), "+f"(d[12]), "+f"(d[13]), "+f"(d[14]), "+f"(d[15])
#define DESC_HI_SW128 "0x40000040"
#define OUT16(d) "=f"(d[0]), "=f"(d[1]), "=f"(d[2]), "=f"(d[3]), "=f"(d[4]), "=f"(d[5]), "=f"(d[6]), "=f"(d[7]), \
                 "=f"(d[8]), "=f"(d[9]), "=f"(d[10]), "=f"(d[11]), "=f"(d[12]), "=f"(d[13]), "=f"(d[14]), "=f"(d[15])
template <int ACCUM, int BOFF>
__device__ __forceinline__ void wg32_rs(float* d, const uint32_t* a, uint64_t dsw) {
    if (ACCUM)
        asm volatile("{\n.reg .b64 db;\nadd.s64 db, %20, %21;\n"
                     "wgmma.mma_async.sync.aligned.m64n32k16.f32.bf16.bf16 {%0,%1,%2,%3,%4,%5,%6,%7,%8,%9,%10,%11,%12,%13,%14,%15}, "
                     "{%16,%17,%18,%19}, db, 1, 1, 1, 0;\n}"
                     : ACC16(d) : "r"(a[0]), "r"(a[1]), "r"(a[2]), "r"(a[3]), "l"(dsw), "n"(BOFF));
    else
        asm volatile("{\n.reg .b64 db;\nadd.s64 db, %20, %21;\n"
                     "wgmma.mma_async.sync.aligned.m64n32k16.f32.bf16.bf16 {%0,%1,%2,%3,%4,%5,%6,%7,%8,%9,%10,%11,%12,%13,%14,%15}, "
                     "{%16,%17,%18,%19}, db, 0, 1, 1, 0;\n}"
                     : OUT16(d) : "r"(a[0]), "r"(a[1]), "r"(a[2]), "r"(a[3]), "l"(dsw), "n"(BOFF));
}
template <int AOFF, int BOFF>
__device__ __forceinline__ void wg32_ss(float* d, uint64_t dsw) {
    asm volatile("{\n.reg .b64 da, db;\nadd.s64 da, %16, %17;\nadd.s64 db, %16, %18;\n"
                 "wgmma.mma_async.sync.aligned.m64n32k16.f32.bf16.bf16 {%0,%1,%2,%3,%4,%5,%6,%7,%8,%9,%10,%11,%12,%13,%14,%15}, "
                 "da, db, 1, 1, 1, 1, 0;\n}"
                 : ACC16(d) : "l"(dsw), "n"(AOFF), "n"(BOFF));
}
template <int ACCUM, int AOFF, int BOFF>
__device__ __forceinline__ void wg8_ss(float* d, uint64_t dsw, uint64_t dns) {
    if (!ACCUM)
        asm volatile("{\n.reg .b64 da, db;\nadd.s64 da, %4, %6;\nadd.s64 db, %5, %7;\n"
                     "wgmma.mma_async.sync.aligned.m64n8k16.f32.bf16.bf16 {%0,%1,%2,%3}, da, db, 0, 1, 1, 1, 0;\n}"
                     : "=f"(d[0]), "=f"(d[1]), "=f"(d[2]), "=f"(d[3]) : "l"(dsw), "l"(dns), "n"(AOFF), "n"(BOFF));
    else
        asm volatile("{\n.reg .b64 da, db;\nadd.s64 da, %4, %6;\nadd.s64 db, %5, %7;\n"
                     "wgmma.mma_async.sync.aligned.m64n8k16.f32.bf16.bf16 {%0,%1,%2,%3}, da, db, 1, 1, 1, 1, 0;\n}"
                     : "+f"(d[0]), "+f"(d[1]), "+f"(d[2]), "+f"(d[3]) : "l"(dsw), "l"(dns), "n"(AOFF), "n"(BOFF));
}
template <int I0, int I1, class F>
__device__ __forceinline__ void static_for(F&& f) {
    if constexpr (I0 < I1) { f(std::integral_constant<int, I0>{}); static_for<I0 + 1, I1>(f); }
}
template <int I0, int I1, int AOFF, int BOFF>
__device__ __forceinline__ void wg8_chain(float* d, uint64_t dsw, uint64_t dns) {
    wg_fence();
    static_for<I0, I1>([&](auto i) { wg8_ss<i.value != 0, AOFF + i.value * 128, BOFF + i.value * 16>(d, dsw, dns); });
    wg_commit();
}

__device__ __forceinline__ void ln_row(const uint4* v, int row, int lane) {
    float f[32];
#pragma unroll
    for (int j = 0; j < 4; j++) {
        f[j * 8 + 0] = bf_lo(v[j].x); f[j * 8 + 1] = bf_hi(v[j].x); f[j * 8 + 2] = bf_lo(v[j].y); f[j * 8 + 3] = bf_hi(v[j].y);
        f[j * 8 + 4] = bf_lo(v[j].z); f[j * 8 + 5] = bf_hi(v[j].z); f[j * 8 + 6] = bf_lo(v[j].w); f[j * 8 + 7] = bf_hi(v[j].w);
    }
    float s = 0.f;
#pragma unroll
    for (int i = 0; i < 32; i++) s += f[i];
#pragma unroll
    for (int o = 16; o; o >>= 1) s += __shfl_xor_sync(~0u, s, o);
    const float mean = s * (1.f / DM);
    float q = 0.f;
#pragma unroll
    for (int i = 0; i < 32; i++) { f[i] -= mean; q += f[i] * f[i]; }
#pragma unroll
    for (int o = 16; o; o >>= 1) q += __shfl_xor_sync(~0u, q, o);
    const float r = 1.f / sqrtf(q * (1.f / DM) + 1e-5f);
    uint4* dst = reinterpret_cast<uint4*>(g_xn + (size_t)row * DM);
    uint4* dst2 = g_xc + (row >> 5) * 4096 + (lane >> 3) * 256 + (row & 31) * 8 + ((lane & 7) ^ (row & 7));
#pragma unroll
    for (int j = 0; j < 4; j++) {
        const uint4 o = make_uint4(pack2(f[j * 8] * r, f[j * 8 + 1] * r), pack2(f[j * 8 + 2] * r, f[j * 8 + 3] * r),
                                   pack2(f[j * 8 + 4] * r, f[j * 8 + 5] * r), pack2(f[j * 8 + 6] * r, f[j * 8 + 7] * r));
        dst[j * 32 + lane] = o;
        dst2[(j & 1) * 2048 + (j >> 1) * 1024] = o;
    }
}
__device__ __forceinline__ void reset_exchange(const __nv_bfloat16* __restrict__ mem0) {
    const int gi = blockIdx.x * 256 + threadIdx.x;
    const uint4 poison = make_uint4(~0u, ~0u, ~0u, ~0u);
    if (gi < 1024) {
        uint4 m = reinterpret_cast<const uint4*>(mem0)[(gi & 7) * 128 + (gi >> 3)];
        if (m.x == ~0u) m.x = 0x7FFF7FFFu;
        if (m.y == ~0u) m.y = 0x7FFF7FFFu;
        if (m.z == ~0u) m.z = 0x7FFF7FFFu;
        if (m.w == ~0u) m.w = 0x7FFF7FFFu;
        g_xmem[0][gi] = m;
    } else if (gi < 4096) {
        (&g_xmem[0][0])[gi] = poison;
    } else if (gi < 4096 + 16384) {
        (&g_xo[0][0])[gi - 4096] = poison;
    } else if (gi < 4096 + 16384 + 48 * FSTR) {
        reinterpret_cast<uint4*>(&g_flag[0][0])[gi - 4096 - 16384] = poison;
    } else if (gi >= 24576 - CNT_NUM) {
        g_cnt[(24575 - gi) * 8] = 0;
    }
}

#define ONKQ 45
constexpr int ONKV = 128 - 2 * ONKQ;
constexpr uint32_t SB0 = 1024;
constexpr uint32_t C_WS = 0, C_XN = 65536, C_MB = 98304, C_WO = 114688, C_SMEM = 232448;
constexpr uint32_t C_BAR = C_SMEM - 384, C_CAL = C_BAR + 192;
constexpr uint32_t C_SLOTQ = C_WO + ONKQ * 2048, C_QX = C_SLOTQ + 8192, C_KX = C_QX + 4096,
                   C_XSL = C_KX + 4096, C_OL = C_XSL + 5120;
constexpr uint32_t C_SLOTV = C_WO + ONKV * 2048, C_V = C_SLOTV + 8192, C_PL = C_V + 20480, C_SL = C_PL + 4096;
constexpr uint32_t C_DUMP = C_BAR - 512;
static_assert(C_OL + 3072 <= C_DUMP && C_SL + 2560 <= C_DUMP, "smem overflow");
enum { B_W0 = 0, B_W1, B_W2, B_WS, B_XF0, B_XF1, B_SC, B_P0, B_P1, B_XS, B_OL, B_MF0, B_MF1, B_OF, B_RT0, B_RT1, B_VF, B_MBF, B_GO, B_DUMP, B_NUM };
struct Descs { uint64_t sw[4], ns; };
constexpr uint64_t DSW = 0x4000004000010000ull, DNS = 0x0000001000080000ull;
template <int V> using ic = std::integral_constant<int, V>;
constexpr float SM_SCALE = 0.08838834764831845f * 1.4426950408889634f;

#define TSD(i) do {} while (0)
#define TS_FLUSH(w)
#define TSX(i, c)
#define TS(i)
#define NOFILL 0
#define DLY1 2160
#define DLY2 1320
#define CANARY ~0u
#define RB1 0
#define QK1 10
#define RFPOS 8
#define STPOS 14
#define OTAIL 3
#define DLYS 450
#define DLYB 1
#define VLEAD 1

#define VEARLY 8
#define QSPLIT 20
__device__ __forceinline__ bool elect() {
    uint32_t r;
    asm volatile("{\n.reg .pred p;\nelect.sync _|p, 0xffffffff;\nselp.u32 %0, 1, 0, p;\n}" : "=r"(r));
    return r;
}
__device__ __forceinline__ int uni(int v) { return __shfl_sync(~0u, v, 0); }
__device__ __forceinline__ void calibrate(uint32_t cal, float keep) {
    const uint32_t t0 = gtick();
    uint32_t t, it = 0;
    do { t = gtick(); spin_guard(it); } while (__any_sync(~0u, t == t0));
    const uint32_t c = clk();
    const uint4 p = lds4u(cal);
    const float cpt = 256.f * fminf(fmaxf(__fdividef((float)(c - p.y), (float)((t - p.x) & 0x7FFFFFF)), 16.f), 128.f);
    __syncwarp();
    sts4u(cal, make_uint4(t, c, (uint32_t)(keep > 0.f ? fmaf(keep, (float)p.z - cpt, cpt) : cpt), 0));
}
struct Stamps { uint32_t v[6]; };
__device__ __forceinline__ void load_stamps2(Stamps& t, const uint32_t* f, uint32_t l16, bool on = true) {
    const char* p = reinterpret_cast<const char*>(f) + (l16 >> 2) * FSTR;
    asm volatile("{\n.reg .pred p;\nsetp.ne.u32 p, %7, 0;\nmov.u32 %0, 63;\nmov.u32 %1, 63;\nmov.u32 %2, 63;\nmov.u32 %3, 63;\nmov.u32 %4, 63;\nmov.u32 %5, 63;\n"
                 "@p ld.relaxed.gpu.global.v2.u32 {%0, %1}, [%6];\n@p ld.relaxed.gpu.global.v2.u32 {%2, %3}, [%6 + %8];\n"
                 "@p ld.relaxed.gpu.global.v2.u32 {%4, %5}, [%6 + %9];\n}"
                 : "=&r"(t.v[0]), "=&r"(t.v[1]), "=&r"(t.v[2]), "=&r"(t.v[3]), "=&r"(t.v[4]), "=&r"(t.v[5])
                 : "l"(p), "r"((uint32_t)on), "n"(128 * FSTR), "n"(256 * FSTR) : "memory");
}
__device__ __forceinline__ void load_stamps1(uint32_t* v, const uint32_t* f, uint32_t l16, bool on = true) {
    const char* p = reinterpret_cast<const char*>(f) + (l16 >> 2) * FSTR;
    asm volatile("{\n.reg .pred p;\nsetp.ne.u32 p, %4, 0;\nmov.u32 %0, 63;\nmov.u32 %1, 63;\nmov.u32 %2, 63;\n"
                 "@p ld.relaxed.gpu.global.u32 %0, [%3];\n@p ld.relaxed.gpu.global.u32 %1, [%3 + %5];\n@p ld.relaxed.gpu.global.u32 %2, [%3 + %6];\n}"
                 : "=&r"(v[0]), "=&r"(v[1]), "=&r"(v[2]) : "l"(p), "r"((uint32_t)on), "n"(128 * FSTR), "n"(256 * FSTR) : "memory");
}
template <int N>
__device__ __forceinline__ uint32_t stamps_missing(const uint32_t* v, int s) {
    uint32_t x = 0;
#pragma unroll
    for (int i = 0; i < N; i++) x |= v[i] ^ s;
    return x & 63;
}
template <int N>
__device__ __forceinline__ uint32_t latest_stamp(const uint32_t* v, const uint4 cal) {
    int late = (int)(v[0] - (cal.x << 6));
#pragma unroll
    for (int i = 1; i < N; i++) late = max(late, (int)(v[i] - (cal.x << 6)));
    return cal.y + (((late >> 6) * (int)cal.z) >> 8);
}
__device__ __forceinline__ void wait_clock(uint32_t target) {
    while (__any_sync(~0u, target - clk() < 65536u)) {}
}

template <int BYTES>
__device__ __forceinline__ bool incomplete(uint32_t buf, uint32_t l16) {
    uint32_t m = 0;
#pragma unroll 1
    for (int o = 0; o < BYTES; o += 256) m = max(m, umax4(lds4u(buf + o + (l16 & 255))));
    return __any_sync(~0u, m == ~0u);
}
__device__ __forceinline__ void refetch(uint32_t buf, const uint4* src, uint32_t bytes, uint32_t b, int w4, int barid, uint32_t& tries) {
    spin_guard(tries);
    bar_sync(barid, 128);
    if (w4 == 0 && elect()) { mbar_expect(b, bytes); bulk_ld(buf, src, bytes, b); }
    __syncwarp();
    mbar_wait(b, 0);
    bar_sync(barid, 128);
    if (w4 == 0 && elect()) mbar_arrive(b);
    __syncwarp();
}

__device__ __forceinline__ void load_chunk(const CUtensorMap* tA, const CUtensorMap* tB, int cl, int rank, uint32_t dst, int j, uint32_t b) {
    const int colA = cl * 256 + (rank >= 4 ? (rank - 4) * 128 : rank * 64), colB = colA + (rank >= 4 ? 64 : 0);
    mbar_expect(b, 65536);
    tma2d(dst, tA, colA, j * 128, b);
    tma2d(dst + 16384, tB, colB, j * 128, b);
    tma2d(dst + 32768, tB, colB, 512 + j * 128, b);
    tma2d(dst + 49152, tA, colA, 512 + j * 128, b);
}

template <bool ISV, int WG>
__device__ __forceinline__ void chain_main(const CUtensorMap* tA, const CUtensorMap* tB, const CUtensorMap* tWo,
                                           const uint32_t sb, const int cl, const int rank, const Descs& D, const uint32_t goal) {
    const int tid = threadIdx.x;
    uint32_t l16 = __shfl_sync(~0u, (tid & 31) * 16, tid & 31);
    int w4 = uni((tid >> 5) & 3);
    const int role = ISV ? 2 : (rank & 1), hh = ISV ? rank - 4 : rank >> 1, head = 2 * cl + hh;
    const uint32_t bar = sb + C_BAR;
    constexpr int ONK = ISV ? ONKV : ONKQ;
    const int ostart = (hh * 128 + role * ONKQ);

    uint32_t wk[24][4], wv[24][4];
    uint32_t a_adr;
    {
        if (WG == 1 && w4 == 0) calibrate(sb + C_CAL, 0.f);
        const int lane = tid & 31, kr = (lane & 7) + ((lane >> 4) << 3);
        a_adr = __shfl_sync(~0u, sb + WG * 32768 + kr * 128 + (((w4 * 2 + ((lane >> 3) & 1)) ^ (kr & 7)) << 4), lane);
#pragma unroll
        for (int j = 0; j < 3; j++) {
            mbar_wait(bar + (B_W0 + j) * 8, 0);
#pragma unroll
            for (int i = 0; i < 8; i++) {
                ldsm4t(wk[j * 8 + i], a_adr + j * 65536 + i * 2048);
                ldsm4t(wv[j * 8 + i], a_adr + j * 65536 + 16384 + i * 2048);
            }
            if (j != 1) {
                bar_sync(6, 256);
                if (j == 0 && tid == 0) TL(1, 6);
                if (WG == 0 && j == 0 && w4 == 0 && elect()) load_chunk(tA, tB, cl, rank, sb + C_WS, 3, bar + B_WS * 8);
                if (WG == 0 && j == 2) {
                    if (elect())
                        for (int i = w4; i < ONK; i += 4) tma2d(sb + C_WO + i * 2048, tWo, cl * 64, (ostart + i) * 16, bar + B_OF * 8);
                }
                __syncwarp();
            }
        }
        if (NOFILL) { for (uint32_t o = C_WO + ONK * 2048 + tid * 16; o < C_BAR; o += 4096) sts4u(sb + o, make_uint4(0, 0, 0, 0)); bar_sync(6, 256); }
        if (WG == 1 && w4 == 1) {
            uint32_t v, it = 0;
            do {
                asm volatile("ld.acquire.gpu.global.u32 %0, [%1];" : "=r"(v) : "l"(&g_epoch) : "memory");
                spin_guard(it);
            } while (__any_sync(~0u, (int)(v - goal) < 0));
        }
        if (WG == 1 && w4 == 0) calibrate(sb + C_CAL, 0.f);
        __syncwarp();
        bar_sync(6, 256);
        asm volatile("fence.proxy.async.global;" ::: "memory");
    }

    constexpr uint32_t SLOT = ISV ? C_SLOTV : C_SLOTQ;
    constexpr int WS_A = (SB0 + C_WS + WG * 32768) >> 4, WO_A = (SB0 + C_WO) >> 4, MB_A = (SB0 + C_MB) >> 4;
#define XN_A(ks) (int)(((SB0 + C_XN + WG * 16384) >> 4) + ((ks) >> 2) * 256 + ((ks) & 3) * 2)
    const uint32_t slot = (sb + SLOT + w4 * 512), mbw = sb + C_MB + WG * 8192;
    const uint32_t sb_v = (mapa(sb, 4 + hh));
    const uint32_t sb_x = uni(mapa(sb, 2 * hh + (WG ? 1 : (~w4 & 1))));
    const uint32_t sb_o = (mapa(sb, w4));
    const uint32_t u_off = (ISV ? (head * 128 + w4 * 32) * 16 : (cl * 4 + rank) * 256 + (w4 & 1) * 128);
    const uint32_t v_row = (sb + C_V + (2 * WG + (w4 >> 1)) * 512), v_b = ((w4 & 1) * 64);
    const uint32_t u_flag = (blockIdx.x * FSTR);
    const uint32_t f_half = (w4 & 1) * role * (ONKV * 128), f_sb = uni(mapa(sb, rank + (w4 & 1) * (4 + hh - rank)));
    const uint32_t f_src = uni((ostart + (w4 & 1) * (2 - role) * ONKQ) * 256 + f_half), f_dst = uni(f_sb + C_MB + f_half);
    const uint32_t m_dst = (sb + C_MB + role * 8192), m_bar = (bar + (B_MF0 + role) * 8);
    uint32_t target, missing;
    int s = -1;
    uint32_t pf[4][4];
    float xk[16], xv[16];

    auto st_async4_unless = [&](uint32_t a, int b, float x, float y, float z, float w, bool hold) {
        const uint32_t dump = sb + C_DUMP + l16;
        st_async4(hold ? dump : a, hold ? (dump & 0xFF000000u) | (SB0 + C_BAR + B_DUMP * 8) : (a & 0xFF000000u) | (SB0 + C_BAR + b * 8), x, y, z, w);
    };
    auto st_async2_unless = [&](uint32_t a, int b, float x, float y, bool hold) {
        const uint32_t dump = sb + C_DUMP + l16;
        st_async2(hold ? dump : a, hold ? (dump & 0xFF000000u) | (SB0 + C_BAR + B_DUMP * 8) : (a & 0xFF000000u) | (SB0 + C_BAR + b * 8), x, y);
    };
    auto load_tokens = [&](int seg, int wina, int g) {
        const int khalf = ISV ? 1 - wina : wina;
        if (!NOFILL && elect()) {
            mbar_expect(bar + (B_XF0 + g) * 8, 16384);
            bulk_ld(sb + C_XN + g * 16384, g_xc + (seg * 4 + khalf * 2 + g) * 1024, 16384, bar + (B_XF0 + g) * 8);
        }
        __syncwarp();
    };
    auto prefetch = [&]() {
#pragma unroll
        for (int i = 0; i < 4; i++) ldsm4t(pf[i], a_adr + C_WS + (i & 1) * 16384 + (i >> 1) * 2048);
    };
    constexpr int HA = ISV ? 0 : 1, NK1 = ISV ? 0 : QK1;
    auto products = [&](auto give, auto half, auto init, auto i0, auto i1, const uint64_t d) {
        static_for<i0.value, i1.value>([&](auto i) {
            constexpr int ks = half.value * 16 + i.value, acc = !(init.value && i.value == 0);
            if constexpr (ks >= 24) wg32_ss<WS_A + give.value * 1024 + (ks - 24) * 128, XN_A(i.value)>(give.value ? xv : xk, d);
            else if constexpr (give.value) wg32_rs<acc, XN_A(i.value)>(xv, wv[ks], d);
            else wg32_rs<acc, XN_A(i.value)>(xk, wk[ks], d);
        });
    };
    auto stream_a = [&](const uint64_t dk, const uint64_t dv) {
        if (NOFILL) return;
        wg_fence();
        products(ic<0>{}, ic<HA>{}, ic<1>{}, ic<0>{}, ic<8>{}, dk);
        products(ic<1>{}, ic<HA>{}, ic<1>{}, ic<0>{}, ic<16>{}, dv);
        products(ic<0>{}, ic<HA>{}, ic<1>{}, ic<8>{}, ic<16>{}, dk);
        wg_commit();
    };
    auto token_softmax = [&]() {
        const int hi = w4 - 2, lane = l16 >> 4;
        const uint32_t src = sb + C_XSL + l16 + hi * 8;
        const int d0 = 16 * role + 8 * hi + (lane >> 2) - 2 * (lane & 3);
        mbar_wait(bar + B_XS * 8, s & 1);
        float e[10];
        float m = -INFINITY;
#pragma unroll
        for (int i = 0; i < 5; i++) {
            __syncwarp();
            const float2 a = lds2f(src + i * 512), b = lds2f(src + 2560 + i * 512);
            e[2 * i] = (i == 0 || d0 >= 8 * (i - 1)) ? a.x + b.x : -INFINITY;
            e[2 * i + 1] = (i == 0 || d0 > 8 * (i - 1)) ? a.y + b.y : -INFINITY;
            m = fmaxf(m, fmaxf(e[2 * i], e[2 * i + 1]));
        }
        m = fmaxf(m, __shfl_xor_sync(~0u, m, 1));
        m = fmaxf(m, __shfl_xor_sync(~0u, m, 2));
        m *= -SM_SCALE;
        float l = 0.f;
#pragma unroll
        for (int i = 0; i < 10; i++) { e[i] = ex2(fmaf(e[i], SM_SCALE, m)); l += e[i]; }
        l += __shfl_xor_sync(~0u, l, 1);
        l += __shfl_xor_sync(~0u, l, 2);
        l = rcp(l);
        const uint32_t pd = sb_v + C_PL + (s & 1) * 2048 + role * 768 + hi * 128 + (l16 >> 2), pb = sb_v + C_BAR + (B_P0 + (s & 1)) * 8;
        st_async1(pd, pb, pack2(e[0] * l, e[1] * l));
        st_async1(pd + 256, pb, pack2(e[2] * l, e[3] * l));
        st_async1(pd + 512, pb, pack2(e[4] * l, e[5] * l));
        if (role) {
            st_async1(pd + 768, pb, pack2(e[6] * l, e[7] * l));
            st_async1(pd + 1024, pb, pack2(e[8] * l, e[9] * l));
        }
        if (hi == 0 && l16 == 0) mbar_expect(bar + B_XS * 8, 3072 + role * 2048);
        __syncwarp();
    };

    auto windows = [&](auto first_) {
        constexpr bool FIRST = first_.value;
        asm volatile("" : "+r"(l16), "+r"(w4));
        const uint64_t dd[4] = {FIRST ? DSW : D.sw[0], FIRST ? DSW : D.sw[1], FIRST ? DSW : D.sw[2], FIRST ? DSW : D.sw[3]};
        TS(5);
        if constexpr (WG == 1) {
            TS(6);
            if (ISV && !FIRST) bar_sync(3, 256);
            Stamps st2;
            if (!ISV && !FIRST) load_stamps2(st2, g_flag[0], l16, __any_sync(~0u, missing) && w4 < 2);
            stream_a(dd[0], dd[1]);
            if (!NOFILL) bar_arrive(7, 256);
            if (!FIRST && !ISV && w4 < 2) {
                const char* src = reinterpret_cast<const char*>(&g_xo[s & 3][0]) + f_src;
                if (__builtin_expect(__any_sync(~0u, missing), 0)) {
                    uint32_t it = 0;
                    while (__any_sync(~0u, stamps_missing<6>(st2.v, s))) { load_stamps2(st2, g_flag[0], l16); spin_guard(it); }
                    target = latest_stamp<6>(st2.v, lds4u(sb + C_CAL)) + DLY1;
                }
                mbar_wait(bar + B_VF * 8, s & 1);
                TS(10);
                wait_clock(target);
                if (elect()) bulk_ld(f_dst, src, ONKQ * 256 - w4 * (ONKQ * 256 - ONKV * 128), f_sb + C_BAR + B_OF * 8);
                __syncwarp();
                TS(8);
            }
            if (!NOFILL) {
                wg_wait<0>();
                reg_fence<16>(xk); reg_fence<16>(xv);
                if (w4 == 3) {
                    bar_sync(2, 128);
                    if (RB1 == 0 || FIRST) load_tokens(s + 1, 0, 1);
                    if (ISV && !FIRST && (s & 3) == 0 && s > 0 && l16 == 0) count_up(CNT_OX + (s >> 2) - 1);
                    __syncwarp();
                }
                else bar_arrive(2, 128);
            }
            TS(7);
        } else {
            if (!NOFILL) {
                mbar_wait(bar + B_XF0 * 8, 0);
                bar_sync(7, 256);
            }
            TS(6);
            stream_a(dd[0], dd[1]);
        }
        uint32_t st[6];
        uint4 cal;
        if constexpr (WG == 0) {
            if constexpr (!FIRST) {
                const uint32_t dst = sb_o + C_OL + rank * 512 + l16;
                const uint32_t can = sb + C_MB + l16 * 8 + (l16 >> 2), can2 = can + (l16 < (ONK * 2 - 64) * 16 ? 8192 : 0);
                float co[4];
                TS(7);
                uint32_t tries = 0;
                for (;; tries |= 1) {
                    asm volatile("" : "+r"(tries));
                    if (__builtin_expect(tries, 0)) {
                        wg_wait<0>();
                        refetch(sb + C_MB, &g_xo[s & 3][ostart * 16], ONK * 256, bar + B_RT0 * 8, w4, 1, tries);
                    }
                    mbar_wait(bar + B_OF * 8, s & 1);
                    TS(8);
                    wg8_chain<0, 8, WO_A, MB_A>(co, D.sw[0], D.ns);
                    if (__builtin_expect(!__any_sync(~0u, max(max(lds1u(can), lds1u(can + 4096)), lds1u(can2)) == CANARY), 1)) break;
                }
                wg_wait<1>();
                if (l16 == 0) mbar_arrive(bar + B_GO * 8);
                wg8_chain<8, ONK - OTAIL, WO_A, MB_A>(co, D.sw[0], D.ns);
                static_for<ONK - OTAIL, ONK>([&](auto i) { wg8_ss<1, WO_A + i.value * 128, MB_A + i.value * 16>(co, D.sw[0], D.ns); });
                wg_commit();
                wg_wait<1>();
                bar_arrive(5, 256);
                wg_wait<0>();
                reg_fence<4>(co);
                const bool nan = any_nan(co[0], co[1]);
                st_async4_unless(dst, B_OL, co[0], co[1], co[2], co[3], nan);
                if (__builtin_expect(nan, 0)) {
                    while (incomplete<ONK * 256>(sb + C_MB, l16)) {
                        refetch(sb + C_MB, &g_xo[s & 3][ostart * 16], ONK * 256, bar + B_RT0 * 8, w4, 1, tries);
                        co[0] = co[1] = co[2] = co[3] = 0.f;
#pragma unroll 1
                        for (int i = 0; i < ONK; i++) {
                            wg_fence();
                            wg8_ss<1, WO_A, MB_A>(co, DSW + i * 128, DNS + i * 16);
                            wg_commit();
                            wg_wait<0>();
                        }
                        reg_fence<4>(co);
                    }
                    st_async4_unless(dst, B_OL, co[0], co[1], co[2], co[3], false);
                }
                TS(9);
                if (l16 < 48 && w4 == 3) mbar_expect(bar + B_MF0 * 8 + (l16 >> 1), l16 == 32 ? ONK * 256 : 8192);
            } else {
                wg_wait<0>();
                if (l16 == 0) mbar_arrive(bar + B_GO * 8);
                bar_arrive(5, 256);
            }
            if (l16 < 32) mbar_arrive_cluster(mapa(bar + B_MBF * 8, 2 * hh + (l16 >> 4)));
            __syncwarp();
            if (!NOFILL) { reg_fence<16>(xk); reg_fence<16>(xv); }
        } else {
            if (w4 < 2) {
                mbar_wait(bar + B_GO * 8, (s + 1) & 1);
                const uint32_t v = ((gtick() - (ISV ? (ONKQ - ONKV) * 18 / 64 : 0)) << 6) | s, c = clk();
                if (w4 == 0) {
                    if (!FIRST) {
                        if (l16 == 0) st_relaxed1(&g_flag[1][u_flag + (l16 >> 1)], v);
                        if (!ISV) calibrate(sb + C_CAL, 0.75f);
                    }
                } else {
                    if (!FIRST) wait_clock(c + DLYB);
                    load_tokens(s + 1, 0, 0);
                }
                if (!ISV && !FIRST) st_relaxed1(reinterpret_cast<char*>(&g_xmem[(s + 3) & 3][0]) + (u_off + (l16 >> 2)), ~0u);
            } else if (!FIRST && !NOFILL) {
                if (RB1 == 1 && w4 == 3) { mbar_wait(bar + B_OF * 8, s & 1); load_tokens(s + 1, 0, 1); }
                if (!ISV) token_softmax();
                TSX(9, w4 == 2);
            }
            if (!NOFILL) mbar_wait(bar + B_XF1 * 8, 1);
            if (!ISV && !FIRST) cal = lds4u(sb + C_CAL);
            bar_sync(5, 256);
            if (!ISV && !FIRST) load_stamps1(st, g_flag[1], l16, w4 == 0);
        }
        asm volatile("" : "+r"(l16), "+r"(w4));
        TSX(11, w4 == 0 && (WG || ISV));
        auto store_tokens = [&](const float4* r) {
            uint32_t lo[4], hi[4];
#pragma unroll
            for (int j = 0; j < 4; j++) {
                lo[j] = pack2(xk[4 * j] + r[j].x, xk[4 * j + 1] + r[j].y);
                hi[j] = pack2(xk[4 * j + 2] + r[j].z, xk[4 * j + 3] + r[j].w);
            }
            if (!ISV) {
                const uint32_t d = sb + C_QX + WG * 4096 + w4 * 1024 + l16;
                stsm4t(d, lo[0], lo[1], lo[2], lo[3]);
                stsm4t(d + 512, hi[0], hi[1], hi[2], hi[3]);
            } else {
                const uint32_t d = v_row + ((s + 1) & 1) * 10240 + ((l16 & 384) << 4) + ((l16 & 96) << 2) + ((l16 & 112) ^ v_b);
                stsm4(d, lo[0], lo[1], lo[2], lo[3]);
                stsm4(d ^ 32, hi[0], hi[1], hi[2], hi[3]);
            }
        };
        if constexpr (WG == 1) {
            if (!NOFILL) {
                wg_fence();
                products(ic<1>{}, ic<1 - HA>{}, ic<0>{}, ic<0>{}, ic<16>{}, dd[3]);
                products(ic<0>{}, ic<1 - HA>{}, ic<0>{}, ic<0>{}, ic<NK1>{}, dd[2]);
                wg_commit();
                if (ISV) bar_arrive(7, 256);
                else {
                    if (!FIRST) load_stamps1(st + 3, g_flag[1], l16, w4 == 0);
                    mbar_wait(bar + B_MBF * 8, (s + 1) & 1);
                    bar_sync(7, 256);
                }
                wg_wait<0>();
                reg_fence<16>(xv); reg_fence<16>(xk);
#pragma unroll
                for (int j = 0; j < 4; j++) sts4f(slot + l16 + j * 2048, xv[4 * j], xv[4 * j + 1], xv[4 * j + 2], xv[4 * j + 3]);
                bar_arrive(8, 256);
            }
            TS(12);
            if (!ISV && w4 == 0) {
                const uint4* src = &g_xmem[(s + 1) & 3][role * 512];
                if (NOFILL) mbar_wait(bar + B_MBF * 8, (s + 1) & 1);
                if (!FIRST) {
                    if (__builtin_expect(__any_sync(~0u, stamps_missing<3>(st, s)), 0)) {
                        uint32_t it = 0;
                        if (!NOFILL) { st[0] = st[3]; st[1] = st[4]; st[2] = st[5]; }
                        while (__any_sync(~0u, stamps_missing<3>(st, s))) { load_stamps1(st, g_flag[1], l16); spin_guard(it); }
                    }
                    TS(3);
                    wait_clock(latest_stamp<3>(st, cal) + DLY2);
                }
                if (hh) { if (elect()) bulk_mc(m_dst, src, 8192, m_bar, 0x2C); }
                else if (elect()) bulk_mc(m_dst, src, 8192, m_bar, 0x13);
                __syncwarp();
                TS(4);
            }
            prefetch();
            if (!NOFILL) {
                bar_sync(9, 256);
                float4 r[4];
#pragma unroll
                for (int j = 0; j < 4; j++) r[j] = lds4f(slot + l16 + j * 2048);
                bar_sync(14, 256);
                wg_fence();
                products(ic<0>{}, ic<1 - HA>{}, ic<0>{}, ic<NK1>{}, ic<16>{}, dd[2]);
                wg_commit();
                wg_wait<0>();
                reg_fence<16>(xk);
                TS(13);
                store_tokens(r);
                bar_arrive(10, 256);
                if (w4 != 3) bar_arrive(13, 128);
            }
        } else {
            float4 r[4];
            if (!NOFILL) mbar_wait(bar + B_XF0 * 8, 1);
            if (!ISV && !FIRST && w4 < 2) {
                char* gd = reinterpret_cast<char*>(&g_xmem[(s + 1) & 3][0]) + (u_off + (l16 >> 2));
                mbar_wait(bar + B_OL * 8, s & 1);
                TSD(3);
                float2 a[6];
#pragma unroll
                for (int i = 0; i < 6; i++) a[i] = lds2f(sb + C_OL + w4 * 8 + l16 + i * 512);
                st_relaxed1(gd, movm(pack2((a[0].x + a[1].x) + (a[2].x + a[3].x) + (a[4].x + a[5].x),
                                           (a[0].y + a[1].y) + (a[2].y + a[3].y) + (a[4].y + a[5].y))));
                TS(11);
                if (w4 == 0 && l16 == 0) mbar_expect(bar + B_OL * 8, 3072);
                __syncwarp();
            }
            if (!NOFILL) {
                bar_sync(7, 256);
                TS(12);
                wg_fence();
                products(ic<1>{}, ic<1 - HA>{}, ic<0>{}, ic<0>{}, ic<16>{}, dd[3]);
                wg_commit();
                products(ic<0>{}, ic<1 - HA>{}, ic<0>{}, ic<0>{}, ic<6>{}, dd[2]);
                wg_commit();
                bar_sync(8, 256);
#pragma unroll
                for (int j = 0; j < 4; j++) r[j] = lds4f(slot + l16 + j * 2048);
                wg_wait<1>();
                reg_fence<16>(xv);
#pragma unroll
                for (int j = 0; j < 4; j++) sts4f(slot + l16 + j * 2048, xv[4 * j], xv[4 * j + 1], xv[4 * j + 2], xv[4 * j + 3]);
                bar_arrive(9, 256);
                products(ic<0>{}, ic<1 - HA>{}, ic<0>{}, ic<6>{}, ic<16>{}, dd[2]);
                wg_commit();
                bar_arrive(14, 256);
                wg_wait<0>();
                reg_fence<16>(xk);
            }
            TS(13);
            if (!NOFILL) store_tokens(r);
            prefetch();
        }
    };

    if (tid == 0) TL(1, 2);
    if (w4 == 0) load_tokens(0, 1, WG);
    mbar_wait(bar + B_WS * 8, 0);
    if (WG == 1 && !NOFILL) mbar_wait(bar + B_XF1 * 8, 0);
    windows(ic<1>{});
    if (tid == 0) TL(1, 3);

#pragma unroll 1
    while (true) {
        s++;
        asm volatile("" : "+r"(l16), "+r"(a_adr), "+r"(w4));
        TS_FLUSH(WG);
        TS(0);
        float ck[4], cv[4], dk[4], dv[4];
        uint32_t b[3][4], tries = 0;
        const uint32_t kl = sb + C_KX + ((l16 & 384) << 2) + (l16 & 112);
        auto load_b = [&](auto kp) { ldsm4(b[kp.value % 3], mbw + l16 + ((kp.value & 3) ? (kp.value >> 2) * 3 + (kp.value & 3) - 1 : 12 + (kp.value >> 2)) * 512); };
        auto kpair = [&](auto kp_) {
            constexpr int kp = kp_.value, grp = kp >> 2, ph = kp & 3;
            if constexpr (kp > 0 && kp < 14) load_b(ic<kp + 2>{});
            const uint32_t* bb = b[kp % 3];
            if constexpr (ph != 0) {
                constexpr int q = (grp * 3 + ph - 1) * 2;
                static_for<(ph == 1 ? 0 : ph), ph + 1>([&](auto i) {
                    if constexpr (grp < 3) ldsm4t(pf[i.value], a_adr + C_WS + (i.value & 1) * 16384 + (grp * 2 + 2 + (i.value >> 1)) * 2048);
                });
                __syncwarp();
                mma16(cv, wv[q][0], wv[q][1], wv[q][2], wv[q][3], bb[0], bb[1]);
                mma16(ck, wk[q][0], wk[q][1], wk[q][2], wk[q][3], bb[0], bb[1]);
                mma16(dv, wv[q + 1][0], wv[q + 1][1], wv[q + 1][2], wv[q + 1][3], bb[2], bb[3]);
                mma16(dk, wk[q + 1][0], wk[q + 1][1], wk[q + 1][2], wk[q + 1][3], bb[2], bb[3]);
            } else {
                if constexpr (kp == 0) {
#pragma unroll
                    for (int i = 0; i < 4; i++) ck[i] = cv[i] = dk[i] = dv[i] = 0.f;
                }
                mma16(ck, pf[0][0], pf[0][1], pf[0][2], pf[0][3], bb[0], bb[1]);
                mma16(cv, pf[1][0], pf[1][1], pf[1][2], pf[1][3], bb[0], bb[1]);
                mma16(dk, pf[2][0], pf[2][1], pf[2][2], pf[2][3], bb[2], bb[3]);
                mma16(dv, pf[3][0], pf[3][1], pf[3][2], pf[3][3], bb[2], bb[3]);
            }
        };
        auto hand_over = [&]() {
#pragma unroll
            for (int i = 0; i < 4; i++) { cv[i] += dv[i]; ck[i] += dk[i]; }
            if (ISV) {
                sts4f(slot + WG * 2048 + l16, cv[0], cv[1], cv[2], cv[3]);
            } else {
                const float *q = WG ? cv : ck, *k = WG ? ck : cv;
                stsm4t(slot + WG * 2048 + l16, pack2(q[0], q[1]), pack2(q[2], q[3]), pack2(k[0], k[1]), pack2(k[2], k[3]));
            }
        };
        auto repair = [&]() {
            bar_sync(6, 256);
            while (incomplete<8192>(mbw, l16)) {
                refetch(mbw, &g_xmem[s & 3][WG * 512], 8192, bar + (B_RT0 + WG) * 8, w4, 1 + WG, tries);
                prefetch();
                static_for<0, 3>(load_b);
                static_for<0, 16>(kpair);
                hand_over();
            }
            bar_sync(6, 256);
        };
        {
            const uint32_t can = mbw + l16 * 8 + (l16 >> 2);
            uint32_t* const flag = &g_flag[0][u_flag + WG + l16];
            for (;; tries |= 1) {
                asm volatile("" : "+r"(tries));
                if (__builtin_expect(tries, 0)) {
                    refetch(mbw, &g_xmem[s & 3][WG * 512], 8192, bar + (B_RT0 + WG) * 8, w4, 1 + WG, tries);
                }
                mbar_wait(bar + (B_MF0 + WG) * 8, s & 1);
                TS(1);
                static_for<0, 3>(load_b);
                const uint32_t c0 = lds1u(can), c1 = lds1u(can + 4096);
                const uint32_t v = ((gtick() - (ISV ? VLEAD : 0)) << 6) | s;
                kpair(ic<0>{});
                const bool early = __any_sync(~0u, max(c0, c1) == CANARY);
                st_pred1(flag, v, w4 * 512 + l16 == 1536 && !early);
                if (__builtin_expect(!early, 1)) break;
            }
            static_for<1, RFPOS>(kpair);
            if (WG == 0 && !NOFILL) bar_sync(10, 256);
            if (WG == 1 && !NOFILL && w4 == 3) {
                bar_sync(13, 128);
                if (s < NSEG - 1) load_tokens(s + 1, 1, 1);
            }
            static_for<RFPOS, 13>(kpair);
        }
        auto finish_projections = [&]() {
            static_for<13, 16>(kpair);
            hand_over();
            TS(2);
            return bar_sync_any_nan(cv[0], cv[1]);
        };
        if constexpr (!ISV) {
            const uint32_t qa = sb + C_SLOTQ + ((l16 >> 1) & 128) + ((l16 & 128) << 3) + (l16 & 112);
            const uint32_t ma = sb + C_SLOTQ + 256 + l16 + (l16 & 256);
            const uint32_t qx = sb + C_QX + l16 + (l16 & 256);
            auto ldsm_sum = [&](uint32_t* r, uint32_t a) {
                uint32_t t[4];
                ldsm4(r, a); ldsm4(t, a + 2048);
#pragma unroll
                for (int i = 0; i < 4; i++) asm("add.rn.bf16x2 %0, %0, %1;" : "+r"(r[i]) : "r"(t[i]));
            };
            auto tile = [&](float* d, const uint32_t (*q)[4], const uint32_t (*k)[4]) {
                d[0] = d[1] = d[2] = d[3] = 0.f;
#pragma unroll
                for (int i = 0; i < 4; i++) mma16(d, q[i][0], q[i][1], q[i][2], q[i][3], k[i >> 1][(i & 1) * 2], k[i >> 1][(i & 1) * 2 + 1]);
            };
            auto send = [&](int ti, const float* d, bool hold) {
                st_async4_unless(sb_x + C_XSL + role * 2560 + ti * 512 + l16, B_XS, d[0], d[1], d[2], d[3], hold);
            };
            if constexpr (WG == 0) {
                auto scores = [&](auto again) {
                    bool nan = false;
                    if (w4 < 2) {
                        uint32_t k0[2][4], k1[2][4], q0[4], q1[4];
                        const uint32_t ka = kl + w4 * 256, dst = sb_v + C_SL + role * 1280 + w4 * 512 + l16;
                        ldsm4(k0[0], ka); ldsm4(k0[1], ka + 2048);
                        ldsm4(k1[0], ka + 128); ldsm4(k1[1], ka + 128 + 2048);
                        __syncwarp();
                        if (!again.value) nan = finish_projections();
                        TS(3);
                        ldsm_sum(q0, qa); ldsm_sum(q1, qa + 512);
                        float s0[4] = {0.f, 0.f, 0.f, 0.f}, s1[4] = {0.f, 0.f, 0.f, 0.f}, s2[4] = {0.f, 0.f, 0.f, 0.f}, s3[4] = {0.f, 0.f, 0.f, 0.f};
                        mma16(s0, q0[0], q0[1], q0[2], q0[3], k0[0][0], k0[0][1]);
                        mma16(s1, q0[0], q0[1], q0[2], q0[3], k0[1][0], k0[1][1]);
                        mma16(s2, q0[0], q0[1], q0[2], q0[3], k1[0][0], k1[0][1]);
                        mma16(s3, q0[0], q0[1], q0[2], q0[3], k1[1][0], k1[1][1]);
                        mma16(s0, q1[0], q1[1], q1[2], q1[3], k0[0][2], k0[0][3]);
                        mma16(s1, q1[0], q1[1], q1[2], q1[3], k0[1][2], k0[1][3]);
                        mma16(s2, q1[0], q1[1], q1[2], q1[3], k1[0][2], k1[0][3]);
                        mma16(s3, q1[0], q1[1], q1[2], q1[3], k1[1][2], k1[1][3]);
                        st_async4_unless(dst, B_SC, s0[0] + s1[2], s0[1] + s1[3], s2[0] + s3[2], s2[1] + s3[3], nan);
                        if (!again.value) bar_arrive(12, 256);
                        TS(4);
                    } else if (w4 == 2) {
                        uint32_t q0[4], q1[4], km[2][4], q[4][4];
                        const uint32_t dst = sb_v + C_SL + role * 1280 + 1024 + (l16 >> 1);
                        if (!again.value) nan = finish_projections();
                        ldsm_sum(q0, qa); ldsm_sum(km[0], ma); ldsm_sum(km[1], ma + 1024); ldsm_sum(q1, qa + 512);
                        __syncwarp();
#pragma unroll
                        for (int i = 0; i < 4; i++) ldsm4(q[i], qx + 256 + i * 1024);
                        float s0[4] = {0.f, 0.f, 0.f, 0.f}, s1[4] = {0.f, 0.f, 0.f, 0.f}, d0[4];
                        mma16(s0, q0[0], q0[1], q0[2], q0[3], km[0][0], km[0][1]);
                        mma16(s1, q0[0], q0[1], q0[2], q0[3], km[1][0], km[1][1]);
                        mma16(s0, q1[0], q1[1], q1[2], q1[3], km[0][2], km[0][3]);
                        mma16(s1, q1[0], q1[1], q1[2], q1[3], km[1][2], km[1][3]);
                        st_async2_unless(dst, B_SC, s0[0] + s1[2], s0[1] + s1[3], nan);
                        if (!NOFILL) tile(d0, q, km);
                        if (!again.value) bar_sync(12, 256);
                        if (!NOFILL) send(0, d0, nan);
                    } else {
                        if (!again.value) {
                            nan = finish_projections();
                            if (s < NSEG - 1) load_tokens(s + 1, 1, 0);
                        }
                        uint32_t q[4][4], k0[2][4], k1[2][4], km[2][4];
                        float d0[4], d1[4], d2[4];
                        if (!NOFILL) {
#pragma unroll
                            for (int i = 0; i < 4; i++) ldsm4(q[i], qx + i * 1024);
                            ldsm4(k0[0], kl); ldsm4(k0[1], kl + 2048);
                            ldsm4(k1[0], kl + 128); ldsm4(k1[1], kl + 128 + 2048);
                            tile(d1, q, k0); tile(d2, q, k1);
                            ldsm_sum(km[0], ma); ldsm_sum(km[1], ma + 1024);
                            tile(d0, q, km);
                        }
                        if (!again.value) bar_sync(12, 256);
                        if (!NOFILL) { send(0, d0, nan); send(1, d1, nan); send(2, d2, nan); }
                    }
                    return nan;
                };
                if (__builtin_expect(__any_sync(~0u, scores(ic<0>{})), 0)) { repair(); scores(ic<1>{}); }
                if (__builtin_expect(s == NSEG - 1, 0)) break;
            } else {
                Stamps st1;
                load_stamps2(st1, g_flag[0], l16, w4 < 2);
                const bool nan = finish_projections();
                mbar_wait(bar + B_WS * 8, 0);
                missing = stamps_missing<6>(st1.v, s);
                target = latest_stamp<6>(st1.v, lds4u(sb + C_CAL)) + DLY1;
                if (!NOFILL) {
                    uint32_t q[4][4], k0[2][4];
                    float d1[4];
#pragma unroll
                    for (int i = 0; i < 4; i++) ldsm4(q[i], qx + 256 + i * 1024);
                    ldsm4(k0[0], kl + w4 * 128); ldsm4(k0[1], kl + w4 * 128 + 2048);
                    tile(d1, q, k0);
                    mbar_wait(bar + B_XF1 * 8, s == NSEG - 1);
                    bar_sync(12, 256);
                    send(1 + w4, d1, false);
                } else {
                    bar_sync(12, 256);
                }
                if (__builtin_expect(__any_sync(~0u, nan), 0)) repair();
                if (__builtin_expect(s == NSEG - 1, 0)) {
                    asm volatile("" : "+r"(l16));
                    if (w4 >= 2 && !NOFILL) token_softmax();
                    break;
                }
            }
        } else {
            const uint32_t lane_b = sb + C_V + w4 * 512 + ((l16 & 384) << 4) + (l16 & 112);
            auto load_values = [&](uint32_t (*vx)[4], uint32_t* vm, int ss) {
#pragma unroll
                for (int j = 0; j < 4; j++) ldsm4(vx[j], ((lane_b + (ss & 1) * 10240) ^ (j * 32)) + j * 128);
                ldsm4(vm, sb + C_V + (ss & 1) * 10240 + w4 * 512 + 8192 + (l16 ^ ((l16 >> 2) & 96)));
            };
            auto token_output = [&](int ss, bool live, auto mid) {
                uint32_t vx[4][4], vm[4];
                const uint32_t pl = sb + C_PL + (ss & 1) * 2048 + (l16 >> 2);
                auto lds_frag = [&](uint32_t a) { return make_uint4(lds1u(a), lds1u(a + 128), lds1u(a + 256), lds1u(a + 384)); };
                load_values(vx, vm, ss);
                mid();
                char* orow = reinterpret_cast<char*>(g_ox) + (ss * (32 * HD * 2) + (u_off >> 3) + (l16 >> 6) * (HD * 2) + (l16 & 48));
#pragma unroll
                for (int mh = 1; mh >= 0; mh--) {
                    __syncwarp();
                    const uint2 pm = make_uint2(lds1u(pl + mh * 768), lds1u(pl + mh * 768 + 128));
                    const uint4 p0 = lds_frag(pl + mh * 768 + 256);
                    float o[4][4];
#pragma unroll
                    for (int j = 0; j < 4; j++) { o[j][0] = o[j][1] = o[j][2] = o[j][3] = 0.f; mma8(o[j], pm.x, pm.y, vm[j]); }
#pragma unroll
                    for (int j = 0; j < 4; j++) mma16(o[j], p0.x, p0.y, p0.z, p0.w, vx[j][0], vx[j][1]);
                    if (mh) {
                        const uint4 p1 = lds_frag(pl + 1536);
#pragma unroll
                        for (int j = 0; j < 4; j++) mma16(o[j], p1.x, p1.y, p1.z, p1.w, vx[j][2], vx[j][3]);
                    }
                    st_pred4(orow + mh * (16 * HD * 2),
                             make_uint4(pack2(o[0][0], o[0][1]), pack2(o[1][0], o[1][1]), pack2(o[2][0], o[2][1]), pack2(o[3][0], o[3][1])), live);
                    st_pred4(orow + mh * (16 * HD * 2) + 8 * HD * 2,
                             make_uint4(pack2(o[0][2], o[0][3]), pack2(o[1][2], o[1][3]), pack2(o[2][2], o[2][3]), pack2(o[3][2], o[3][3])), live);
                }
            };
            const uint32_t vd = v_row + (s & 1) * 10240 + 8192 + ((l16 & 96) << 2) + ((l16 & 112) ^ v_b ^ ((l16 & 128) >> 2));
            if (__builtin_expect(__any_sync(~0u, finish_projections()), 0)) repair();
            const float4 r = lds4f(slot + (WG ^ 1) * 2048 + l16);
            __syncwarp();
            auto finish = [&]() {
                stsm2(vd, pack2(ck[0] + r.x, ck[1] + r.y), pack2(ck[2] + r.z, ck[3] + r.w));
                if (WG == 1) {
                    bar_arrive(11, 256);
                    if (w4 == 3 && l16 < 32) mbar_arrive_cluster(mapa(bar + B_VF * 8, 2 * hh + (l16 >> 4)));
                }
                TSX(3, WG == 0 && w4 == 0);
            };
            if (!NOFILL && WG == 1) {
                token_output(s - 1, s > 0, [&]() { finish(); mbar_wait(bar + (B_P0 + ((s - 1) & 1)) * 8, ((s - 1) >> 1) & 1); });
                if (w4 == 1 && l16 == 0 && s > 0) mbar_expect(bar + (B_P0 + ((s - 1) & 1)) * 8, 2048);
                mbar_wait(bar + B_XF1 * 8, s == NSEG - 1);
            } else {
                finish();
            }
            if (WG == 0) bar_sync(11, 256);
            if (__builtin_expect(s == NSEG - 1, 0)) {
                bar_sync(6, 256);
                if (WG == 1) {
                    if (!NOFILL) token_output(s, true, [&]() { mbar_wait(bar + (B_P0 + (s & 1)) * 8, (s >> 1) & 1); });
                    bar_sync(2, 128);
                    if (w4 == 0 && l16 == 0) {
                        if (NOFILL) for (int i = 0; i < 15; i++) count_up(CNT_OX + i);
                        count_up(CNT_OX + 15);
                    }
                    __syncwarp();
                }
                mbar_wait(bar + B_SC * 8, s & 1);
                break;
            }
            if constexpr (WG == 0) {
                uint32_t vx[4][4], vm[4];
                load_values(vx, vm, s);
                const uint32_t oo = u_off + ((l16 & 48) << 3) + ((l16 >> 2) & 112);
                char* dst = reinterpret_cast<char*>(&g_xo[s & 3][0]) + oo;
                if (w4 == 3) load_tokens(s + 1, 1, 0);
                mbar_wait(bar + B_SC * 8, s & 1);
                TS(4);
                const float4 a0 = lds4f(sb + C_SL + l16), b0 = lds4f(sb + C_SL + 1280 + l16);
                const float4 a1 = lds4f(sb + C_SL + 512 + l16), b1 = lds4f(sb + C_SL + 1280 + 512 + l16);
                const float2 a2 = lds2f(sb + C_SL + 1024 + (l16 >> 1)), b2 = lds2f(sb + C_SL + 1280 + 1024 + (l16 >> 1));
                const float e[10] = {a0.x + b0.x, a0.y + b0.y, a0.z + b0.z, a0.w + b0.w, a1.x + b1.x, a1.y + b1.y, a1.z + b1.z, a1.w + b1.w,
                                     a2.x + b2.x, a2.y + b2.y};
                float m = fmaxf(fmaxf(fmaxf(e[0], e[1]), fmaxf(e[2], e[3])), fmaxf(fmaxf(e[4], e[5]), fmaxf(e[6], e[7])));
                m = fmaxf(m, fmaxf(e[8], e[9]));
                m = fmaxf(fmaxf(m, __shfl_xor_sync(~0u, m, 1)), fmaxf(__shfl_xor_sync(~0u, m, 2), __shfl_xor_sync(~0u, m, 3)));
                m *= -SM_SCALE;
                float x[10];
#pragma unroll
                for (int i = 0; i < 10; i++) x[i] = ex2(fmaf(e[i], SM_SCALE, m));
                float o[4][4];
                const uint32_t p0 = pack2(x[0], x[1]), p1 = pack2(x[2], x[3]), j0 = __float_as_uint(x[1]), j1 = __float_as_uint(x[3]);
#pragma unroll
                for (int j = 0; j < 4; j++) { o[j][0] = o[j][1] = o[j][2] = o[j][3] = 0.f; mma16(o[j], p0, j0, p1, j1, vx[j][0], vx[j][1]); }
                const uint32_t p2 = pack2(x[4], x[5]), p3 = pack2(x[6], x[7]), j2 = __float_as_uint(x[5]), j3 = __float_as_uint(x[7]);
#pragma unroll
                for (int j = 0; j < 4; j++) mma16(o[j], p2, j2, p3, j3, vx[j][2], vx[j][3]);
                const uint32_t p4 = pack2(x[8], x[9]), j4 = __float_as_uint(x[9]);
                float l = (((x[0] + x[1]) + (x[2] + x[3])) + ((x[4] + x[5]) + (x[6] + x[7]))) + (x[8] + x[9]);
                l = (l + __shfl_xor_sync(~0u, l, 1)) + (__shfl_xor_sync(~0u, l, 2) + __shfl_xor_sync(~0u, l, 3));
#pragma unroll
                for (int j = 0; j < 4; j++) mma8(o[j], p4, j4, vm[j]);
                l = rcp(l);
                st_relaxed4(reinterpret_cast<uint4*>(dst), make_uint4(pack2(o[0][0] * l, o[0][1] * l), pack2(o[1][0] * l, o[1][1] * l),
                                                                      pack2(o[2][0] * l, o[2][1] * l), pack2(o[3][0] * l, o[3][1] * l)));
                bar_arrive(3, 256);
                st_relaxed4(reinterpret_cast<uint4*>(reinterpret_cast<char*>(&g_xo[(s + 2) & 3][0]) + oo), make_uint4(~0u, ~0u, ~0u, ~0u));
                if (w4 == 0 && l16 == 0) mbar_expect(bar + B_SC * 8, 2560);
            }
        }
        windows(ic<0>{});
    }
}

__global__ void __cluster_dims__(6, 1, 1) __launch_bounds__(256, 1)
chain_kernel(const __grid_constant__ CUtensorMap tq, const __grid_constant__ CUtensorMap tk, const __grid_constant__ CUtensorMap tv,
             const __grid_constant__ CUtensorMap two, const __grid_constant__ Descs D, const __grid_constant__ Descs DV,
             const __nv_bfloat16* __restrict__ x, const __nv_bfloat16* __restrict__ mem0) {
    extern __shared__ __align__(1024) uint8_t smem[];
    const uint32_t sb = smem_u32(smem);
    const int rank = blockIdx.x % 6, cl = blockIdx.x / 6, role = rank >= 4 ? 2 : rank & 1;
    const int tid = threadIdx.x, lane = tid & 31, gw = blockIdx.x * 8 + uni(tid >> 5);
    const CUtensorMap *tA = role == 2 ? &tv : &tq, *tB = role == 2 ? &tv : &tk;
    uint4 cur[4], nxt[4];
#pragma unroll
    for (int j = 0; j < 4; j++) {
        cur[j] = reinterpret_cast<const uint4*>(x)[gw * 128 + j * 32 + lane];
        nxt[j] = reinterpret_cast<const uint4*>(x)[(gw + 768) * 128 + j * 32 + lane];
    }
    if (gw < 512 && lane < 16) asm volatile("prefetch.global.L2 [%0];" :: "l"(x + (gw + 1536) * DM + lane * 64));
    if (threadIdx.x == 0) {
        TL(1, 0); TLSM(1);
        if ((sb & 0xFFFFFF) != SB0 || mapa(sb, 5) != (SB0 | 0x5000000u)) __trap();
        const uint32_t bar = sb + C_BAR;
        for (int i = 0; i < B_NUM; i++) mbar_init(bar + i * 8, i == B_MBF ? 12 : (i == B_GO ? 4 : 1));
        mbar_expect(bar + B_MF0 * 8, 8192);
        mbar_expect(bar + B_MF1 * 8, 8192);
        if (role == 2) {
            mbar_expect(bar + B_SC * 8, 2560);
            mbar_expect(bar + B_P0 * 8, 2048);
            mbar_expect(bar + B_P1 * 8, 2048);
            mbar_expect(bar + B_OF * 8, ONKV * (256 + 2048));
        } else {
            mbar_expect(bar + B_XS * 8, role ? 5120 : 3072);
            mbar_expect(bar + B_OL * 8, 3072);
            mbar_expect(bar + B_OF * 8, ONKQ * (256 + 2048));
        }
        asm volatile("fence.mbarrier_init.release.cluster;" ::: "memory");
        fence_async();
        for (int j = 0; j < 3; j++) load_chunk(tA, tB, cl, rank, sb + j * 65536, j, bar + (B_W0 + j) * 8);
    }
    __syncwarp();
    asm volatile("barrier.cluster.arrive.release.aligned;" ::: "memory");
    reset_exchange(mem0);
#pragma unroll 1
    for (int row = gw; row < SEQ; row += 768) {
        uint4 v[4];
#pragma unroll
        for (int j = 0; j < 4; j++) {
            v[j] = cur[j]; cur[j] = nxt[j];
            if (row + 1536 < SEQ) nxt[j] = reinterpret_cast<const uint4*>(x)[(row + 1536) * 128 + j * 32 + lane];
        }
        ln_row(v, row, lane);
    }
    if (tid == 0) TL(1, 5);
    __syncthreads();
    uint32_t goal = 0;
    if (tid == 160) {
        __threadfence();
        goal = (atomicAdd(&g_epoch, 1u) / 96 + 1) * 96;
        asm volatile("griddepcontrol.launch_dependents;" ::: "memory");
        TL(1, 4);
    }
    __syncwarp();
    asm volatile("barrier.cluster.wait.acquire.aligned;" ::: "memory");
    goal = uni(goal);
    const int wg = uni(threadIdx.x >> 7);
    if (role == 2) {
        if (wg == 0) chain_main<true, 0>(&tv, &tv, &two, sb, cl, rank, DV, goal);
        else chain_main<true, 1>(&tv, &tv, &two, sb, cl, rank, DV, goal);
    } else {
        if (wg == 0) chain_main<false, 0>(&tq, &tk, &two, sb, cl, rank, D, goal);
        else chain_main<false, 1>(&tq, &tk, &two, sb, cl, rank, D, goal);
    }
    __syncwarp();
    cluster_sync();
    if (threadIdx.x == 0) TL(1, 1);
}

__device__ __forceinline__ void wg256(float* d, uint32_t da, uint32_t db, uint32_t accum) {
    asm volatile("{\n.reg .b64 da, db;\n.reg .pred p;\nsetp.ne.u32 p, %130, 0;\nmov.b64 da, {%128, " DESC_HI_SW128 "};\nmov.b64 db, {%129, " DESC_HI_SW128 "};\n"
                 "wgmma.mma_async.sync.aligned.m64n256k16.f32.bf16.bf16 {"
                 "%0,%1,%2,%3,%4,%5,%6,%7,%8,%9,%10,%11,%12,%13,%14,%15,%16,%17,%18,%19,%20,%21,%22,%23,%24,%25,%26,%27,%28,%29,%30,%31,"
                 "%32,%33,%34,%35,%36,%37,%38,%39,%40,%41,%42,%43,%44,%45,%46,%47,%48,%49,%50,%51,%52,%53,%54,%55,%56,%57,%58,%59,%60,%61,%62,%63,"
                 "%64,%65,%66,%67,%68,%69,%70,%71,%72,%73,%74,%75,%76,%77,%78,%79,%80,%81,%82,%83,%84,%85,%86,%87,%88,%89,%90,%91,%92,%93,%94,%95,"
                 "%96,%97,%98,%99,%100,%101,%102,%103,%104,%105,%106,%107,%108,%109,%110,%111,%112,%113,%114,%115,%116,%117,%118,%119,%120,%121,%122,%123,%124,%125,%126,%127"
                 "}, da, db, p, 1, 1, 0, 1;\n}"
                 : ACC16(d), ACC16((d + 16)), ACC16((d + 32)), ACC16((d + 48)), ACC16((d + 64)), ACC16((d + 80)), ACC16((d + 96)), ACC16((d + 112))
                 : "r"(da), "r"(db), "r"(accum));
}
__device__ __forceinline__ void wg128(float* d, uint32_t da, uint32_t db, uint32_t accum) {
    asm volatile("{\n.reg .b64 da, db;\n.reg .pred p;\nsetp.ne.u32 p, %66, 0;\nmov.b64 da, {%64, " DESC_HI_SW128 "};\nmov.b64 db, {%65, " DESC_HI_SW128 "};\n"
                 "wgmma.mma_async.sync.aligned.m64n128k16.f32.bf16.bf16 {"
                 "%0,%1,%2,%3,%4,%5,%6,%7,%8,%9,%10,%11,%12,%13,%14,%15,%16,%17,%18,%19,%20,%21,%22,%23,%24,%25,%26,%27,%28,%29,%30,%31,"
                 "%32,%33,%34,%35,%36,%37,%38,%39,%40,%41,%42,%43,%44,%45,%46,%47,%48,%49,%50,%51,%52,%53,%54,%55,%56,%57,%58,%59,%60,%61,%62,%63"
                 "}, da, db, p, 1, 1, 0, 1;\n}"
                 : ACC16(d), ACC16((d + 16)), ACC16((d + 32)), ACC16((d + 48))
                 : "r"(da), "r"(db), "r"(accum));
}
__device__ __forceinline__ float sigmoidf_(float v) { return rcp(1.f + ex2(-1.4426950408889634f * v)); }
__device__ __forceinline__ void wait_count(int idx, uint32_t n) {
    uint32_t v, it = 0;
    while (true) {
        asm volatile("ld.acquire.gpu.global.u32 %0, [%1];" : "=r"(v) : "l"(&g_cnt[idx * 8]) : "memory");
        if (v >= n) break;
        __nanosleep(100);
        spin_guard(it);
    }
    asm volatile("fence.proxy.async.global;" ::: "memory");
}

constexpr int G_STAGES = 4, G_PAIRS = 18;
constexpr uint32_t G_STAGE = 49152, G_EPI = G_STAGES * G_STAGE, G_BAR = G_EPI + 32768, G_SMEM = G_BAR + 256;
__device__ __forceinline__ int glu_job(int p, int j) {
    if (j < 12) return j * G_PAIRS + p;
    if (p < 14) return j == 12 ? 224 + p : (j == 13 ? 242 + p : -1);
    return j < 14 ? 216 + (j - 12) * 4 + (p - 14) : (j == 14 ? 224 + p : -1);
}

__global__ void __cluster_dims__(2, 1, 1) __launch_bounds__(384, 1)
glu_kernel(const __grid_constant__ CUtensorMap tXn, const __grid_constant__ CUtensorMap tG, const __grid_constant__ CUtensorMap tU,
           const __grid_constant__ CUtensorMap tHst, const __grid_constant__ CUtensorMap tHld, const __grid_constant__ CUtensorMap tD,
           const __grid_constant__ CUtensorMap tYst) {
    extern __shared__ __align__(1024) uint8_t smem[];
    const uint32_t sb = smem_u32(smem);
    const uint32_t full = sb + G_BAR, empty = full + 64;
    const int tid = threadIdx.x, lane = tid & 31;
    const int warp = uni(tid >> 5), wg = warp >> 2;
    const int rank = blockIdx.x & 1, pair = blockIdx.x >> 1;
    asm volatile("griddepcontrol.launch_dependents;" ::: "memory");
    if (tid == 0) {
        TL(2, 0); TLSM(2);
        for (int i = 0; i < G_STAGES; i++) { mbar_init(full + i * 8, 1); mbar_init(empty + i * 8, 16); }
        asm volatile("fence.mbarrier_init.release.cluster;" ::: "memory");
        fence_async();
    }
    __syncthreads();
    cluster_sync();
    if (wg == 0) {
        asm volatile("setmaxnreg.dec.sync.aligned.u32 40;");
        if (warp == 0) {
            if (lane == 0) {
                uint32_t st = 0, ph = 1;
                asm volatile("fence.acq_rel.gpu;\nfence.proxy.async.global;" ::: "memory");
                for (int j = 0, job; (job = glu_job(pair, j)) >= 0; j++) {
                    const bool dn = job >= 224;
                    const int mp = dn ? (job - 224) >> 2 : job / 28, nt = dn ? job & 3 : job % 28, rb = mp * 2 + rank;
                    const CUtensorMap* tA = dn ? &tHld : &tXn;
                    const CUtensorMap* tB = dn ? &tD : (rank ? &tU : &tG);
                    const int bcol = dn ? nt * 256 + rank * 128 : nt * 128, nkb = dn ? FF / 64 : DM / 64;
                    if (j == 12) TL(2, 2);
                    if (dn) wait_count(CNT_H + rb, 56);
                    for (int kb = 0; kb < nkb; kb++) {
                        mbar_wait(empty + st * 8, ph);
                        const uint32_t base = sb + st * G_STAGE;
                        mbar_expect(full + st * 8, G_STAGE);
                        tma2d(base, tA, kb * 64, rb * 128, full + st * 8);
                        tma2d_mc(base + 16384 + rank * 16384, tB, bcol, kb * 64, full + st * 8, 3);
                        tma2d_mc(base + 16384 + rank * 16384 + 8192, tB, bcol + 64, kb * 64, full + st * 8, 3);
                        if (++st == G_STAGES) { st = 0; ph ^= 1; }
                    }
                }
            }
        } else if (warp < 3) {
            const int cw = warp - 1;
            const uint32_t epi = sb + G_EPI + cw * 16384;
            bar_arrive(3 + cw, 160);
            for (int j = 0, job; (job = glu_job(pair, j)) >= 0; j++) {
                const bool dn = job >= 224;
                const int mp = dn ? (job - 224) >> 2 : job / 28, nt = dn ? job & 3 : job % 28, rb = mp * 2 + rank;
                for (int hp = 0; hp <= (int)dn; hp++) {
                    bar_sync(1 + cw, 160);
                    if (lane == 0) {
                        const int col = dn ? nt * 256 + hp * 128 : nt * 128;
                        tma2d_store(dn ? &tYst : &tHst, col, rb * 128 + cw * 64, epi);
                        tma2d_store(dn ? &tYst : &tHst, col + 64, rb * 128 + cw * 64, epi + 8192);
                        asm volatile("cp.async.bulk.commit_group;\ncp.async.bulk.wait_group.read 0;" ::: "memory");
                    }
                    __syncwarp();
                    bar_arrive(3 + cw, 160);
                    if (lane == 0) {
                        asm volatile("cp.async.bulk.wait_group 0;\nfence.proxy.async.global;" ::: "memory");
                        count_up(dn ? CNT_Y + rb * 8 + nt * 2 + hp : CNT_H + rb);
                    }
                    __syncwarp();
                }
            }
        }
        cluster_sync();
    } else {
        asm volatile("setmaxnreg.inc.sync.aligned.u32 232;");
        const int cw = wg - 1, w4 = warp & 3;
        const uint32_t empty_dst = mapa(empty, lane & 1);
        const int er = w4 * 16 + (lane & 15), ec = lane >> 4;
        const uint32_t epi = sb + G_EPI + cw * 16384 + er * 128;
        uint32_t st = 0, ph = 0;
        float acc[128];
        auto put = [&](const uint32_t* o) {
            bar_sync(3 + cw, 160);
#pragma unroll
            for (int q = 0; q < 8; q++) stsm4(epi + (q >> 2) * 8192 + (((2 * (q & 3) + ec) ^ (er & 7)) << 4), o[q * 4], o[q * 4 + 1], o[q * 4 + 2], o[q * 4 + 3]);
            fence_async();
            bar_arrive(1 + cw, 160);
        };
        for (int j = 0, job; (job = glu_job(pair, j)) >= 0; j++) {
            const bool dn = job >= 224;
            const int nkb = dn ? FF / 64 : DM / 64;
            uint32_t prev = 0;
#pragma unroll 1
            for (int kb = 0; kb < nkb; kb++) {
                mbar_wait(full + st * 8, ph);
                const uint32_t base = sb + st * G_STAGE;
                const uint32_t da = (((base + cw * 8192) & 0x3FFFF) >> 4) | (1u << 16);
                const uint32_t db = (((base + 16384) & 0x3FFFF) >> 4) | (512u << 16);
                wg_fence();
#pragma unroll
                for (int k = 0; k < 4; k++) wg256(acc, da + k * 2, db + k * 128, (kb | k) != 0);
                wg_commit();
                if (kb > 0) {
                    wg_wait<1>();
                    if (lane < 2) mbar_arrive_cluster(empty_dst + prev * 8);
                }
                prev = st;
                if (++st == G_STAGES) { st = 0; ph ^= 1; }
            }
            wg_wait<0>();
            reg_fence<128>(acc);
            if (lane < 2) mbar_arrive_cluster(empty_dst + prev * 8);
            uint32_t o[32];
            if (!dn) {
#pragma unroll
                for (int i = 0; i < 32; i++) o[i] = pack2(sigmoidf_(acc[2 * i]) * acc[64 + 2 * i], sigmoidf_(acc[2 * i + 1]) * acc[65 + 2 * i]);
                put(o);
            } else {
#pragma unroll
                for (int hp = 0; hp < 2; hp++) {
#pragma unroll
                    for (int i = 0; i < 32; i++) {
                        const float a = acc[hp * 64 + 2 * i], b = acc[hp * 64 + 2 * i + 1];
                        o[i] = pack2(sigmoidf_(a) * a, sigmoidf_(b) * b);
                    }
                    put(o);
                }
            }
        }
        bar_sync(3 + cw, 160);
        if (tid == 128) TL(2, 1);
        cluster_sync();
    }
}

constexpr int O_STAGES = 7;
constexpr uint32_t O_STAGE = 32768, O_BAR = O_STAGES * O_STAGE, O_SMEM = O_BAR + 256;

__global__ void __cluster_dims__(2, 1, 1) __launch_bounds__(384, 1)
out_kernel(const __grid_constant__ CUtensorMap tOx, const __grid_constant__ CUtensorMap tWo, const __grid_constant__ CUtensorMap tX,
           const __grid_constant__ CUtensorMap tY, const __grid_constant__ CUtensorMap tOut) {
    extern __shared__ __align__(1024) uint8_t smem[];
    const uint32_t sb = smem_u32(smem);
    const uint32_t full = sb + O_BAR, empty = full + 64;
    const int tid = threadIdx.x, lane = tid & 31;
    const int warp = uni(tid >> 5), wg = warp >> 2;
    const int rank = blockIdx.x & 1, nt = (blockIdx.x >> 1) & 7, rb = (blockIdx.x >> 4) * 2 + rank;
    constexpr int NKB = HD / 64;
    if (tid == 0) {
        TL(3, 0); TLSM(3);
        for (int i = 0; i < O_STAGES; i++) { mbar_init(full + i * 8, 1); mbar_init(empty + i * 8, 16); }
        asm volatile("fence.mbarrier_init.release.cluster;" ::: "memory");
        fence_async();
    }
    __syncthreads();
    cluster_sync();
    if (wg == 0) {
        if (tid == 0) {
            uint32_t st = 0, ph = 1;
            for (int kb = 0; kb < O_STAGES; kb++) {
                mbar_expect(full + kb * 8, O_STAGE);
                tma2d_mc(sb + kb * O_STAGE + 16384 + rank * 8192, &tWo, nt * 128 + rank * 64, kb * 64, full + kb * 8, 3);
            }
            wait_count(CNT_OX + rb, 32);
            TL(3, 2);
            for (int kb = 0; kb < NKB + 2; kb++) {
                const uint32_t base = sb + st * O_STAGE;
                if (kb >= O_STAGES) {
                    mbar_wait(empty + st * 8, ph);
                    mbar_expect(full + st * 8, O_STAGE);
                }
                if (kb < NKB) {
                    tma2d(base, &tOx, kb * 64, rb * 128, full + st * 8);
                    if (kb >= O_STAGES) tma2d_mc(base + 16384 + rank * 8192, &tWo, nt * 128 + rank * 64, kb * 64, full + st * 8, 3);
                } else {
                    if (kb == NKB) wait_count(CNT_Y + rb * 8 + nt, 2);
                    tma2d(base, &tX, nt * 128 + (kb - NKB) * 64, rb * 128, full + st * 8);
                    tma2d(base + 16384, &tY, nt * 128 + (kb - NKB) * 64, rb * 128, full + st * 8);
                }
                if (++st == O_STAGES) { st = 0; ph ^= 1; }
            }
        }
        __syncwarp();
    } else {
        const int cw = wg - 1, w4 = warp & 3;
        const uint32_t empty_dst = mapa(empty, lane & 1);
        const int er = cw * 64 + w4 * 16 + (lane & 15), ec = lane >> 4;
        uint32_t st = 0, ph = 0, prev = 0;
        float acc[64];
#pragma unroll 1
        for (int kb = 0; kb < NKB; kb++) {
            mbar_wait(full + st * 8, ph);
            const uint32_t base = sb + st * O_STAGE;
            const uint32_t da = (((base + cw * 8192) & 0x3FFFF) >> 4) | (1u << 16);
            const uint32_t db = (((base + 16384) & 0x3FFFF) >> 4) | (512u << 16);
            wg_fence();
#pragma unroll
            for (int k = 0; k < 4; k++) wg128(acc, da + k * 2, db + k * 128, (kb | k) != 0);
            wg_commit();
            if (kb > 0) {
                wg_wait<1>();
                if (lane < 2) mbar_arrive_cluster(empty_dst + prev * 8);
            }
            prev = st;
            if (++st == O_STAGES) { st = 0; ph ^= 1; }
        }
        wg_wait<0>();
        reg_fence<64>(acc);
#pragma unroll
        for (int bx = 0; bx < 2; bx++) {
            mbar_wait(full + st * 8, ph);
            const uint32_t base = sb + st * O_STAGE;
#pragma unroll
            for (int j = 0; j < 4; j++) {
                uint32_t xv[4], yv[4];
                const uint32_t ad = base + er * 128 + (((2 * j + ec) ^ (er & 7)) << 4);
                ldsm4(xv, ad); ldsm4(yv, ad + 16384);
                const float* a = acc + bx * 32 + j * 8;
#pragma unroll
                for (int i = 0; i < 4; i++)
                    xv[i] = pack2(fmaf(a[2 * i], bf_lo(yv[i]), bf_lo(xv[i])), fmaf(a[2 * i + 1], bf_hi(yv[i]), bf_hi(xv[i])));
                stsm4(ad, xv[0], xv[1], xv[2], xv[3]);
            }
            fence_async();
            bar_sync(1 + cw, 128);
            if ((tid & 127) == 0) {
                tma2d_store(&tOut, nt * 128 + bx * 64, rb * 128 + cw * 64, base + cw * 8192);
                asm volatile("cp.async.bulk.commit_group;" ::: "memory");
            }
            if (++st == O_STAGES) { st = 0; ph ^= 1; }
        }
        if ((tid & 127) == 0) asm volatile("cp.async.bulk.wait_group 0;" ::: "memory");
        if (tid == 128) TL(3, 1);
        __syncwarp();
    }
    cluster_sync();
}

typedef CUresult (*EncodeFn)(CUtensorMap*, CUtensorMapDataType, cuuint32_t, void*, const cuuint64_t*, const cuuint64_t*, const cuuint32_t*,
                             const cuuint32_t*, CUtensorMapInterleave, CUtensorMapSwizzle, CUtensorMapL2promotion, CUtensorMapFloatOOBfill);

CUtensorMap make_map(EncodeFn enc, const void* p, int rows, int cols, int box_rows) {
    CUtensorMap m;
    cuuint64_t dims[2] = {(cuuint64_t)cols, (cuuint64_t)rows}, strides[1] = {(cuuint64_t)cols * 2};
    cuuint32_t box[2] = {64, (cuuint32_t)box_rows}, es[2] = {1, 1};
    enc(&m, CU_TENSOR_MAP_DATA_TYPE_BFLOAT16, 2, const_cast<void*>(p), dims, strides, box, es, CU_TENSOR_MAP_INTERLEAVE_NONE,
        CU_TENSOR_MAP_SWIZZLE_128B, CU_TENSOR_MAP_L2_PROMOTION_L2_128B, CU_TENSOR_MAP_FLOAT_OOB_FILL_NONE);
    return m;
}

}

#define PDL 7
extern "C" void kernel_launch(void* const* d_in, const int* in_sizes, int n_in, void* d_out, int out_size) {
    const __nv_bfloat16* x = (const __nv_bfloat16*)d_in[0];
    const __nv_bfloat16* mem0 = (const __nv_bfloat16*)d_in[1];
    void* fn = nullptr;
    cudaDriverEntryPointQueryResult qr;
    cudaGetDriverEntryPoint("cuTensorMapEncodeTiled", &fn, cudaEnableDefault, &qr);
    EncodeFn enc = (EncodeFn)fn;
    void *xn, *ox, *h, *y;
    cudaGetSymbolAddress(&xn, g_xn); cudaGetSymbolAddress(&ox, g_ox); cudaGetSymbolAddress(&h, g_h); cudaGetSymbolAddress(&y, g_y);

    const CUtensorMap tq = make_map(enc, d_in[2], DM, HD, 128), tk = make_map(enc, d_in[3], DM, HD, 128), tv = make_map(enc, d_in[4], DM, HD, 128);
    const CUtensorMap two16 = make_map(enc, d_in[5], HD, DM, 16);
    const CUtensorMap txn128 = make_map(enc, xn, SEQ, DM, 128), tg = make_map(enc, d_in[8], DM, FF, 64), tu = make_map(enc, d_in[9], DM, FF, 64);
    const CUtensorMap th64 = make_map(enc, h, SEQ, FF, 64), th128 = make_map(enc, h, SEQ, FF, 128), td = make_map(enc, d_in[10], FF, DM, 64);
    const CUtensorMap ty64 = make_map(enc, y, SEQ, DM, 64), ty128 = make_map(enc, y, SEQ, DM, 128), tx128 = make_map(enc, x, SEQ, DM, 128);
    const CUtensorMap tox = make_map(enc, ox, SEQ, HD, 128), two64 = make_map(enc, d_in[5], HD, DM, 64), tout = make_map(enc, d_out, SEQ, DM, 64);

    cudaFuncSetAttribute(chain_kernel, cudaFuncAttributeMaxDynamicSharedMemorySize, C_SMEM);
    cudaFuncSetAttribute(glu_kernel, cudaFuncAttributeMaxDynamicSharedMemorySize, G_SMEM);
    cudaFuncSetAttribute(out_kernel, cudaFuncAttributeMaxDynamicSharedMemorySize, O_SMEM);

    Descs D;
    for (int i = 0; i < 4; i++) D.sw[i] = DSW;
    D.ns = DNS;
    cudaStream_t st = cudaStreamPerThread;
    cudaLaunchAttribute at;
    at.id = cudaLaunchAttributeProgrammaticStreamSerialization;
    at.val.programmaticStreamSerializationAllowed = 1;
    cudaLaunchConfig_t cfg = {};
    cfg.stream = st; cfg.attrs = &at; cfg.numAttrs = 0;
    cfg.gridDim = dim3(96); cfg.blockDim = dim3(256); cfg.dynamicSmemBytes = C_SMEM;
    cudaLaunchKernelEx(&cfg, chain_kernel, tq, tk, tv, two16, D, D, x, mem0);
    cfg.gridDim = dim3(2 * G_PAIRS); cfg.blockDim = dim3(384); cfg.dynamicSmemBytes = G_SMEM; cfg.numAttrs = (PDL >> 1) & 1;
    cudaLaunchKernelEx(&cfg, glu_kernel, txn128, tg, tu, th64, th128, td, ty64);
    cfg.gridDim = dim3(128); cfg.dynamicSmemBytes = O_SMEM; cfg.numAttrs = (PDL >> 2) & 1;
    cudaLaunchKernelEx(&cfg, out_kernel, tox, two64, tx128, ty128, tout);
}
```

```cpp
#include <cuda_runtime.h>
#include <cuda_bf16.h>
#include <cuda.h>
#include <stdint.h>
#include <type_traits>

namespace {

constexpr int SEQ = 2048, DM = 1024, HD = 4096, FF = 3584, NSEG = 64;

__device__ __align__(1024) __nv_bfloat16 g_xn[SEQ * DM];
__device__ __align__(1024) uint4 g_xc[SEQ * DM / 8];
__device__ __align__(1024) __nv_bfloat16 g_ox[SEQ * HD];
__device__ __align__(1024) __nv_bfloat16 g_h[SEQ * FF];
__device__ __align__(1024) __nv_bfloat16 g_y[SEQ * DM];
__device__ __align__(1024) uint4 g_xmem[4][1024];
__device__ __align__(1024) uint4 g_xo[4][4096];
#define FSTR 8
__device__ __align__(1024) uint32_t g_flag[2][96 * FSTR];
enum { CNT_H = 0, CNT_OX = 16, CNT_Y = 32, CNT_NUM = 160 };
__device__ __align__(1024) uint32_t g_cnt[CNT_NUM * 8];
__device__ __align__(128) uint32_t g_epoch;
#define TL(k, i)
#define TLSM(k)

__device__ __forceinline__ uint32_t smem_u32(const void* p) { return (uint32_t)__cvta_generic_to_shared(p); }
__device__ __forceinline__ uint32_t mapa(uint32_t a, uint32_t r) {
    uint32_t o; asm("mapa.shared::cluster.u32 %0, %1, %2;" : "=r"(o) : "r"(a), "r"(r)); return o;
}
__device__ __forceinline__ void mbar_init(uint32_t a, uint32_t cnt) {
    asm volatile("mbarrier.init.shared.b64 [%0], %1;" :: "r"(a), "r"(cnt) : "memory");
}
__device__ __forceinline__ void mbar_expect(uint32_t a, uint32_t bytes) {
    asm volatile("mbarrier.arrive.expect_tx.shared.b64 _, [%0], %1;" :: "r"(a), "r"(bytes) : "memory");
}
__device__ __forceinline__ void mbar_arrive_cluster(uint32_t a) {
    asm volatile("mbarrier.arrive.shared::cluster.b64 _, [%0];" :: "r"(a) : "memory");
}
__device__ __forceinline__ void spin_guard(uint32_t& it) {
    asm volatile("{\n.reg .pred p;\nadd.u32 %0, %0, 1;\nsetp.gt.u32 p, %0, 0x400000;\n@p st.shared.u32 [%0], %0;\n}" : "+r"(it));
}
__device__ __forceinline__ void mbar_wait(uint32_t a, uint32_t par) {
    asm volatile("{\n.reg .pred p;\n.reg .u32 i;\nmov.u32 i, 0;\n"
                 "WL:\nadd.u32 i, i, 1;\nsetp.gt.u32 p, i, 0x400000;\n@p st.shared.u32 [i], i;\n"
                 "mbarrier.try_wait.parity.shared::cta.b64 p, [%0], %1;\n@!p bra WL;\n}" :: "r"(a), "r"(par) : "memory");
}
__device__ __forceinline__ void mbar_arrive(uint32_t a) { asm volatile("mbarrier.arrive.shared.b64 _, [%0];" :: "r"(a) : "memory"); }
__device__ __forceinline__ void tma2d(uint32_t dst, const CUtensorMap* m, int c0, int c1, uint32_t bar) {
    asm volatile("cp.async.bulk.tensor.2d.shared::cluster.global.mbarrier::complete_tx::bytes [%0], [%1, {%3, %4}], [%2];"
                 :: "r"(dst), "l"(m), "r"(bar), "r"(c0), "r"(c1) : "memory");
}
__device__ __forceinline__ void tma2d_mc(uint32_t dst, const CUtensorMap* m, int c0, int c1, uint32_t bar, uint16_t mask) {
    asm volatile("cp.async.bulk.tensor.2d.shared::cluster.global.mbarrier::complete_tx::bytes.multicast::cluster [%0], [%1, {%3, %4}], [%2], %5;"
                 :: "r"(dst), "l"(m), "r"(bar), "r"(c0), "r"(c1), "h"(mask) : "memory");
}
__device__ __forceinline__ void bulk_mc(uint32_t dst, const void* src, uint32_t bytes, uint32_t bar, uint16_t mask) {
    asm volatile("cp.async.bulk.shared::cluster.global.mbarrier::complete_tx::bytes.multicast::cluster [%0], [%1], %2, [%3], %4;"
                 :: "r"(dst), "l"(src), "r"(bytes), "r"(bar), "h"(mask) : "memory");
}
__device__ __forceinline__ void bulk_ld(uint32_t dst, const void* src, uint32_t bytes, uint32_t bar) {
    asm volatile("cp.async.bulk.shared::cluster.global.mbarrier::complete_tx::bytes [%0], [%1], %2, [%3];"
                 :: "r"(dst), "l"(src), "r"(bytes), "r"(bar) : "memory");
}
__device__ __forceinline__ uint32_t gtick() { uint64_t c; asm volatile("mov.u64 %0, %%globaltimer;" : "=l"(c)); return (uint32_t)c >> 5; }
__device__ __forceinline__ uint32_t gtick_dep(uint32_t zero) {
    uint32_t c;
    asm volatile("{\n.reg .pred p;\nsetp.eq.u32 p, %1, 0;\nmov.u32 %0, 0;\n@p mov.u32 %0, %%globaltimer_lo;\n}" : "=r"(c) : "r"(zero));
    return c >> 5;
}
__device__ __forceinline__ uint32_t ld_relaxed1(const void* p) {
    uint32_t v; asm volatile("ld.relaxed.gpu.global.u32 %0, [%1];" : "=r"(v) : "l"(p) : "memory"); return v;
}
__device__ __forceinline__ bool any_nan(float a, float b) {
    uint32_t r;
    asm volatile("{\n.reg .pred p;\nsetp.nan.f32 p, %1, %2;\nvote.sync.any.pred p, p, 0xffffffff;\nselp.u32 %0, 1, 0, p;\n}" : "=r"(r) : "f"(a), "f"(b));
    return r;
}
__device__ __forceinline__ bool bar_sync_any_nan(float a, float b) {
    uint32_t r;
    asm volatile("{\n.reg .pred p;\nsetp.nan.f32 p, %1, %2;\nbarrier.cta.red.or.aligned.pred p, 6, 256, p;\nselp.u32 %0, 1, 0, p;\n}"
                 : "=r"(r) : "f"(a), "f"(b) : "memory");
    return r;
}
__device__ __forceinline__ void bar_arrive(int id, int n) { asm volatile("bar.arrive %0, %1;" :: "r"(id), "r"(n) : "memory"); }
__device__ __forceinline__ uint32_t clk() { uint64_t c; asm volatile("mov.u64 %0, %%clock64;" : "=l"(c)); return (uint32_t)c; }
__device__ __forceinline__ void tma2d_store(const CUtensorMap* m, int c0, int c1, uint32_t src) {
    asm volatile("cp.async.bulk.tensor.2d.global.shared::cta.bulk_group [%0, {%1, %2}], [%3];"
                 :: "l"(m), "r"(c0), "r"(c1), "r"(src) : "memory");
}
__device__ __forceinline__ void bar_sync(int id, int n) { asm volatile("bar.sync %0, %1;" :: "r"(id), "r"(n) : "memory"); }
__device__ __forceinline__ void fence_async() { asm volatile("fence.proxy.async.shared::cta;" ::: "memory"); }
__device__ __forceinline__ void cluster_sync() {
    asm volatile("barrier.cluster.arrive.release.aligned;\nbarrier.cluster.wait.acquire.aligned;" ::: "memory");
}
__device__ __forceinline__ void ldsm4(uint32_t* r, uint32_t a) {
    asm volatile("ldmatrix.sync.aligned.m8n8.x4.shared.b16 {%0,%1,%2,%3}, [%4];"
                 : "=r"(r[0]), "=r"(r[1]), "=r"(r[2]), "=r"(r[3]) : "r"(a) : "memory");
}
__device__ __forceinline__ void ldsm4t(uint32_t* r, uint32_t a) {
    asm volatile("ldmatrix.sync.aligned.m8n8.x4.trans.shared.b16 {%0,%1,%2,%3}, [%4];"
                 : "=r"(r[0]), "=r"(r[1]), "=r"(r[2]), "=r"(r[3]) : "r"(a) : "memory");
}
__device__ __forceinline__ void stsm4(uint32_t a, uint32_t r0, uint32_t r1, uint32_t r2, uint32_t r3) {
    asm volatile("stmatrix.sync.aligned.m8n8.x4.shared.b16 [%0], {%1,%2,%3,%4};" :: "r"(a), "r"(r0), "r"(r1), "r"(r2), "r"(r3) : "memory");
}
__device__ __forceinline__ void stsm4f(uint32_t a, const float* v) {
    asm volatile("{\n.reg .b32 a, b, c, d;\nmov.b32 a, %1;\nmov.b32 b, %2;\nmov.b32 c, %3;\nmov.b32 d, %4;\n"
                 "stmatrix.sync.aligned.m8n8.x4.shared.b16 [%0], {a, b, c, d};\n}" :: "r"(a), "f"(v[0]), "f"(v[1]), "f"(v[2]), "f"(v[3]) : "memory");
}
__device__ __forceinline__ void ldsm4f(float* v, uint32_t a) {
    uint32_t r[4];
    ldsm4(r, a);
#pragma unroll
    for (int i = 0; i < 4; i++) v[i] = __uint_as_float(r[i]);
}
__device__ __forceinline__ void stsm4t(uint32_t a, uint32_t r0, uint32_t r1, uint32_t r2, uint32_t r3) {
    asm volatile("stmatrix.sync.aligned.m8n8.x4.trans.shared.b16 [%0], {%1,%2,%3,%4};" :: "r"(a), "r"(r0), "r"(r1), "r"(r2), "r"(r3) : "memory");
}
__device__ __forceinline__ void stsm2(uint32_t a, uint32_t r0, uint32_t r1) {
    asm volatile("stmatrix.sync.aligned.m8n8.x2.shared.b16 [%0], {%1,%2};" :: "r"(a), "r"(r0), "r"(r1) : "memory");
}
__device__ __forceinline__ void stsm2t(uint32_t a, uint32_t r0, uint32_t r1) {
    asm volatile("stmatrix.sync.aligned.m8n8.x2.trans.shared.b16 [%0], {%1,%2};" :: "r"(a), "r"(r0), "r"(r1) : "memory");
}
__device__ __forceinline__ uint32_t movm(uint32_t a) {
    uint32_t d; asm volatile("movmatrix.sync.aligned.m8n8.trans.b16 %0, %1;" : "=r"(d) : "r"(a)); return d;
}
__device__ __forceinline__ void mma16(float* d, uint32_t a0, uint32_t a1, uint32_t a2, uint32_t a3, uint32_t b0, uint32_t b1) {
    asm volatile("mma.sync.aligned.m16n8k16.row.col.f32.bf16.bf16.f32 {%0,%1,%2,%3}, {%4,%5,%6,%7}, {%8,%9}, {%0,%1,%2,%3};"
                 : "+f"(d[0]), "+f"(d[1]), "+f"(d[2]), "+f"(d[3]) : "r"(a0), "r"(a1), "r"(a2), "r"(a3), "r"(b0), "r"(b1));
}
__device__ __forceinline__ void mma8(float* d, uint32_t a0, uint32_t a1, uint32_t b0) {
    asm volatile("mma.sync.aligned.m16n8k8.row.col.f32.bf16.bf16.f32 {%0,%1,%2,%3}, {%4,%5}, {%6}, {%0,%1,%2,%3};"
                 : "+f"(d[0]), "+f"(d[1]), "+f"(d[2]), "+f"(d[3]) : "r"(a0), "r"(a1), "r"(b0));
}
__device__ __forceinline__ uint32_t pack2(float lo, float hi) {
    uint32_t r; asm("cvt.rn.bf16x2.f32 %0, %1, %2;" : "=r"(r) : "f"(hi), "f"(lo)); return r;
}
__device__ __forceinline__ float bf_lo(uint32_t v) { return __uint_as_float(v << 16); }
__device__ __forceinline__ float bf_hi(uint32_t v) { return __uint_as_float(v & 0xFFFF0000u); }
__device__ __forceinline__ float ex2(float x) { float y; asm("ex2.approx.ftz.f32 %0, %1;" : "=f"(y) : "f"(x)); return y; }
__device__ __forceinline__ float rcp(float x) { float y; asm("rcp.approx.ftz.f32 %0, %1;" : "=f"(y) : "f"(x)); return y; }
__device__ __forceinline__ void sts4f(uint32_t a, float x, float y, float z, float w) {
    asm volatile("st.shared.v4.f32 [%0], {%1,%2,%3,%4};" :: "r"(a), "f"(x), "f"(y), "f"(z), "f"(w) : "memory");
}
__device__ __forceinline__ void sts1u(uint32_t a, uint32_t v) { asm volatile("st.shared.u32 [%0], %1;" :: "r"(a), "r"(v) : "memory"); }
__device__ __forceinline__ void sts4u(uint32_t a, uint4 v) {
    asm volatile("st.shared.v4.u32 [%0], {%1,%2,%3,%4};" :: "r"(a), "r"(v.x), "r"(v.y), "r"(v.z), "r"(v.w) : "memory");
}
__device__ __forceinline__ float4 lds4f(uint32_t a) {
    float4 v; asm volatile("ld.shared.v4.f32 {%0,%1,%2,%3}, [%4];" : "=f"(v.x), "=f"(v.y), "=f"(v.z), "=f"(v.w) : "r"(a) : "memory"); return v;
}
__device__ __forceinline__ float2 lds2f(uint32_t a) {
    float2 v; asm volatile("ld.shared.v2.f32 {%0,%1}, [%2];" : "=f"(v.x), "=f"(v.y) : "r"(a) : "memory"); return v;
}
__device__ __forceinline__ uint4 lds4u(uint32_t a) {
    uint4 v; asm volatile("ld.shared.v4.u32 {%0,%1,%2,%3}, [%4];" : "=r"(v.x), "=r"(v.y), "=r"(v.z), "=r"(v.w) : "r"(a) : "memory"); return v;
}
__device__ __forceinline__ uint32_t lds1u(uint32_t a) {
    uint32_t v; asm volatile("ld.shared.u32 %0, [%1];" : "=r"(v) : "r"(a) : "memory"); return v;
}
__device__ __forceinline__ uint2 lds2u(uint32_t a) {
    uint2 v; asm volatile("ld.shared.v2.u32 {%0,%1}, [%2];" : "=r"(v.x), "=r"(v.y) : "r"(a) : "memory"); return v;
}
__device__ __forceinline__ void st_async4(uint32_t a, uint32_t bar, float x, float y, float z, float w) {
    asm volatile("st.async.shared::cluster.mbarrier::complete_tx::bytes.v4.f32 [%0], {%1,%2,%3,%4}, [%5];"
                 :: "r"(a), "f"(x), "f"(y), "f"(z), "f"(w), "r"(bar) : "memory");
}
__device__ __forceinline__ void st_async2(uint32_t a, uint32_t bar, float x, float y) {
    asm volatile("st.async.shared::cluster.mbarrier::complete_tx::bytes.v2.f32 [%0], {%1,%2}, [%3];"
                 :: "r"(a), "f"(x), "f"(y), "r"(bar) : "memory");
}
__device__ __forceinline__ void st_async1f(uint32_t a, uint32_t bar, float x) {
    asm volatile("st.async.shared::cluster.mbarrier::complete_tx::bytes.f32 [%0], %1, [%2];" :: "r"(a), "f"(x), "r"(bar) : "memory");
}
__device__ __forceinline__ void st_async1(uint32_t a, uint32_t bar, uint32_t x) {
    asm volatile("st.async.shared::cluster.mbarrier::complete_tx::bytes.b32 [%0], %1, [%2];" :: "r"(a), "r"(x), "r"(bar) : "memory");
}
__device__ __forceinline__ uint4 ld_relaxed4(const uint4* p) {
    uint4 v;
    asm volatile("ld.relaxed.gpu.global.v4.u32 {%0,%1,%2,%3}, [%4];" : "=r"(v.x), "=r"(v.y), "=r"(v.z), "=r"(v.w) : "l"(p) : "memory");
    return v;
}
__device__ __forceinline__ void st_relaxed4(uint4* p, uint4 v) {
    asm volatile("st.relaxed.gpu.global.v4.u32 [%0], {%1,%2,%3,%4};" :: "l"(p), "r"(v.x), "r"(v.y), "r"(v.z), "r"(v.w) : "memory");
}
__device__ __forceinline__ void count_up(int idx) {
    asm volatile("red.release.gpu.global.add.u32 [%0], 1;" :: "l"(&g_cnt[idx * 8]) : "memory");
}
__device__ __forceinline__ void st_pred1(void* p, uint32_t v, bool on) {
    asm volatile("{\n.reg .pred p;\nsetp.ne.u32 p, %2, 0;\n@p st.relaxed.gpu.global.u32 [%0], %1;\n}" :: "l"(p), "r"(v), "r"((uint32_t)on) : "memory");
}
__device__ __forceinline__ void st_pred4(void* p, uint4 v, bool on) {
    asm volatile("{\n.reg .pred p;\nsetp.ne.u32 p, %5, 0;\n@p st.global.v4.u32 [%0], {%1,%2,%3,%4};\n}"
                 :: "l"(p), "r"(v.x), "r"(v.y), "r"(v.z), "r"(v.w), "r"((uint32_t)on) : "memory");
}
__device__ __forceinline__ void st_relaxed1(void* p, uint32_t v) {
    asm volatile("st.relaxed.gpu.global.u32 [%0], %1;" :: "l"(p), "r"(v) : "memory");
}
__device__ __forceinline__ uint32_t umax4(uint4 v) { return max(max(v.x, v.y), max(v.z, v.w)); }
__device__ __forceinline__ void wg_fence() { asm volatile("wgmma.fence.sync.aligned;" ::: "memory"); }
__device__ __forceinline__ void wg_commit() { asm volatile("wgmma.commit_group.sync.aligned;" ::: "memory"); }
template <int N> __device__ __forceinline__ void wg_wait() { asm volatile("wgmma.wait_group.sync.aligned %0;" :: "n"(N) : "memory"); }
template <int N> __device__ __forceinline__ void reg_fence(float* d) {
#pragma unroll
    for (int i = 0; i < N; i++) asm volatile("" : "+f"(d[i]) :: "memory");
}
#define ACC16(d) "+f"(d[0]), "+f"(d[1]), "+f"(d[2]), "+f"(d[3]), "+f"(d[4]), "+f"(d[5]), "+f"(d[6]), "+f"(d[7]), \
                 "+f"(d[8]), "+f"(d[9]), "+f"(d[10]), "+f"(d[11]), "+f"(d[12]), "+f"(d[13]), "+f"(d[14]), "+f"(d[15])
#define DESC_HI_SW128 "0x40000040"
#define OUT16(d) "=f"(d[0]), "=f"(d[1]), "=f"(d[2]), "=f"(d[3]), "=f"(d[4]), "=f"(d[5]), "=f"(d[6]), "=f"(d[7]), \
                 "=f"(d[8]), "=f"(d[9]), "=f"(d[10]), "=f"(d[11]), "=f"(d[12]), "=f"(d[13]), "=f"(d[14]), "=f"(d[15])
template <int ACCUM, int BOFF>
__device__ __forceinline__ void wg32_rs(float* d, const uint32_t* a, uint64_t dsw) {
    if (ACCUM)
        asm volatile("{\n.reg .b64 db;\nadd.s64 db, %20, %21;\n"
                     "wgmma.mma_async.sync.aligned.m64n32k16.f32.bf16.bf16 {%0,%1,%2,%3,%4,%5,%6,%7,%8,%9,%10,%11,%12,%13,%14,%15}, "
                     "{%16,%17,%18,%19}, db, 1, 1, 1, 0;\n}"
                     : ACC16(d) : "r"(a[0]), "r"(a[1]), "r"(a[2]), "r"(a[3]), "l"(dsw), "n"(BOFF));
    else
        asm volatile("{\n.reg .b64 db;\nadd.s64 db, %20, %21;\n"
                     "wgmma.mma_async.sync.aligned.m64n32k16.f32.bf16.bf16 {%0,%1,%2,%3,%4,%5,%6,%7,%8,%9,%10,%11,%12,%13,%14,%15}, "
                     "{%16,%17,%18,%19}, db, 0, 1, 1, 0;\n}"
                     : OUT16(d) : "r"(a[0]), "r"(a[1]), "r"(a[2]), "r"(a[3]), "l"(dsw), "n"(BOFF));
}
template <int ACCUM, int AOFF, int BOFF>
__device__ __forceinline__ void wg32_ss(float* d, uint64_t dsw) {
    if (ACCUM)
        asm volatile("{\n.reg .b64 da, db;\nadd.s64 da, %16, %17;\nadd.s64 db, %16, %18;\n"
                     "wgmma.mma_async.sync.aligned.m64n32k16.f32.bf16.bf16 {%0,%1,%2,%3,%4,%5,%6,%7,%8,%9,%10,%11,%12,%13,%14,%15}, "
                     "da, db, 1, 1, 1, 1, 0;\n}"
                     : ACC16(d) : "l"(dsw), "n"(AOFF), "n"(BOFF));
    else
        asm volatile("{\n.reg .b64 da, db;\nadd.s64 da, %16, %17;\nadd.s64 db, %16, %18;\n"
                     "wgmma.mma_async.sync.aligned.m64n32k16.f32.bf16.bf16 {%0,%1,%2,%3,%4,%5,%6,%7,%8,%9,%10,%11,%12,%13,%14,%15}, "
                     "da, db, 0, 1, 1, 1, 0;\n}"
                     : OUT16(d) : "l"(dsw), "n"(AOFF), "n"(BOFF));
}
template <int ACCUM, int AOFF, int BOFF>
__device__ __forceinline__ void wg8_ss(float* d, uint64_t dsw, uint64_t dns) {
    if (!ACCUM)
        asm volatile("{\n.reg .b64 da, db;\nadd.s64 da, %4, %6;\nadd.s64 db, %5, %7;\n"
                     "wgmma.mma_async.sync.aligned.m64n8k16.f32.bf16.bf16 {%0,%1,%2,%3}, da, db, 0, 1, 1, 1, 0;\n}"
                     : "=f"(d[0]), "=f"(d[1]), "=f"(d[2]), "=f"(d[3]) : "l"(dsw), "l"(dns), "n"(AOFF), "n"(BOFF));
    else
        asm volatile("{\n.reg .b64 da, db;\nadd.s64 da, %4, %6;\nadd.s64 db, %5, %7;\n"
                     "wgmma.mma_async.sync.aligned.m64n8k16.f32.bf16.bf16 {%0,%1,%2,%3}, da, db, 1, 1, 1, 1, 0;\n}"
                     : "+f"(d[0]), "+f"(d[1]), "+f"(d[2]), "+f"(d[3]) : "l"(dsw), "l"(dns), "n"(AOFF), "n"(BOFF));
}
template <int I0, int I1, class F>
__device__ __forceinline__ void static_for(F&& f) {
    if constexpr (I0 < I1) { f(std::integral_constant<int, I0>{}); static_for<I0 + 1, I1>(f); }
}
template <int I0, int I1, int AOFF, int BOFF>
__device__ __forceinline__ void wg8_chain(float* d, uint64_t dsw, uint64_t dns) {
    wg_fence();
    static_for<I0, I1>([&](auto i) { wg8_ss<i.value != 0, AOFF + i.value * 128, BOFF + i.value * 16>(d, dsw, dns); });
    wg_commit();
}

__device__ __forceinline__ void ln_row(const uint4* v, int row, int lane) {
    float f[32];
#pragma unroll
    for (int j = 0; j < 4; j++) {
        f[j * 8 + 0] = bf_lo(v[j].x); f[j * 8 + 1] = bf_hi(v[j].x); f[j * 8 + 2] = bf_lo(v[j].y); f[j * 8 + 3] = bf_hi(v[j].y);
        f[j * 8 + 4] = bf_lo(v[j].z); f[j * 8 + 5] = bf_hi(v[j].z); f[j * 8 + 6] = bf_lo(v[j].w); f[j * 8 + 7] = bf_hi(v[j].w);
    }
    float s = 0.f;
#pragma unroll
    for (int i = 0; i < 32; i++) s += f[i];
#pragma unroll
    for (int o = 16; o; o >>= 1) s += __shfl_xor_sync(~0u, s, o);
    const float mean = s * (1.f / DM);
    float q = 0.f;
#pragma unroll
    for (int i = 0; i < 32; i++) { f[i] -= mean; q += f[i] * f[i]; }
#pragma unroll
    for (int o = 16; o; o >>= 1) q += __shfl_xor_sync(~0u, q, o);
    const float r = 1.f / sqrtf(q * (1.f / DM) + 1e-5f);
    uint4* dst = reinterpret_cast<uint4*>(g_xn + (size_t)row * DM);
    uint4* dst2 = g_xc + (row >> 5) * 4096 + (lane >> 3) * 256 + (row & 31) * 8 + ((lane & 7) ^ (row & 7));
#pragma unroll
    for (int j = 0; j < 4; j++) {
        const uint4 o = make_uint4(pack2(f[j * 8] * r, f[j * 8 + 1] * r), pack2(f[j * 8 + 2] * r, f[j * 8 + 3] * r),
                                   pack2(f[j * 8 + 4] * r, f[j * 8 + 5] * r), pack2(f[j * 8 + 6] * r, f[j * 8 + 7] * r));
        dst[j * 32 + lane] = o;
        dst2[(j & 1) * 2048 + (j >> 1) * 1024] = o;
    }
}
__device__ __forceinline__ void reset_exchange(const __nv_bfloat16* __restrict__ mem0) {
    const int gi = blockIdx.x * 256 + threadIdx.x;
    const uint4 poison = make_uint4(~0u, ~0u, ~0u, ~0u);
    if (gi < 1024) {
        uint4 m = reinterpret_cast<const uint4*>(mem0)[(gi & 7) * 128 + (gi >> 3)];
        if (m.x == ~0u) m.x = 0x7FFF7FFFu;
        if (m.y == ~0u) m.y = 0x7FFF7FFFu;
        if (m.z == ~0u) m.z = 0x7FFF7FFFu;
        if (m.w == ~0u) m.w = 0x7FFF7FFFu;
        g_xmem[0][gi] = m;
    } else if (gi < 4096) {
        (&g_xmem[0][0])[gi] = poison;
    } else if (gi < 4096 + 16384) {
        (&g_xo[0][0])[gi - 4096] = poison;
    } else if (gi < 4096 + 16384 + 48 * FSTR) {
        reinterpret_cast<uint4*>(&g_flag[0][0])[gi - 4096 - 16384] = poison;
    } else if (gi >= 24576 - CNT_NUM) {
        g_cnt[(24575 - gi) * 8] = 0;
    }
}

#define ONKQ 45
constexpr int ONKV = 128 - 2 * ONKQ;
constexpr uint32_t SB0 = 1024;
constexpr uint32_t C_WS = 0, C_XN = 65536, C_MB = 98304, C_WO = 114688, C_SMEM = 232448;
constexpr uint32_t C_BAR = C_SMEM - 384, C_CAL = C_BAR + 192;
constexpr uint32_t C_SLOTQ = C_WO + ONKQ * 2048, C_QX = C_SLOTQ + 8192, C_KX = C_QX + 4096,
                   C_XSL = C_KX + 4096, C_OL = C_XSL + 5120;
constexpr uint32_t C_SLOTV = C_WO + ONKV * 2048, C_V = C_SLOTV + 8192, C_PL = C_V + 20480, C_SL = C_PL + 4096;
constexpr uint32_t C_DUMP = C_BAR - 512;
static_assert(C_OL + 3072 <= C_DUMP && C_SL + 2560 <= C_DUMP, "smem overflow");
enum { B_W0 = 0, B_W1, B_W2, B_WS, B_XF0, B_XF1, B_SC, B_P0, B_P1, B_XS, B_OL, B_MF0, B_MF1, B_OF, B_RT0, B_RT1, B_VF, B_MBF, B_GO, B_DUMP, B_NUM };
struct Descs { uint64_t sw[4], ns; };
constexpr uint64_t DSW = 0x4000004000010000ull, DNS = 0x0000001000080000ull;
template <int V> using ic = std::integral_constant<int, V>;
constexpr float SM_SCALE = 0.08838834764831845f * 1.4426950408889634f;

#define TSD(i) do {} while (0)
#define TS_FLUSH(w)
#define TSX(i, c)
#define TS(i)
#define NOFILL 0
#define DLY1 2200
#define DLY2 1300
#define CNTPOS 0
#define SWAP16 0
#define SSFIRST 1
#define EARLYB 0
#define CANARY ~0u
#define QK1 10
#define RFPOS 6
#define STPOS 14
#define OTAIL 3
#define DLYS 450
#define DLYB 1
#define VLEAD 1

#define VEARLY 8
#define QSPLIT 20
__device__ __forceinline__ bool elect() {
    uint32_t r;
    asm volatile("{\n.reg .pred p;\nelect.sync _|p, 0xffffffff;\nselp.u32 %0, 1, 0, p;\n}" : "=r"(r));
    return r;
}
__device__ __forceinline__ int uni(int v) { return __shfl_sync(~0u, v, 0); }
__device__ __forceinline__ void calibrate(uint32_t cal, float keep) {
    const uint32_t t0 = gtick();
    uint32_t t, it = 0;
    do { t = gtick(); spin_guard(it); } while (__any_sync(~0u, t == t0));
    const uint32_t c = clk();
    const uint4 p = lds4u(cal);
    const float cpt = 256.f * fminf(fmaxf(__fdividef((float)(c - p.y), (float)((t - p.x) & 0x7FFFFFF)), 16.f), 128.f);
    __syncwarp();
    sts4u(cal, make_uint4(t, c, (uint32_t)(keep > 0.f ? fmaf(keep, (float)p.z - cpt, cpt) : cpt), 0));
}
struct Stamps { uint32_t v[6]; };
__device__ __forceinline__ void load_stamps2(Stamps& t, const uint32_t* f, uint32_t l16, bool on = true) {
    const char* p = reinterpret_cast<const char*>(f) + (l16 >> 2) * FSTR;
    asm volatile("{\n.reg .pred p;\nsetp.ne.u32 p, %7, 0;\nmov.u32 %0, 63;\nmov.u32 %1, 63;\nmov.u32 %2, 63;\nmov.u32 %3, 63;\nmov.u32 %4, 63;\nmov.u32 %5, 63;\n"
                 "@p ld.relaxed.gpu.global.v2.u32 {%0, %1}, [%6];\n@p ld.relaxed.gpu.global.v2.u32 {%2, %3}, [%6 + %8];\n"
                 "@p ld.relaxed.gpu.global.v2.u32 {%4, %5}, [%6 + %9];\n}"
                 : "=&r"(t.v[0]), "=&r"(t.v[1]), "=&r"(t.v[2]), "=&r"(t.v[3]), "=&r"(t.v[4]), "=&r"(t.v[5])
                 : "l"(p), "r"((uint32_t)on), "n"(128 * FSTR), "n"(256 * FSTR) : "memory");
}
__device__ __forceinline__ void load_stamps1(uint32_t* v, const uint32_t* f, uint32_t l16, bool on = true) {
    const char* p = reinterpret_cast<const char*>(f) + (l16 >> 2) * FSTR;
    asm volatile("{\n.reg .pred p;\nsetp.ne.u32 p, %4, 0;\nmov.u32 %0, 63;\nmov.u32 %1, 63;\nmov.u32 %2, 63;\n"
                 "@p ld.relaxed.gpu.global.u32 %0, [%3];\n@p ld.relaxed.gpu.global.u32 %1, [%3 + %5];\n@p ld.relaxed.gpu.global.u32 %2, [%3 + %6];\n}"
                 : "=&r"(v[0]), "=&r"(v[1]), "=&r"(v[2]) : "l"(p), "r"((uint32_t)on), "n"(128 * FSTR), "n"(256 * FSTR) : "memory");
}
template <int N>
__device__ __forceinline__ uint32_t stamps_missing(const uint32_t* v, int s) {
    uint32_t x = 0;
#pragma unroll
    for (int i = 0; i < N; i++) x |= v[i] ^ s;
    return x & 63;
}
template <int N>
__device__ __forceinline__ uint32_t latest_stamp(const uint32_t* v, const uint4 cal) {
    int late = (int)(v[0] - (cal.x << 6));
#pragma unroll
    for (int i = 1; i < N; i++) late = max(late, (int)(v[i] - (cal.x << 6)));
    return cal.y + (((late >> 6) * (int)cal.z) >> 8);
}
__device__ __forceinline__ void wait_clock(uint32_t target) {
    while (__any_sync(~0u, target - clk() < 65536u)) {}
}

template <int BYTES>
__device__ __forceinline__ bool incomplete(uint32_t buf, uint32_t l16) {
    uint32_t m = 0;
#pragma unroll 1
    for (int o = 0; o < BYTES; o += 256) m = max(m, umax4(lds4u(buf + o + (l16 & 255))));
    return __any_sync(~0u, m == ~0u);
}
__device__ __forceinline__ void refetch(uint32_t buf, const uint4* src, uint32_t bytes, uint32_t b, int w4, int barid, uint32_t& tries) {
    spin_guard(tries);
    bar_sync(barid, 128);
    if (w4 == 0 && elect()) { mbar_expect(b, bytes); bulk_ld(buf, src, bytes, b); }
    __syncwarp();
    mbar_wait(b, 0);
    bar_sync(barid, 128);
    if (w4 == 0 && elect()) mbar_arrive(b);
    __syncwarp();
}

__device__ __forceinline__ void load_chunk(const CUtensorMap* tA, const CUtensorMap* tB, int cl, int rank, uint32_t dst, int j, uint32_t b) {
    const int colA = cl * 256 + (rank >= 4 ? (rank - 4) * 128 : rank * 64), colB = colA + (rank >= 4 ? 64 : 0);
    mbar_expect(b, 65536);
    tma2d(dst, tA, colA, j * 128, b);
    tma2d(dst + 16384, tB, colB, j * 128, b);
    tma2d(dst + 32768, tB, colB, 512 + j * 128, b);
    tma2d(dst + 49152, tA, colA, 512 + j * 128, b);
}

template <bool ISV, int WG>
__device__ __forceinline__ void chain_main(const CUtensorMap* tA, const CUtensorMap* tB, const CUtensorMap* tWo,
                                           const uint32_t sb, const int cl, const int rank, const Descs& D, const uint32_t goal) {
    const int tid = threadIdx.x;
    uint32_t l16 = __shfl_sync(~0u, (tid & 31) * 16, tid & 31);
    int w4 = uni((tid >> 5) & 3);
    const int role = ISV ? 2 : (rank & 1), hh = ISV ? rank - 4 : rank >> 1, head = 2 * cl + hh;
    const uint32_t bar = sb + C_BAR;
    constexpr int ONK = ISV ? ONKV : ONKQ;
    const int ostart = (hh * 128 + role * ONKQ);

    uint32_t wk[24][4], wv[24][4];
    uint32_t a_adr;
    {
        if (WG == 1 && w4 == 0) calibrate(sb + C_CAL, 0.f);
        const int lane = tid & 31, kr = (lane & 7) + ((lane >> 4) << 3);
        a_adr = __shfl_sync(~0u, sb + WG * 32768 + kr * 128 + (((w4 * 2 + ((lane >> 3) & 1)) ^ (kr & 7)) << 4), lane);
#pragma unroll
        for (int j = 0; j < 3; j++) {
            mbar_wait(bar + (B_W0 + j) * 8, 0);
#pragma unroll
            for (int i = 0; i < 8; i++) {
                ldsm4t(wk[j * 8 + i], a_adr + j * 65536 + i * 2048);
                ldsm4t(wv[j * 8 + i], a_adr + j * 65536 + 16384 + i * 2048);
            }
            if (j != 1) {
                bar_sync(6, 256);
                if (j == 0 && tid == 0) TL(1, 6);
                if (WG == 0 && j == 0 && w4 == 0 && elect()) load_chunk(tA, tB, cl, rank, sb + C_WS, 3, bar + B_WS * 8);
                if (WG == 0 && j == 2) {
                    if (elect())
                        for (int i = w4; i < ONK; i += 4) tma2d(sb + C_WO + i * 2048, tWo, cl * 64, (ostart + i) * 16, bar + B_OF * 8);
                }
                __syncwarp();
            }
        }
        if (NOFILL) { for (uint32_t o = C_WO + ONK * 2048 + tid * 16; o < C_BAR; o += 4096) sts4u(sb + o, make_uint4(0, 0, 0, 0)); bar_sync(6, 256); }
        if (WG == 1 && w4 == 1) {
            uint32_t v, it = 0;
            do {
                asm volatile("ld.acquire.gpu.global.u32 %0, [%1];" : "=r"(v) : "l"(&g_epoch) : "memory");
                spin_guard(it);
            } while (__any_sync(~0u, (int)(v - goal) < 0));
        }
        if (WG == 1 && w4 == 0) calibrate(sb + C_CAL, 0.f);
        __syncwarp();
        bar_sync(6, 256);
        asm volatile("fence.proxy.async.global;" ::: "memory");
    }

    constexpr uint32_t SLOT = ISV ? C_SLOTV : C_SLOTQ;
    constexpr int WS_A = (SB0 + C_WS + WG * 32768) >> 4, WO_A = (SB0 + C_WO) >> 4, MB_A = (SB0 + C_MB) >> 4;
#define XN_A(ks) (int)(((SB0 + C_XN + WG * 16384) >> 4) + ((ks) >> 2) * 256 + ((ks) & 3) * 2)
    const uint32_t slot = (sb + SLOT + w4 * 512), mbw = sb + C_MB + WG * 8192;
    const uint32_t sb_v = (mapa(sb, 4 + hh));
    const uint32_t sb_x = uni(mapa(sb, 2 * hh + (WG ? 1 : (~w4 & 1))));
    const uint32_t sb_o = (mapa(sb, w4));
    const uint32_t u_off = (ISV ? (head * 128 + w4 * 32) * 16 : (cl * 4 + rank) * 256 + (w4 & 1) * 128);
    const uint32_t v_row = (sb + C_V + (2 * WG + (w4 >> 1)) * 512), v_b = ((w4 & 1) * 64);
    const uint32_t u_flag = (blockIdx.x * FSTR);
    const uint32_t f_half = (w4 & 1) * role * (ONKV * 128), f_sb = uni(mapa(sb, rank + (w4 & 1) * (4 + hh - rank)));
    const uint32_t f_src = uni((ostart + (w4 & 1) * (2 - role) * ONKQ) * 256 + f_half), f_dst = uni(f_sb + C_MB + f_half);
    const uint32_t m_dst = (sb + C_MB + role * 8192), m_bar = (bar + (B_MF0 + role) * 8);
    uint32_t target, missing;
    int s = -1;
    uint32_t pf[4][4];
    float xk[16], xv[16];
    uint4 oxp[4];

    auto send_planes = [&](auto n, uint32_t a, int b, const float* v, bool hold) {
        const uint32_t dump = sb + C_DUMP + (l16 >> 2), to = a + (l16 >> 2), ad = hold ? dump : to;
        const uint32_t mb = hold ? (dump & 0xFF000000u) | (SB0 + C_BAR + B_DUMP * 8) : (to & 0xFF000000u) | (SB0 + C_BAR + b * 8);
#pragma unroll
        for (int i = 0; i < n.value; i++) st_async1f(ad + i * 128, mb, v[i]);
    };
    auto store_ox = [&](int ss) {
        char* orow = reinterpret_cast<char*>(g_ox) + (ss * (32 * HD * 2) + (u_off >> 3) + (l16 >> 6) * (HD * 2) + (l16 & 48));
#pragma unroll
        for (int i = 0; i < 4; i++) st_pred4(orow + i * (8 * HD * 2), oxp[i], ss >= 0);
    };
    auto load_tokens = [&](int seg, int wina, int g) {
        const int khalf = ISV ? 1 - wina : wina;
        if (!NOFILL && elect()) {
            mbar_expect(bar + (B_XF0 + g) * 8, 16384);
            bulk_ld(sb + C_XN + g * 16384, g_xc + (seg * 4 + khalf * 2 + g) * 1024, 16384, bar + (B_XF0 + g) * 8);
        }
        __syncwarp();
    };
    auto prefetch = [&]() {
#pragma unroll
        for (int i = 0; i < 4; i++) ldsm4t(pf[i], a_adr + C_WS + (i & 1) * 16384 + (i >> 1) * 2048);
    };
    constexpr int HA = ISV ? 0 : 1, NK1 = ISV ? 0 : QK1;
    auto products = [&](auto give, auto half, auto init, auto i0, auto i1, const uint64_t d) {
        static_for<i0.value, i1.value>([&](auto i) {
            constexpr int ks = half.value * 16 + i.value, acc = !(init.value && i.value == i0.value);
            if constexpr (ks >= 24) wg32_ss<acc, WS_A + give.value * 1024 + (ks - 24) * 128, XN_A(i.value)>(give.value ? xv : xk, d);
            else if constexpr (give.value) wg32_rs<acc, XN_A(i.value)>(xv, wv[ks], d);
            else wg32_rs<acc, XN_A(i.value)>(xk, wk[ks], d);
        });
    };
    auto stream_a = [&](const uint64_t dk, const uint64_t dv) {
        if (NOFILL) return;
        constexpr int F = (WG == 0 && SSFIRST) ? 8 : 0;
        wg_fence();
        products(ic<0>{}, ic<HA>{}, ic<1>{}, ic<F>{}, ic<F + 8>{}, dk);
        products(ic<1>{}, ic<HA>{}, ic<1>{}, ic<F>{}, ic<F + 8>{}, dv);
        products(ic<1>{}, ic<HA>{}, ic<0>{}, ic<8 - F>{}, ic<16 - F>{}, dv);
        products(ic<0>{}, ic<HA>{}, ic<0>{}, ic<8 - F>{}, ic<16 - F>{}, dk);
        wg_commit();
    };
    auto token_softmax = [&]() {
        const int hi = w4 - 2, lane = l16 >> 4;
        const uint32_t src = sb + C_XSL + hi * 256 + (l16 & 255) + (l16 >> 8) * 2560;
        const int d0 = 16 * role + 8 * hi + (lane >> 2) - 2 * (lane & 3);
        mbar_wait(bar + B_XS * 8, s & 1);
        float e[10];
        float m = -INFINITY;
#pragma unroll
        for (int i = 0; i < 5; i++) {
            __syncwarp();
            float a[4];
            ldsm4f(a, src + i * 512);
            e[2 * i] = (i == 0 || d0 >= 8 * (i - 1)) ? a[0] + a[2] : -INFINITY;
            e[2 * i + 1] = (i == 0 || d0 > 8 * (i - 1)) ? a[1] + a[3] : -INFINITY;
            m = fmaxf(m, fmaxf(e[2 * i], e[2 * i + 1]));
        }
        m = fmaxf(m, __shfl_xor_sync(~0u, m, 1));
        m = fmaxf(m, __shfl_xor_sync(~0u, m, 2));
        m *= -SM_SCALE;
        float l = 0.f;
#pragma unroll
        for (int i = 0; i < 10; i++) { e[i] = ex2(fmaf(e[i], SM_SCALE, m)); l += e[i]; }
        l += __shfl_xor_sync(~0u, l, 1);
        l += __shfl_xor_sync(~0u, l, 2);
        l = rcp(l);
        const uint32_t pd = sb_v + C_PL + (s & 1) * 2048 + role * 768 + hi * 128 + (l16 >> 2), pb = sb_v + C_BAR + (B_P0 + (s & 1)) * 8;
        st_async1(pd, pb, pack2(e[0] * l, e[1] * l));
        st_async1(pd + 256, pb, pack2(e[2] * l, e[3] * l));
        st_async1(pd + 512, pb, pack2(e[4] * l, e[5] * l));
        if (role) {
            st_async1(pd + 768, pb, pack2(e[6] * l, e[7] * l));
            st_async1(pd + 1024, pb, pack2(e[8] * l, e[9] * l));
        }
        if (hi == 0 && l16 == 0) mbar_expect(bar + B_XS * 8, 3072 + role * 2048);
        __syncwarp();
    };

    auto windows = [&](auto first_) {
        constexpr bool FIRST = first_.value;
        asm volatile("" : "+r"(l16), "+r"(w4));
        const uint64_t dd[4] = {FIRST ? DSW : D.sw[0], FIRST ? DSW : D.sw[1], FIRST ? DSW : D.sw[2], FIRST ? DSW : D.sw[3]};
        TS(5);
        if constexpr (WG == 1) {
            TS(6);
            if (ISV && !FIRST) bar_sync(3, 256);
            Stamps st2;
            if (!ISV && !FIRST) load_stamps2(st2, g_flag[0], l16, __any_sync(~0u, missing) && w4 < 2);
            stream_a(dd[0], dd[1]);
            if (!NOFILL) bar_arrive(7, 256);
            if (CNTPOS == 1 && ISV && !FIRST && w4 == 2 && (s & 3) == 1 && s > 1 && l16 == 0) count_up(CNT_OX + (s >> 2) - 1);
            __syncwarp();
            if (ISV && !FIRST && !NOFILL) store_ox(s - 1);
            auto fetch_o = [&]() {
            if (!FIRST && !ISV && w4 < 2) {
                const char* src = reinterpret_cast<const char*>(&g_xo[s & 3][0]) + f_src;
                if (__builtin_expect(__any_sync(~0u, missing), 0)) {
                    uint32_t it = 0;
                    while (__any_sync(~0u, stamps_missing<6>(st2.v, s))) { load_stamps2(st2, g_flag[0], l16); spin_guard(it); }
                    target = latest_stamp<6>(st2.v, lds4u(sb + C_CAL)) + DLY1;
                }
                mbar_wait(bar + B_VF * 8, s & 1);
                TS(10);
                wait_clock(target);
                if (elect()) bulk_ld(f_dst, src, ONKQ * 256 - w4 * (ONKQ * 256 - ONKV * 128), f_sb + C_BAR + B_OF * 8);
                __syncwarp();
                TS(8);
            }
            };
            if (!EARLYB) fetch_o();
            if (!NOFILL) {
                wg_wait<0>();
                reg_fence<16>(xk); reg_fence<16>(xv);
                if (w4 == 3) { bar_sync(2, 128); load_tokens(s + 1, 0, 1); }
                else bar_arrive(2, 128);
            }
            if (EARLYB) fetch_o();
            TS(7);
        } else {
            if (!NOFILL) {
                mbar_wait(bar + B_XF0 * 8, 0);
                bar_sync(7, 256);
            }
            TS(6);
            stream_a(dd[0], dd[1]);
        }
        uint32_t st[6];
        uint4 cal;
        if constexpr (WG == 0) {
            if constexpr (!FIRST) {
                const uint32_t dst = sb_o + C_OL + rank * 512;
                const uint32_t can = sb + C_MB + l16 * 8 + (l16 >> 2), can2 = can + (l16 < (ONK * 2 - 64) * 16 ? 8192 : 0);
                float co[4];
                TS(7);
                uint32_t tries = 0;
                for (;; tries |= 1) {
                    asm volatile("" : "+r"(tries));
                    if (__builtin_expect(tries, 0)) {
                        wg_wait<0>();
                        refetch(sb + C_MB, &g_xo[s & 3][ostart * 16], ONK * 256, bar + B_RT0 * 8, w4, 1, tries);
                    }
                    mbar_wait(bar + B_OF * 8, s & 1);
                    TS(8);
                    wg8_chain<0, 8, WO_A, MB_A>(co, D.sw[0], D.ns);
                    if (__builtin_expect(!__any_sync(~0u, max(max(lds1u(can), lds1u(can + 4096)), lds1u(can2)) == CANARY), 1)) break;
                }
                wg_wait<1>();
                if (l16 == 0) mbar_arrive(bar + B_GO * 8);
                wg8_chain<8, ONK - OTAIL, WO_A, MB_A>(co, D.sw[0], D.ns);
                static_for<ONK - OTAIL, ONK>([&](auto i) { wg8_ss<1, WO_A + i.value * 128, MB_A + i.value * 16>(co, D.sw[0], D.ns); });
                wg_commit();
                wg_wait<1>();
                bar_arrive(5, 256);
                wg_wait<0>();
                reg_fence<4>(co);
                const bool nan = any_nan(co[0], co[1]);
                send_planes(ic<4>{}, dst, B_OL, co, nan);
                if (__builtin_expect(nan, 0)) {
                    while (incomplete<ONK * 256>(sb + C_MB, l16)) {
                        refetch(sb + C_MB, &g_xo[s & 3][ostart * 16], ONK * 256, bar + B_RT0 * 8, w4, 1, tries);
                        co[0] = co[1] = co[2] = co[3] = 0.f;
#pragma unroll 1
                        for (int i = 0; i < ONK; i++) {
                            wg_fence();
                            wg8_ss<1, WO_A, MB_A>(co, DSW + i * 128, DNS + i * 16);
                            wg_commit();
                            wg_wait<0>();
                        }
                        reg_fence<4>(co);
                    }
                    send_planes(ic<4>{}, dst, B_OL, co, false);
                }
                TS(9);
                if (l16 < 48 && w4 == 3) mbar_expect(bar + B_MF0 * 8 + (l16 >> 1), l16 == 32 ? ONK * 256 : 8192);
            } else {
                wg_wait<0>();
                if (l16 == 0) mbar_arrive(bar + B_GO * 8);
                bar_arrive(5, 256);
            }
            if (l16 < 32) mbar_arrive_cluster(mapa(bar + B_MBF * 8, 2 * hh + (l16 >> 4)));
            __syncwarp();
            if (!NOFILL) { reg_fence<16>(xk); reg_fence<16>(xv); }
        } else {
            if (w4 < 2) {
                mbar_wait(bar + B_GO * 8, (s + 1) & 1);
                const uint32_t v = ((gtick() - (ISV ? (ONKQ - ONKV) * 18 / 64 : 0)) << 6) | s, c = clk();
                if (w4 == 0) {
                    if (!FIRST) {
                        if (l16 == 0) st_relaxed1(&g_flag[1][u_flag + (l16 >> 1)], v);
                        if (!ISV) calibrate(sb + C_CAL, 0.75f);
                    }
                } else {
                    if (!FIRST) wait_clock(c + DLYB);
                    load_tokens(s + 1, 0, 0);
                }
                if (!ISV && !FIRST) st_relaxed1(reinterpret_cast<char*>(&g_xmem[(s + 3) & 3][0]) + (u_off + (l16 >> 2)), ~0u);
            } else if (!FIRST && !NOFILL) {
                if (CNTPOS == 0 && ISV && w4 == 2 && (s & 3) == 1 && s > 1 && l16 == 0) count_up(CNT_OX + (s >> 2) - 1);
                if (CNTPOS == 2 && ISV && w4 == 2 && (s & 3) == 1 && s > 1 && l16 == 0) asm volatile("red.relaxed.gpu.global.add.u32 [%0], 1;" :: "l"(&g_cnt[(CNT_OX + (s >> 2) - 1) * 8]) : "memory");
                __syncwarp();
                if (!ISV) token_softmax();
                TSX(9, w4 == 2);
            }
            if (!NOFILL) mbar_wait(bar + B_XF1 * 8, 1);
            if (!ISV && !FIRST) cal = lds4u(sb + C_CAL);
            bar_sync(5, 256);
            if (!ISV && !FIRST) load_stamps1(st, g_flag[1], l16, w4 == 0);
        }
        asm volatile("" : "+r"(l16), "+r"(w4));
        TSX(11, w4 == 0 && (WG || ISV));
        constexpr int NR = SWAP16 ? 2 : 4;
        constexpr uint32_t OUT = SWAP16 ? WG * 4096 : 0, IN = SWAP16 ? (WG ^ 1) * 4096 : 0;
        auto give = [&]() {
#pragma unroll
            for (int j = 0; j < NR; j++) {
                if (SWAP16) stsm4(slot + OUT + l16 + j * 2048, pack2(xv[8 * j], xv[8 * j + 1]), pack2(xv[8 * j + 2], xv[8 * j + 3]),
                                  pack2(xv[8 * j + 4], xv[8 * j + 5]), pack2(xv[8 * j + 6], xv[8 * j + 7]));
                else stsm4f(slot + l16 + j * 2048, xv + 4 * j);
            }
        };
        auto take = [&](uint32_t (*r)[4]) {
#pragma unroll
            for (int j = 0; j < NR; j++) ldsm4(r[j], slot + IN + l16 + j * 2048);
        };
        auto store_tokens = [&](const uint32_t (*r)[4]) {
            uint32_t lo[4], hi[4];
#pragma unroll
            for (int j = 0; j < 4; j++) {
                if (SWAP16) {
                    const uint32_t a = r[j >> 1][(j & 1) * 2], b = r[j >> 1][(j & 1) * 2 + 1];
                    lo[j] = pack2(xk[4 * j] + bf_lo(a), xk[4 * j + 1] + bf_hi(a));
                    hi[j] = pack2(xk[4 * j + 2] + bf_lo(b), xk[4 * j + 3] + bf_hi(b));
                } else {
                    lo[j] = pack2(xk[4 * j] + __uint_as_float(r[j % NR][0]), xk[4 * j + 1] + __uint_as_float(r[j % NR][1]));
                    hi[j] = pack2(xk[4 * j + 2] + __uint_as_float(r[j % NR][2]), xk[4 * j + 3] + __uint_as_float(r[j % NR][3]));
                }
            }
            if (!ISV) {
                const uint32_t d = sb + C_QX + WG * 4096 + w4 * 1024 + l16;
                stsm4t(d, lo[0], lo[1], lo[2], lo[3]);
                stsm4t(d + 512, hi[0], hi[1], hi[2], hi[3]);
            } else {
                const uint32_t d = v_row + ((s + 1) & 1) * 10240 + ((l16 & 384) << 4) + ((l16 & 96) << 2) + ((l16 & 112) ^ v_b);
                stsm4(d, lo[0], lo[1], lo[2], lo[3]);
                stsm4(d ^ 32, hi[0], hi[1], hi[2], hi[3]);
            }
        };
        if constexpr (WG == 1) {
            if (!NOFILL) {
                wg_fence();
                products(ic<1>{}, ic<1 - HA>{}, ic<0>{}, ic<0>{}, ic<16>{}, dd[3]);
                products(ic<0>{}, ic<1 - HA>{}, ic<0>{}, ic<0>{}, ic<NK1>{}, dd[2]);
                wg_commit();
                if (ISV) bar_arrive(7, 256);
                else {
                    if (!FIRST) load_stamps1(st + 3, g_flag[1], l16, w4 == 0);
                    mbar_wait(bar + B_MBF * 8, (s + 1) & 1);
                    bar_sync(7, 256);
                }
                wg_wait<0>();
                reg_fence<16>(xv); reg_fence<16>(xk);
                give();
                bar_arrive(8, 256);
            }
            TS(12);
            if (!ISV && w4 == 0) {
                const uint4* src = &g_xmem[(s + 1) & 3][role * 512];
                if (NOFILL) mbar_wait(bar + B_MBF * 8, (s + 1) & 1);
                if (!FIRST) {
                    if (__builtin_expect(__any_sync(~0u, stamps_missing<3>(st, s)), 0)) {
                        uint32_t it = 0;
                        if (!NOFILL) { st[0] = st[3]; st[1] = st[4]; st[2] = st[5]; }
                        while (__any_sync(~0u, stamps_missing<3>(st, s))) { load_stamps1(st, g_flag[1], l16); spin_guard(it); }
                    }
                    TS(3);
                    wait_clock(latest_stamp<3>(st, cal) + DLY2);
                }
                if (hh) { if (elect()) bulk_mc(m_dst, src, 8192, m_bar, 0x2C); }
                else if (elect()) bulk_mc(m_dst, src, 8192, m_bar, 0x13);
                __syncwarp();
                TS(4);
            }
            prefetch();
            if (!NOFILL) {
                bar_sync(9, 256);
                uint32_t r[NR][4];
                take(r);
                bar_sync(14, 256);
                wg_fence();
                products(ic<0>{}, ic<1 - HA>{}, ic<0>{}, ic<NK1>{}, ic<16>{}, dd[2]);
                wg_commit();
                wg_wait<0>();
                reg_fence<16>(xk);
                TS(13);
                store_tokens(r);
                bar_arrive(10, 256);
                if (w4 != 3) bar_arrive(13, 128);
            }
        } else {
            uint32_t r[NR][4];
            if (!NOFILL) mbar_wait(bar + B_XF0 * 8, 1);
            if (!ISV && !FIRST && w4 < 2) {
                char* gd = reinterpret_cast<char*>(&g_xmem[(s + 1) & 3][0]) + (u_off + (l16 >> 2));
                const uint32_t src = sb + C_OL + w4 * 256 + l16 + (l16 & 256);
                mbar_wait(bar + B_OL * 8, s & 1);
                TSD(3);
                float a[3][4];
#pragma unroll
                for (int i = 0; i < 3; i++) ldsm4f(a[i], src + i * 1024);
                st_relaxed1(gd, movm(pack2((a[0][0] + a[0][2]) + (a[1][0] + a[1][2]) + (a[2][0] + a[2][2]),
                                           (a[0][1] + a[0][3]) + (a[1][1] + a[1][3]) + (a[2][1] + a[2][3]))));
                TS(11);
                if (w4 == 0 && l16 == 0) mbar_expect(bar + B_OL * 8, 3072);
                __syncwarp();
            }
            if (!NOFILL) {
                bar_sync(7, 256);
                TS(12);
                wg_fence();
                products(ic<1>{}, ic<1 - HA>{}, ic<0>{}, ic<0>{}, ic<16>{}, dd[3]);
                wg_commit();
                products(ic<0>{}, ic<1 - HA>{}, ic<0>{}, ic<0>{}, ic<6>{}, dd[2]);
                wg_commit();
                bar_sync(8, 256);
                take(r);
                wg_wait<1>();
                reg_fence<16>(xv);
                give();
                bar_arrive(9, 256);
                products(ic<0>{}, ic<1 - HA>{}, ic<0>{}, ic<6>{}, ic<16>{}, dd[2]);
                wg_commit();
                bar_arrive(14, 256);
                wg_wait<0>();
                reg_fence<16>(xk);
            }
            TS(13);
            if (!NOFILL) store_tokens(r);
            prefetch();
        }
    };

    if (tid == 0) TL(1, 2);
    if (w4 == 0) load_tokens(0, 1, WG);
    mbar_wait(bar + B_WS * 8, 0);
    if (WG == 1 && !NOFILL) mbar_wait(bar + B_XF1 * 8, 0);
    windows(ic<1>{});
    if (tid == 0) TL(1, 3);

#pragma unroll 1
    while (true) {
        s++;
        asm volatile("" : "+r"(l16), "+r"(a_adr), "+r"(w4));
        TS_FLUSH(WG);
        TS(0);
        float ck[4], cv[4], dk[4], dv[4];
        uint32_t b[3][4], tries = 0;
        const uint32_t kl = sb + C_KX + ((l16 & 384) << 2) + (l16 & 112);
        auto load_b = [&](auto kp) { ldsm4(b[kp.value % 3], mbw + l16 + ((kp.value & 3) ? (kp.value >> 2) * 3 + (kp.value & 3) - 1 : 12 + (kp.value >> 2)) * 512); };
        auto kpair = [&](auto kp_) {
            constexpr int kp = kp_.value, grp = kp >> 2, ph = kp & 3;
            if constexpr (kp > 0 && kp < 14) load_b(ic<kp + 2>{});
            const uint32_t* bb = b[kp % 3];
            if constexpr (ph != 0) {
                constexpr int q = (grp * 3 + ph - 1) * 2;
                static_for<(ph == 1 ? 0 : ph), ph + 1>([&](auto i) {
                    if constexpr (grp < 3) ldsm4t(pf[i.value], a_adr + C_WS + (i.value & 1) * 16384 + (grp * 2 + 2 + (i.value >> 1)) * 2048);
                });
                __syncwarp();
                mma16(cv, wv[q][0], wv[q][1], wv[q][2], wv[q][3], bb[0], bb[1]);
                mma16(ck, wk[q][0], wk[q][1], wk[q][2], wk[q][3], bb[0], bb[1]);
                mma16(dv, wv[q + 1][0], wv[q + 1][1], wv[q + 1][2], wv[q + 1][3], bb[2], bb[3]);
                mma16(dk, wk[q + 1][0], wk[q + 1][1], wk[q + 1][2], wk[q + 1][3], bb[2], bb[3]);
            } else {
                if constexpr (kp == 0) {
#pragma unroll
                    for (int i = 0; i < 4; i++) ck[i] = cv[i] = dk[i] = dv[i] = 0.f;
                }
                mma16(ck, pf[0][0], pf[0][1], pf[0][2], pf[0][3], bb[0], bb[1]);
                mma16(cv, pf[1][0], pf[1][1], pf[1][2], pf[1][3], bb[0], bb[1]);
                mma16(dk, pf[2][0], pf[2][1], pf[2][2], pf[2][3], bb[2], bb[3]);
                mma16(dv, pf[3][0], pf[3][1], pf[3][2], pf[3][3], bb[2], bb[3]);
            }
        };
        auto hand_over = [&]() {
#pragma unroll
            for (int i = 0; i < 4; i++) { cv[i] += dv[i]; ck[i] += dk[i]; }
            if (ISV) {
                stsm4f(slot + WG * 2048 + l16, cv);
            } else {
                const float *q = WG ? cv : ck, *k = WG ? ck : cv;
                stsm4t(slot + WG * 2048 + l16, pack2(q[0], q[1]), pack2(q[2], q[3]), pack2(k[0], k[1]), pack2(k[2], k[3]));
            }
        };
        auto repair = [&]() {
            bar_sync(6, 256);
            while (incomplete<8192>(mbw, l16)) {
                refetch(mbw, &g_xmem[s & 3][WG * 512], 8192, bar + (B_RT0 + WG) * 8, w4, 1 + WG, tries);
                prefetch();
                static_for<0, 3>(load_b);
                static_for<0, 16>(kpair);
                hand_over();
            }
            bar_sync(6, 256);
        };
        {
            const uint32_t can = mbw + l16 * 8 + (l16 >> 2);
            uint32_t* const flag = &g_flag[0][u_flag + WG + l16];
            for (;; tries |= 1) {
                asm volatile("" : "+r"(tries));
                if (__builtin_expect(tries, 0)) {
                    refetch(mbw, &g_xmem[s & 3][WG * 512], 8192, bar + (B_RT0 + WG) * 8, w4, 1 + WG, tries);
                }
                mbar_wait(bar + (B_MF0 + WG) * 8, s & 1);
                TS(1);
                static_for<0, 3>(load_b);
                const uint32_t c0 = lds1u(can), c1 = lds1u(can + 4096);
                const uint32_t v = ((gtick() - (ISV ? VLEAD : 0)) << 6) | s;
                kpair(ic<0>{});
                const bool early = __any_sync(~0u, max(c0, c1) == CANARY);
                st_pred1(flag, v, w4 * 512 + l16 == 1536 && !early);
                if (__builtin_expect(!early, 1)) break;
            }
            static_for<1, RFPOS>(kpair);
            if (WG == 0 && !NOFILL) bar_sync(10, 256);
            if (WG == 1 && !NOFILL && w4 == 3) {
                bar_sync(13, 128);
                if (s < NSEG - 1) load_tokens(s + 1, 1, 1);
            }
            static_for<RFPOS, 13>(kpair);
        }
        auto finish_projections = [&]() {
            static_for<13, 16>(kpair);
            hand_over();
            TS(2);
            return bar_sync_any_nan(cv[0], cv[1]);
        };
        if constexpr (!ISV) {
            const uint32_t qa = sb + C_SLOTQ + ((l16 >> 1) & 128) + ((l16 & 128) << 3) + (l16 & 112);
            const uint32_t ma = sb + C_SLOTQ + 256 + l16 + (l16 & 256);
            const uint32_t qx = sb + C_QX + l16 + (l16 & 256);
            auto ldsm_sum = [&](uint32_t* r, uint32_t a) {
                uint32_t t[4];
                ldsm4(r, a); ldsm4(t, a + 2048);
#pragma unroll
                for (int i = 0; i < 4; i++) asm("add.rn.bf16x2 %0, %0, %1;" : "+r"(r[i]) : "r"(t[i]));
            };
            auto tile = [&](float* d, const uint32_t (*q)[4], const uint32_t (*k)[4]) {
                d[0] = d[1] = d[2] = d[3] = 0.f;
#pragma unroll
                for (int i = 0; i < 4; i++) mma16(d, q[i][0], q[i][1], q[i][2], q[i][3], k[i >> 1][(i & 1) * 2], k[i >> 1][(i & 1) * 2 + 1]);
            };
            auto send = [&](int ti, const float* d, bool hold) {
                send_planes(ic<4>{}, sb_x + C_XSL + role * 2560 + ti * 512, B_XS, d, hold);
            };
            if constexpr (WG == 0) {
                auto scores = [&](auto again) {
                    bool nan = false;
                    if (w4 < 2) {
                        uint32_t k0[2][4], k1[2][4], q0[4], q1[4];
                        const uint32_t ka = kl + w4 * 256, dst = sb_v + C_SL + role * 1024 + w4 * 512;
                        ldsm4(k0[0], ka); ldsm4(k0[1], ka + 2048);
                        ldsm4(k1[0], ka + 128); ldsm4(k1[1], ka + 128 + 2048);
                        __syncwarp();
                        if (!again.value) nan = finish_projections();
                        TS(3);
                        ldsm_sum(q0, qa); ldsm_sum(q1, qa + 512);
                        float s0[4] = {0.f, 0.f, 0.f, 0.f}, s1[4] = {0.f, 0.f, 0.f, 0.f}, s2[4] = {0.f, 0.f, 0.f, 0.f}, s3[4] = {0.f, 0.f, 0.f, 0.f};
                        mma16(s0, q0[0], q0[1], q0[2], q0[3], k0[0][0], k0[0][1]);
                        mma16(s1, q0[0], q0[1], q0[2], q0[3], k0[1][0], k0[1][1]);
                        mma16(s2, q0[0], q0[1], q0[2], q0[3], k1[0][0], k1[0][1]);
                        mma16(s3, q0[0], q0[1], q0[2], q0[3], k1[1][0], k1[1][1]);
                        mma16(s0, q1[0], q1[1], q1[2], q1[3], k0[0][2], k0[0][3]);
                        mma16(s1, q1[0], q1[1], q1[2], q1[3], k0[1][2], k0[1][3]);
                        mma16(s2, q1[0], q1[1], q1[2], q1[3], k1[0][2], k1[0][3]);
                        mma16(s3, q1[0], q1[1], q1[2], q1[3], k1[1][2], k1[1][3]);
                        const float out[4] = {s0[0] + s1[2], s0[1] + s1[3], s2[0] + s3[2], s2[1] + s3[3]};
                        send_planes(ic<4>{}, dst, B_SC, out, nan);
                        if (!again.value) bar_arrive(12, 256);
                        TS(4);
                    } else if (w4 == 2) {
                        uint32_t q0[4], q1[4], km[2][4], q[4][4];
                        const uint32_t dst = sb_v + C_SL + 2048 + role * 256;
                        if (!again.value) nan = finish_projections();
                        ldsm_sum(q0, qa); ldsm_sum(km[0], ma); ldsm_sum(km[1], ma + 1024); ldsm_sum(q1, qa + 512);
                        __syncwarp();
#pragma unroll
                        for (int i = 0; i < 4; i++) ldsm4(q[i], qx + 256 + i * 1024);
                        float s0[4] = {0.f, 0.f, 0.f, 0.f}, s1[4] = {0.f, 0.f, 0.f, 0.f}, d0[4];
                        mma16(s0, q0[0], q0[1], q0[2], q0[3], km[0][0], km[0][1]);
                        mma16(s1, q0[0], q0[1], q0[2], q0[3], km[1][0], km[1][1]);
                        mma16(s0, q1[0], q1[1], q1[2], q1[3], km[0][2], km[0][3]);
                        mma16(s1, q1[0], q1[1], q1[2], q1[3], km[1][2], km[1][3]);
                        const float out[2] = {s0[0] + s1[2], s0[1] + s1[3]};
                        send_planes(ic<2>{}, dst, B_SC, out, nan);
                        if (!NOFILL) tile(d0, q, km);
                        if (!again.value) bar_sync(12, 256);
                        if (!NOFILL) send(0, d0, nan);
                    } else {
                        if (!again.value) {
                            nan = finish_projections();
                            if (s < NSEG - 1) load_tokens(s + 1, 1, 0);
                        }
                        uint32_t q[4][4], k0[2][4], k1[2][4], km[2][4];
                        float d0[4], d1[4], d2[4];
                        if (!NOFILL) {
#pragma unroll
                            for (int i = 0; i < 4; i++) ldsm4(q[i], qx + i * 1024);
                            ldsm4(k0[0], kl); ldsm4(k0[1], kl + 2048);
                            ldsm4(k1[0], kl + 128); ldsm4(k1[1], kl + 128 + 2048);
                            tile(d1, q, k0); tile(d2, q, k1);
                            ldsm_sum(km[0], ma); ldsm_sum(km[1], ma + 1024);
                            tile(d0, q, km);
                        }
                        if (!again.value) bar_sync(12, 256);
                        if (!NOFILL) { send(0, d0, nan); send(1, d1, nan); send(2, d2, nan); }
                    }
                    return nan;
                };
                if (__builtin_expect(__any_sync(~0u, scores(ic<0>{})), 0)) { repair(); scores(ic<1>{}); }
                if (__builtin_expect(s == NSEG - 1, 0)) break;
            } else {
                Stamps st1;
                load_stamps2(st1, g_flag[0], l16, w4 < 2);
                const bool nan = finish_projections();
                mbar_wait(bar + B_WS * 8, 0);
                missing = stamps_missing<6>(st1.v, s);
                target = latest_stamp<6>(st1.v, lds4u(sb + C_CAL)) + DLY1;
                if (!NOFILL) {
                    uint32_t q[4][4], k0[2][4];
                    float d1[4];
#pragma unroll
                    for (int i = 0; i < 4; i++) ldsm4(q[i], qx + 256 + i * 1024);
                    ldsm4(k0[0], kl + w4 * 128); ldsm4(k0[1], kl + w4 * 128 + 2048);
                    tile(d1, q, k0);
                    mbar_wait(bar + B_XF1 * 8, s == NSEG - 1);
                    bar_sync(12, 256);
                    send(1 + w4, d1, false);
                } else {
                    bar_sync(12, 256);
                }
                if (__builtin_expect(__any_sync(~0u, nan), 0)) repair();
                if (__builtin_expect(s == NSEG - 1, 0)) {
                    asm volatile("" : "+r"(l16));
                    if (w4 >= 2 && !NOFILL) token_softmax();
                    break;
                }
            }
        } else {
            const uint32_t lane_b = sb + C_V + w4 * 512 + ((l16 & 384) << 4) + (l16 & 112);
            auto load_values = [&](uint32_t (*vx)[4], uint32_t* vm, int ss) {
#pragma unroll
                for (int j = 0; j < 4; j++) ldsm4(vx[j], ((lane_b + (ss & 1) * 10240) ^ (j * 32)) + j * 128);
                ldsm4(vm, sb + C_V + (ss & 1) * 10240 + w4 * 512 + 8192 + (l16 ^ ((l16 >> 2) & 96)));
            };
            auto token_output = [&](int ss, auto mid) {
                uint32_t vx[4][4], vm[4];
                const uint32_t pl = sb + C_PL + (ss & 1) * 2048 + l16;
                auto lds_frag = [&](uint32_t a) { uint32_t r[4]; ldsm4(r, a); return make_uint4(r[0], r[1], r[2], r[3]); };
                load_values(vx, vm, ss);
                mid();
                uint32_t dep = 0;
#pragma unroll
                for (int mh = 1; mh >= 0; mh--) {
                    uint2 pm;
                    asm volatile("ldmatrix.sync.aligned.m8n8.x2.shared.b16 {%0,%1}, [%2];" : "=r"(pm.x), "=r"(pm.y) : "r"(pl + mh * 768 + dep) : "memory");
                    const uint4 p0 = lds_frag(pl + mh * 768 + 256);
                    float o[4][4];
#pragma unroll
                    for (int j = 0; j < 4; j++) { o[j][0] = o[j][1] = o[j][2] = o[j][3] = 0.f; mma8(o[j], pm.x, pm.y, vm[j]); }
#pragma unroll
                    for (int j = 0; j < 4; j++) mma16(o[j], p0.x, p0.y, p0.z, p0.w, vx[j][0], vx[j][1]);
                    if (mh) {
                        const uint4 p1 = lds_frag(pl + 1536);
#pragma unroll
                        for (int j = 0; j < 4; j++) mma16(o[j], p1.x, p1.y, p1.z, p1.w, vx[j][2], vx[j][3]);
                    }
                    oxp[2 * mh] = make_uint4(pack2(o[0][0], o[0][1]), pack2(o[1][0], o[1][1]), pack2(o[2][0], o[2][1]), pack2(o[3][0], o[3][1]));
                    oxp[2 * mh + 1] = make_uint4(pack2(o[0][2], o[0][3]), pack2(o[1][2], o[1][3]), pack2(o[2][2], o[2][3]), pack2(o[3][2], o[3][3]));
                    dep = oxp[2].x == ~0u ? 16 : 0;
                }
            };
            const uint32_t vd = v_row + (s & 1) * 10240 + 8192 + ((l16 & 96) << 2) + ((l16 & 112) ^ v_b ^ ((l16 & 128) >> 2));
            if (__builtin_expect(__any_sync(~0u, finish_projections()), 0)) repair();
            float r[4];
            ldsm4f(r, slot + (WG ^ 1) * 2048 + l16);
            __syncwarp();
            auto finish = [&]() {
                stsm2(vd, pack2(ck[0] + r[0], ck[1] + r[1]), pack2(ck[2] + r[2], ck[3] + r[3]));
                if (WG == 1) {
                    bar_arrive(11, 256);
                    if (w4 == 3 && l16 < 32) mbar_arrive_cluster(mapa(bar + B_VF * 8, 2 * hh + (l16 >> 4)));
                }
                TSX(3, WG == 0 && w4 == 0);
            };
            if (!NOFILL && WG == 1) {
                token_output(s - 1, [&]() { finish(); mbar_wait(bar + (B_P0 + ((s - 1) & 1)) * 8, ((s - 1) >> 1) & 1); });
                if (w4 == 1 && l16 == 0 && s > 0) mbar_expect(bar + (B_P0 + ((s - 1) & 1)) * 8, 2048);
                mbar_wait(bar + B_XF1 * 8, s == NSEG - 1);
            } else {
                finish();
            }
            if (WG == 0) bar_sync(11, 256);
            if (__builtin_expect(s == NSEG - 1, 0)) {
                bar_sync(6, 256);
                if (WG == 1) {
                    if (!NOFILL) {
                        store_ox(s - 1);
                        token_output(s, [&]() { mbar_wait(bar + (B_P0 + (s & 1)) * 8, (s >> 1) & 1); });
                        store_ox(s);
                    }
                    bar_sync(2, 128);
                    if (w4 == 0 && l16 == 0) {
                        if (NOFILL) for (int i = 0; i < 15; i++) count_up(CNT_OX + i);
                        count_up(CNT_OX + 15);
                    }
                    __syncwarp();
                }
                mbar_wait(bar + B_SC * 8, s & 1);
                break;
            }
            if constexpr (WG == 0) {
                uint32_t vx[4][4], vm[4];
                load_values(vx, vm, s);
                const uint32_t oo = u_off + ((l16 & 48) << 3) + ((l16 >> 2) & 112);
                char* dst = reinterpret_cast<char*>(&g_xo[s & 3][0]) + oo;
                if (w4 == 3) load_tokens(s + 1, 1, 0);
                mbar_wait(bar + B_SC * 8, s & 1);
                TS(4);
                float a0[4], b0[4], a1[4], b1[4], a2[4];
                ldsm4f(a0, sb + C_SL + l16); ldsm4f(b0, sb + C_SL + 1024 + l16);
                ldsm4f(a1, sb + C_SL + 512 + l16); ldsm4f(b1, sb + C_SL + 1536 + l16);
                ldsm4f(a2, sb + C_SL + 2048 + l16);
                const float e[10] = {a0[0] + b0[0], a0[1] + b0[1], a0[2] + b0[2], a0[3] + b0[3], a1[0] + b1[0], a1[1] + b1[1], a1[2] + b1[2], a1[3] + b1[3],
                                     a2[0] + a2[2], a2[1] + a2[3]};
                float m = fmaxf(fmaxf(fmaxf(e[0], e[1]), fmaxf(e[2], e[3])), fmaxf(fmaxf(e[4], e[5]), fmaxf(e[6], e[7])));
                m = fmaxf(m, fmaxf(e[8], e[9]));
                m = fmaxf(fmaxf(m, __shfl_xor_sync(~0u, m, 1)), fmaxf(__shfl_xor_sync(~0u, m, 2), __shfl_xor_sync(~0u, m, 3)));
                m *= -SM_SCALE;
                float x[10];
#pragma unroll
                for (int i = 0; i < 10; i++) x[i] = ex2(fmaf(e[i], SM_SCALE, m));
                float o[4][4];
                const uint32_t p0 = pack2(x[0], x[1]), p1 = pack2(x[2], x[3]), j0 = __float_as_uint(x[1]), j1 = __float_as_uint(x[3]);
#pragma unroll
                for (int j = 0; j < 4; j++) { o[j][0] = o[j][1] = o[j][2] = o[j][3] = 0.f; mma16(o[j], p0, j0, p1, j1, vx[j][0], vx[j][1]); }
                const uint32_t p2 = pack2(x[4], x[5]), p3 = pack2(x[6], x[7]), j2 = __float_as_uint(x[5]), j3 = __float_as_uint(x[7]);
#pragma unroll
                for (int j = 0; j < 4; j++) mma16(o[j], p2, j2, p3, j3, vx[j][2], vx[j][3]);
                const uint32_t p4 = pack2(x[8], x[9]), j4 = __float_as_uint(x[9]);
                float l = (((x[0] + x[1]) + (x[2] + x[3])) + ((x[4] + x[5]) + (x[6] + x[7]))) + (x[8] + x[9]);
                l = (l + __shfl_xor_sync(~0u, l, 1)) + (__shfl_xor_sync(~0u, l, 2) + __shfl_xor_sync(~0u, l, 3));
#pragma unroll
                for (int j = 0; j < 4; j++) mma8(o[j], p4, j4, vm[j]);
                l = rcp(l);
                st_relaxed4(reinterpret_cast<uint4*>(dst), make_uint4(pack2(o[0][0] * l, o[0][1] * l), pack2(o[1][0] * l, o[1][1] * l),
                                                                      pack2(o[2][0] * l, o[2][1] * l), pack2(o[3][0] * l, o[3][1] * l)));
                bar_arrive(3, 256);
                st_relaxed4(reinterpret_cast<uint4*>(reinterpret_cast<char*>(&g_xo[(s + 2) & 3][0]) + oo), make_uint4(~0u, ~0u, ~0u, ~0u));
                if (w4 == 0 && l16 == 0) mbar_expect(bar + B_SC * 8, 2560);
            }
        }
        windows(ic<0>{});
    }
}

__global__ void __cluster_dims__(6, 1, 1) __launch_bounds__(256, 1)
chain_kernel(const __grid_constant__ CUtensorMap tq, const __grid_constant__ CUtensorMap tk, const __grid_constant__ CUtensorMap tv,
             const __grid_constant__ CUtensorMap two, const __grid_constant__ Descs D, const __grid_constant__ Descs DV,
             const __nv_bfloat16* __restrict__ x, const __nv_bfloat16* __restrict__ mem0) {
    extern __shared__ __align__(1024) uint8_t smem[];
    const uint32_t sb = smem_u32(smem);
    const int rank = blockIdx.x % 6, cl = blockIdx.x / 6, role = rank >= 4 ? 2 : rank & 1;
    const int tid = threadIdx.x, lane = tid & 31, gw = blockIdx.x * 8 + uni(tid >> 5);
    const CUtensorMap *tA = role == 2 ? &tv : &tq, *tB = role == 2 ? &tv : &tk;
    uint4 cur[4], nxt[4];
#pragma unroll
    for (int j = 0; j < 4; j++) {
        cur[j] = reinterpret_cast<const uint4*>(x)[gw * 128 + j * 32 + lane];
        nxt[j] = reinterpret_cast<const uint4*>(x)[(gw + 768) * 128 + j * 32 + lane];
    }
    if (gw < 512 && lane < 16) asm volatile("prefetch.global.L2 [%0];" :: "l"(x + (gw + 1536) * DM + lane * 64));
    if (threadIdx.x == 0) {
        TL(1, 0); TLSM(1);
        if ((sb & 0xFFFFFF) != SB0 || mapa(sb, 5) != (SB0 | 0x5000000u)) __trap();
        const uint32_t bar = sb + C_BAR;
        for (int i = 0; i < B_NUM; i++) mbar_init(bar + i * 8, i == B_MBF ? 12 : (i == B_GO ? 4 : 1));
        mbar_expect(bar + B_MF0 * 8, 8192);
        mbar_expect(bar + B_MF1 * 8, 8192);
        if (role == 2) {
            mbar_expect(bar + B_SC * 8, 2560);
            mbar_expect(bar + B_P0 * 8, 2048);
            mbar_expect(bar + B_P1 * 8, 2048);
            mbar_expect(bar + B_OF * 8, ONKV * (256 + 2048));
        } else {
            mbar_expect(bar + B_XS * 8, role ? 5120 : 3072);
            mbar_expect(bar + B_OL * 8, 3072);
            mbar_expect(bar + B_OF * 8, ONKQ * (256 + 2048));
        }
        asm volatile("fence.mbarrier_init.release.cluster;" ::: "memory");
        fence_async();
        for (int j = 0; j < 3; j++) load_chunk(tA, tB, cl, rank, sb + j * 65536, j, bar + (B_W0 + j) * 8);
    }
    __syncwarp();
    asm volatile("barrier.cluster.arrive.release.aligned;" ::: "memory");
    reset_exchange(mem0);
#pragma unroll 1
    for (int row = gw; row < SEQ; row += 768) {
        uint4 v[4];
#pragma unroll
        for (int j = 0; j < 4; j++) {
            v[j] = cur[j]; cur[j] = nxt[j];
            if (row + 1536 < SEQ) nxt[j] = reinterpret_cast<const uint4*>(x)[(row + 1536) * 128 + j * 32 + lane];
        }
        ln_row(v, row, lane);
    }
    if (tid == 0) TL(1, 5);
    __syncthreads();
    uint32_t goal = 0;
    if (tid == 160) {
        __threadfence();
        goal = (atomicAdd(&g_epoch, 1u) / 96 + 1) * 96;
        asm volatile("griddepcontrol.launch_dependents;" ::: "memory");
        TL(1, 4);
    }
    __syncwarp();
    asm volatile("barrier.cluster.wait.acquire.aligned;" ::: "memory");
    goal = uni(goal);
    const int wg = uni(threadIdx.x >> 7);
    if (role == 2) {
        if (wg == 0) chain_main<true, 0>(&tv, &tv, &two, sb, cl, rank, DV, goal);
        else chain_main<true, 1>(&tv, &tv, &two, sb, cl, rank, DV, goal);
    } else {
        if (wg == 0) chain_main<false, 0>(&tq, &tk, &two, sb, cl, rank, D, goal);
        else chain_main<false, 1>(&tq, &tk, &two, sb, cl, rank, D, goal);
    }
    __syncwarp();
    cluster_sync();
    if (threadIdx.x == 0) TL(1, 1);
}

__device__ __forceinline__ void wg256(float* d, uint32_t da, uint32_t db, uint32_t accum) {
    asm volatile("{\n.reg .b64 da, db;\n.reg .pred p;\nsetp.ne.u32 p, %130, 0;\nmov.b64 da, {%128, " DESC_HI_SW128 "};\nmov.b64 db, {%129, " DESC_HI_SW128 "};\n"
                 "wgmma.mma_async.sync.aligned.m64n256k16.f32.bf16.bf16 {"
                 "%0,%1,%2,%3,%4,%5,%6,%7,%8,%9,%10,%11,%12,%13,%14,%15,%16,%17,%18,%19,%20,%21,%22,%23,%24,%25,%26,%27,%28,%29,%30,%31,"
                 "%32,%33,%34,%35,%36,%37,%38,%39,%40,%41,%42,%43,%44,%45,%46,%47,%48,%49,%50,%51,%52,%53,%54,%55,%56,%57,%58,%59,%60,%61,%62,%63,"
                 "%64,%65,%66,%67,%68,%69,%70,%71,%72,%73,%74,%75,%76,%77,%78,%79,%80,%81,%82,%83,%84,%85,%86,%87,%88,%89,%90,%91,%92,%93,%94,%95,"
                 "%96,%97,%98,%99,%100,%101,%102,%103,%104,%105,%106,%107,%108,%109,%110,%111,%112,%113,%114,%115,%116,%117,%118,%119,%120,%121,%122,%123,%124,%125,%126,%127"
                 "}, da, db, p, 1, 1, 0, 1;\n}"
                 : ACC16(d), ACC16((d + 16)), ACC16((d + 32)), ACC16((d + 48)), ACC16((d + 64)), ACC16((d + 80)), ACC16((d + 96)), ACC16((d + 112))
                 : "r"(da), "r"(db), "r"(accum));
}
__device__ __forceinline__ void wg128(float* d, uint32_t da, uint32_t db, uint32_t accum) {
    asm volatile("{\n.reg .b64 da, db;\n.reg .pred p;\nsetp.ne.u32 p, %66, 0;\nmov.b64 da, {%64, " DESC_HI_SW128 "};\nmov.b64 db, {%65, " DESC_HI_SW128 "};\n"
                 "wgmma.mma_async.sync.aligned.m64n128k16.f32.bf16.bf16 {"
                 "%0,%1,%2,%3,%4,%5,%6,%7,%8,%9,%10,%11,%12,%13,%14,%15,%16,%17,%18,%19,%20,%21,%22,%23,%24,%25,%26,%27,%28,%29,%30,%31,"
                 "%32,%33,%34,%35,%36,%37,%38,%39,%40,%41,%42,%43,%44,%45,%46,%47,%48,%49,%50,%51,%52,%53,%54,%55,%56,%57,%58,%59,%60,%61,%62,%63"
                 "}, da, db, p, 1, 1, 0, 1;\n}"
                 : ACC16(d), ACC16((d + 16)), ACC16((d + 32)), ACC16((d + 48))
                 : "r"(da), "r"(db), "r"(accum));
}
__device__ __forceinline__ float sigmoidf_(float v) { return rcp(1.f + ex2(-1.4426950408889634f * v)); }
__device__ __forceinline__ void wait_count(int idx, uint32_t n) {
    uint32_t v, it = 0;
    while (true) {
        asm volatile("ld.acquire.gpu.global.u32 %0, [%1];" : "=r"(v) : "l"(&g_cnt[idx * 8]) : "memory");
        if (v >= n) break;
        __nanosleep(100);
        spin_guard(it);
    }
    asm volatile("fence.proxy.async.global;" ::: "memory");
}

constexpr int G_STAGES = 4, G_PAIRS = 18;
constexpr uint32_t G_STAGE = 49152, G_EPI = G_STAGES * G_STAGE, G_BAR = G_EPI + 32768, G_SMEM = G_BAR + 256;
__device__ __forceinline__ int glu_job(int p, int j) {
    if (j < 12) return j * G_PAIRS + p;
    if (p < 14) return j == 12 ? 224 + p : (j == 13 ? 242 + p : -1);
    return j < 14 ? 216 + (j - 12) * 4 + (p - 14) : (j == 14 ? 224 + p : -1);
}

__global__ void __cluster_dims__(2, 1, 1) __launch_bounds__(384, 1)
glu_kernel(const __grid_constant__ CUtensorMap tXn, const __grid_constant__ CUtensorMap tG, const __grid_constant__ CUtensorMap tU,
           const __grid_constant__ CUtensorMap tHst, const __grid_constant__ CUtensorMap tHld, const __grid_constant__ CUtensorMap tD,
           const __grid_constant__ CUtensorMap tYst) {
    extern __shared__ __align__(1024) uint8_t smem[];
    const uint32_t sb = smem_u32(smem);
    const uint32_t full = sb + G_BAR, empty = full + 64;
    const int tid = threadIdx.x, lane = tid & 31;
    const int warp = uni(tid >> 5), wg = warp >> 2;
    const int rank = blockIdx.x & 1, pair = blockIdx.x >> 1;
    asm volatile("griddepcontrol.launch_dependents;" ::: "memory");
    if (tid == 0) {
        TL(2, 0); TLSM(2);
        for (int i = 0; i < G_STAGES; i++) { mbar_init(full + i * 8, 1); mbar_init(empty + i * 8, 16); }
        asm volatile("fence.mbarrier_init.release.cluster;" ::: "memory");
        fence_async();
    }
    __syncthreads();
    cluster_sync();
    if (wg == 0) {
        asm volatile("setmaxnreg.dec.sync.aligned.u32 40;");
        if (warp == 0) {
            if (lane == 0) {
                uint32_t st = 0, ph = 1;
                asm volatile("fence.acq_rel.gpu;\nfence.proxy.async.global;" ::: "memory");
                for (int j = 0, job; (job = glu_job(pair, j)) >= 0; j++) {
                    const bool dn = job >= 224;
                    const int mp = dn ? (job - 224) >> 2 : job / 28, nt = dn ? job & 3 : job % 28, rb = mp * 2 + rank;
                    const CUtensorMap* tA = dn ? &tHld : &tXn;
                    const CUtensorMap* tB = dn ? &tD : (rank ? &tU : &tG);
                    const int bcol = dn ? nt * 256 + rank * 128 : nt * 128, nkb = dn ? FF / 64 : DM / 64;
                    if (j == 12) TL(2, 2);
                    if (dn) wait_count(CNT_H + rb, 56);
                    for (int kb = 0; kb < nkb; kb++) {
                        mbar_wait(empty + st * 8, ph);
                        const uint32_t base = sb + st * G_STAGE;
                        mbar_expect(full + st * 8, G_STAGE);
                        tma2d(base, tA, kb * 64, rb * 128, full + st * 8);
                        tma2d_mc(base + 16384 + rank * 16384, tB, bcol, kb * 64, full + st * 8, 3);
                        tma2d_mc(base + 16384 + rank * 16384 + 8192, tB, bcol + 64, kb * 64, full + st * 8, 3);
                        if (++st == G_STAGES) { st = 0; ph ^= 1; }
                    }
                }
            }
        } else if (warp < 3) {
            const int cw = warp - 1;
            const uint32_t epi = sb + G_EPI + cw * 16384;
            bar_arrive(3 + cw, 160);
            for (int j = 0, job; (job = glu_job(pair, j)) >= 0; j++) {
                const bool dn = job >= 224;
                const int mp = dn ? (job - 224) >> 2 : job / 28, nt = dn ? job & 3 : job % 28, rb = mp * 2 + rank;
                for (int hp = 0; hp <= (int)dn; hp++) {
                    bar_sync(1 + cw, 160);
                    if (lane == 0) {
                        const int col = dn ? nt * 256 + hp * 128 : nt * 128;
                        tma2d_store(dn ? &tYst : &tHst, col, rb * 128 + cw * 64, epi);
                        tma2d_store(dn ? &tYst : &tHst, col + 64, rb * 128 + cw * 64, epi + 8192);
                        asm volatile("cp.async.bulk.commit_group;\ncp.async.bulk.wait_group.read 0;" ::: "memory");
                    }
                    __syncwarp();
                    bar_arrive(3 + cw, 160);
                    if (lane == 0) {
                        asm volatile("cp.async.bulk.wait_group 0;\nfence.proxy.async.global;" ::: "memory");
                        count_up(dn ? CNT_Y + rb * 8 + nt * 2 + hp : CNT_H + rb);
                    }
                    __syncwarp();
                }
            }
        }
        cluster_sync();
    } else {
        asm volatile("setmaxnreg.inc.sync.aligned.u32 232;");
        const int cw = wg - 1, w4 = warp & 3;
        const uint32_t empty_dst = mapa(empty, lane & 1);
        const int er = w4 * 16 + (lane & 15), ec = lane >> 4;
        const uint32_t epi = sb + G_EPI + cw * 16384 + er * 128;
        uint32_t st = 0, ph = 0;
        float acc[128];
        auto put = [&](const uint32_t* o) {
            bar_sync(3 + cw, 160);
#pragma unroll
            for (int q = 0; q < 8; q++) stsm4(epi + (q >> 2) * 8192 + (((2 * (q & 3) + ec) ^ (er & 7)) << 4), o[q * 4], o[q * 4 + 1], o[q * 4 + 2], o[q * 4 + 3]);
            fence_async();
            bar_arrive(1 + cw, 160);
        };
        for (int j = 0, job; (job = glu_job(pair, j)) >= 0; j++) {
            const bool dn = job >= 224;
            const int nkb = dn ? FF / 64 : DM / 64;
            uint32_t prev = 0;
#pragma unroll 1
            for (int kb = 0; kb < nkb; kb++) {
                mbar_wait(full + st * 8, ph);
                const uint32_t base = sb + st * G_STAGE;
                const uint32_t da = (((base + cw * 8192) & 0x3FFFF) >> 4) | (1u << 16);
                const uint32_t db = (((base + 16384) & 0x3FFFF) >> 4) | (512u << 16);
                wg_fence();
#pragma unroll
                for (int k = 0; k < 4; k++) wg256(acc, da + k * 2, db + k * 128, (kb | k) != 0);
                wg_commit();
                if (kb > 0) {
                    wg_wait<1>();
                    if (lane < 2) mbar_arrive_cluster(empty_dst + prev * 8);
                }
                prev = st;
                if (++st == G_STAGES) { st = 0; ph ^= 1; }
            }
            wg_wait<0>();
            reg_fence<128>(acc);
            if (lane < 2) mbar_arrive_cluster(empty_dst + prev * 8);
            uint32_t o[32];
            if (!dn) {
#pragma unroll
                for (int i = 0; i < 32; i++) o[i] = pack2(sigmoidf_(acc[2 * i]) * acc[64 + 2 * i], sigmoidf_(acc[2 * i + 1]) * acc[65 + 2 * i]);
                put(o);
            } else {
#pragma unroll
                for (int hp = 0; hp < 2; hp++) {
#pragma unroll
                    for (int i = 0; i < 32; i++) {
                        const float a = acc[hp * 64 + 2 * i], b = acc[hp * 64 + 2 * i + 1];
                        o[i] = pack2(sigmoidf_(a) * a, sigmoidf_(b) * b);
                    }
                    put(o);
                }
            }
        }
        bar_sync(3 + cw, 160);
        if (tid == 128) TL(2, 1);
        cluster_sync();
    }
}

constexpr int O_STAGES = 7;
constexpr uint32_t O_STAGE = 32768, O_BAR = O_STAGES * O_STAGE, O_SMEM = O_BAR + 256;

__global__ void __cluster_dims__(2, 1, 1) __launch_bounds__(384, 1)
out_kernel(const __grid_constant__ CUtensorMap tOx, const __grid_constant__ CUtensorMap tWo, const __grid_constant__ CUtensorMap tX,
           const __grid_constant__ CUtensorMap tY, const __grid_constant__ CUtensorMap tOut) {
    extern __shared__ __align__(1024) uint8_t smem[];
    const uint32_t sb = smem_u32(smem);
    const uint32_t full = sb + O_BAR, empty = full + 64;
    const int tid = threadIdx.x, lane = tid & 31;
    const int warp = uni(tid >> 5), wg = warp >> 2;
    const int rank = blockIdx.x & 1, nt = (blockIdx.x >> 1) & 7, rb = (blockIdx.x >> 4) * 2 + rank;
    constexpr int NKB = HD / 64;
    if (tid == 0) {
        TL(3, 0); TLSM(3);
        for (int i = 0; i < O_STAGES; i++) { mbar_init(full + i * 8, 1); mbar_init(empty + i * 8, 16); }
        asm volatile("fence.mbarrier_init.release.cluster;" ::: "memory");
        fence_async();
    }
    __syncthreads();
    cluster_sync();
    if (wg == 0) {
        if (tid == 0) {
            uint32_t st = 0, ph = 1;
            for (int kb = 0; kb < O_STAGES; kb++) {
                mbar_expect(full + kb * 8, O_STAGE);
                tma2d_mc(sb + kb * O_STAGE + 16384 + rank * 8192, &tWo, nt * 128 + rank * 64, kb * 64, full + kb * 8, 3);
            }
            wait_count(CNT_OX + rb, 32);
            TL(3, 2);
            for (int kb = 0; kb < NKB + 2; kb++) {
                const uint32_t base = sb + st * O_STAGE;
                if (kb >= O_STAGES) {
                    mbar_wait(empty + st * 8, ph);
                    mbar_expect(full + st * 8, O_STAGE);
                }
                if (kb < NKB) {
                    tma2d(base, &tOx, kb * 64, rb * 128, full + st * 8);
                    if (kb >= O_STAGES) tma2d_mc(base + 16384 + rank * 8192, &tWo, nt * 128 + rank * 64, kb * 64, full + st * 8, 3);
                } else {
                    if (kb == NKB) wait_count(CNT_Y + rb * 8 + nt, 2);
                    tma2d(base, &tX, nt * 128 + (kb - NKB) * 64, rb * 128, full + st * 8);
                    tma2d(base + 16384, &tY, nt * 128 + (kb - NKB) * 64, rb * 128, full + st * 8);
                }
                if (++st == O_STAGES) { st = 0; ph ^= 1; }
            }
        }
        __syncwarp();
    } else {
        const int cw = wg - 1, w4 = warp & 3;
        const uint32_t empty_dst = mapa(empty, lane & 1);
        const int er = cw * 64 + w4 * 16 + (lane & 15), ec = lane >> 4;
        uint32_t st = 0, ph = 0, prev = 0;
        float acc[64];
#pragma unroll 1
        for (int kb = 0; kb < NKB; kb++) {
            mbar_wait(full + st * 8, ph);
            const uint32_t base = sb + st * O_STAGE;
            const uint32_t da = (((base + cw * 8192) & 0x3FFFF) >> 4) | (1u << 16);
            const uint32_t db = (((base + 16384) & 0x3FFFF) >> 4) | (512u << 16);
            wg_fence();
#pragma unroll
            for (int k = 0; k < 4; k++) wg128(acc, da + k * 2, db + k * 128, (kb | k) != 0);
            wg_commit();
            if (kb > 0) {
                wg_wait<1>();
                if (lane < 2) mbar_arrive_cluster(empty_dst + prev * 8);
            }
            prev = st;
            if (++st == O_STAGES) { st = 0; ph ^= 1; }
        }
        wg_wait<0>();
        reg_fence<64>(acc);
#pragma unroll
        for (int bx = 0; bx < 2; bx++) {
            mbar_wait(full + st * 8, ph);
            const uint32_t base = sb + st * O_STAGE;
#pragma unroll
            for (int j = 0; j < 4; j++) {
                uint32_t xv[4], yv[4];
                const uint32_t ad = base + er * 128 + (((2 * j + ec) ^ (er & 7)) << 4);
                ldsm4(xv, ad); ldsm4(yv, ad + 16384);
                const float* a = acc + bx * 32 + j * 8;
#pragma unroll
                for (int i = 0; i < 4; i++)
                    xv[i] = pack2(fmaf(a[2 * i], bf_lo(yv[i]), bf_lo(xv[i])), fmaf(a[2 * i + 1], bf_hi(yv[i]), bf_hi(xv[i])));
                stsm4(ad, xv[0], xv[1], xv[2], xv[3]);
            }
            fence_async();
            bar_sync(1 + cw, 128);
            if ((tid & 127) == 0) {
                tma2d_store(&tOut, nt * 128 + bx * 64, rb * 128 + cw * 64, base + cw * 8192);
                asm volatile("cp.async.bulk.commit_group;" ::: "memory");
            }
            if (++st == O_STAGES) { st = 0; ph ^= 1; }
        }
        if ((tid & 127) == 0) asm volatile("cp.async.bulk.wait_group 0;" ::: "memory");
        if (tid == 128) TL(3, 1);
        __syncwarp();
    }
    cluster_sync();
}

typedef CUresult (*EncodeFn)(CUtensorMap*, CUtensorMapDataType, cuuint32_t, void*, const cuuint64_t*, const cuuint64_t*, const cuuint32_t*,
                             const cuuint32_t*, CUtensorMapInterleave, CUtensorMapSwizzle, CUtensorMapL2promotion, CUtensorMapFloatOOBfill);

CUtensorMap make_map(EncodeFn enc, const void* p, int rows, int cols, int box_rows) {
    CUtensorMap m;
    cuuint64_t dims[2] = {(cuuint64_t)cols, (cuuint64_t)rows}, strides[1] = {(cuuint64_t)cols * 2};
    cuuint32_t box[2] = {64, (cuuint32_t)box_rows}, es[2] = {1, 1};
    enc(&m, CU_TENSOR_MAP_DATA_TYPE_BFLOAT16, 2, const_cast<void*>(p), dims, strides, box, es, CU_TENSOR_MAP_INTERLEAVE_NONE,
        CU_TENSOR_MAP_SWIZZLE_128B, CU_TENSOR_MAP_L2_PROMOTION_L2_128B, CU_TENSOR_MAP_FLOAT_OOB_FILL_NONE);
    return m;
}

}

#define PDL 7
extern "C" void kernel_launch(void* const* d_in, const int* in_sizes, int n_in, void* d_out, int out_size) {
    const __nv_bfloat16* x = (const __nv_bfloat16*)d_in[0];
    const __nv_bfloat16* mem0 = (const __nv_bfloat16*)d_in[1];
    void* fn = nullptr;
    cudaDriverEntryPointQueryResult qr;
    cudaGetDriverEntryPoint("cuTensorMapEncodeTiled", &fn, cudaEnableDefault, &qr);
    EncodeFn enc = (EncodeFn)fn;
    void *xn, *ox, *h, *y;
    cudaGetSymbolAddress(&xn, g_xn); cudaGetSymbolAddress(&ox, g_ox); cudaGetSymbolAddress(&h, g_h); cudaGetSymbolAddress(&y, g_y);

    const CUtensorMap tq = make_map(enc, d_in[2], DM, HD, 128), tk = make_map(enc, d_in[3], DM, HD, 128), tv = make_map(enc, d_in[4], DM, HD, 128);
    const CUtensorMap two16 = make_map(enc, d_in[5], HD, DM, 16);
    const CUtensorMap txn128 = make_map(enc, xn, SEQ, DM, 128), tg = make_map(enc, d_in[8], DM, FF, 64), tu = make_map(enc, d_in[9], DM, FF, 64);
    const CUtensorMap th64 = make_map(enc, h, SEQ, FF, 64), th128 = make_map(enc, h, SEQ, FF, 128), td = make_map(enc, d_in[10], FF, DM, 64);
    const CUtensorMap ty64 = make_map(enc, y, SEQ, DM, 64), ty128 = make_map(enc, y, SEQ, DM, 128), tx128 = make_map(enc, x, SEQ, DM, 128);
    const CUtensorMap tox = make_map(enc, ox, SEQ, HD, 128), two64 = make_map(enc, d_in[5], HD, DM, 64), tout = make_map(enc, d_out, SEQ, DM, 64);

    cudaFuncSetAttribute(chain_kernel, cudaFuncAttributeMaxDynamicSharedMemorySize, C_SMEM);
    cudaFuncSetAttribute(glu_kernel, cudaFuncAttributeMaxDynamicSharedMemorySize, G_SMEM);
    cudaFuncSetAttribute(out_kernel, cudaFuncAttributeMaxDynamicSharedMemorySize, O_SMEM);

    Descs D;
    for (int i = 0; i < 4; i++) D.sw[i] = DSW;
    D.ns = DNS;
    cudaStream_t st = cudaStreamPerThread;
    cudaLaunchAttribute at;
    at.id = cudaLaunchAttributeProgrammaticStreamSerialization;
    at.val.programmaticStreamSerializationAllowed = 1;
    cudaLaunchConfig_t cfg = {};
    cfg.stream = st; cfg.attrs = &at; cfg.numAttrs = 0;
    cfg.gridDim = dim3(96); cfg.blockDim = dim3(256); cfg.dynamicSmemBytes = C_SMEM;
    cudaLaunchKernelEx(&cfg, chain_kernel, tq, tk, tv, two16, D, D, x, mem0);
    cfg.gridDim = dim3(2 * G_PAIRS); cfg.blockDim = dim3(384); cfg.dynamicSmemBytes = G_SMEM; cfg.numAttrs = (PDL >> 1) & 1;
    cudaLaunchKernelEx(&cfg, glu_kernel, txn128, tg, tu, th64, th128, td, ty64);
    cfg.gridDim = dim3(128); cfg.dynamicSmemBytes = O_SMEM; cfg.numAttrs = (PDL >> 2) & 1;
    cudaLaunchKernelEx(&cfg, out_kernel, tox, two64, tx128, ty128, tout);
}
```

```cpp
#include <cuda_runtime.h>
#include <cuda_bf16.h>
#include <cuda.h>
#include <stdint.h>
#include <type_traits>

namespace {

constexpr int SEQ = 2048, DM = 1024, HD = 4096, FF = 3584, NSEG = 64;

__device__ __align__(1024) __nv_bfloat16 g_xn[SEQ * DM];
__device__ __align__(1024) uint4 g_xc[SEQ * DM / 8];
__device__ __align__(1024) __nv_bfloat16 g_ox[SEQ * HD];
__device__ __align__(1024) __nv_bfloat16 g_h[SEQ * FF];
__device__ __align__(1024) __nv_bfloat16 g_y[SEQ * DM];
__device__ __align__(1024) uint4 g_xmem[4][1024];
__device__ __align__(1024) uint4 g_xo[4][4096];
#define FSTR 8
__device__ __align__(1024) uint32_t g_flag[2][96 * FSTR];
enum { CNT_H = 0, CNT_OX = 16, CNT_Y = 32, CNT_NUM = 160 };
__device__ __align__(1024) uint32_t g_cnt[CNT_NUM * 8];
__device__ __align__(128) uint32_t g_epoch;
#define TL(k, i)
#define TLSM(k)

__device__ __forceinline__ uint32_t smem_u32(const void* p) { return (uint32_t)__cvta_generic_to_shared(p); }
__device__ __forceinline__ uint32_t mapa(uint32_t a, uint32_t r) {
    uint32_t o; asm("mapa.shared::cluster.u32 %0, %1, %2;" : "=r"(o) : "r"(a), "r"(r)); return o;
}
__device__ __forceinline__ void mbar_init(uint32_t a, uint32_t cnt) {
    asm volatile("mbarrier.init.shared.b64 [%0], %1;" :: "r"(a), "r"(cnt) : "memory");
}
__device__ __forceinline__ void mbar_expect(uint32_t a, uint32_t bytes) {
    asm volatile("mbarrier.arrive.expect_tx.shared.b64 _, [%0], %1;" :: "r"(a), "r"(bytes) : "memory");
}
__device__ __forceinline__ void mbar_arrive_cluster(uint32_t a) {
    asm volatile("mbarrier.arrive.shared::cluster.b64 _, [%0];" :: "r"(a) : "memory");
}
__device__ __forceinline__ void spin_guard(uint32_t& it) {
    asm volatile("{\n.reg .pred p;\nadd.u32 %0, %0, 1;\nsetp.gt.u32 p, %0, 0x400000;\n@p st.shared.u32 [%0], %0;\n}" : "+r"(it));
}
__device__ __forceinline__ void mbar_wait(uint32_t a, uint32_t par) {
    asm volatile("{\n.reg .pred p;\n.reg .u32 i;\nmov.u32 i, 0;\n"
                 "WL:\nadd.u32 i, i, 1;\nsetp.gt.u32 p, i, 0x400000;\n@p st.shared.u32 [i], i;\n"
                 "mbarrier.try_wait.parity.shared::cta.b64 p, [%0], %1;\n@!p bra WL;\n}" :: "r"(a), "r"(par) : "memory");
}
__device__ __forceinline__ void mbar_arrive(uint32_t a) { asm volatile("mbarrier.arrive.shared.b64 _, [%0];" :: "r"(a) : "memory"); }
__device__ __forceinline__ void tma2d(uint32_t dst, const CUtensorMap* m, int c0, int c1, uint32_t bar) {
    asm volatile("cp.async.bulk.tensor.2d.shared::cluster.global.mbarrier::complete_tx::bytes [%0], [%1, {%3, %4}], [%2];"
                 :: "r"(dst), "l"(m), "r"(bar), "r"(c0), "r"(c1) : "memory");
}
__device__ __forceinline__ void tma2d_mc(uint32_t dst, const CUtensorMap* m, int c0, int c1, uint32_t bar, uint16_t mask) {
    asm volatile("cp.async.bulk.tensor.2d.shared::cluster.global.mbarrier::complete_tx::bytes.multicast::cluster [%0], [%1, {%3, %4}], [%2], %5;"
                 :: "r"(dst), "l"(m), "r"(bar), "r"(c0), "r"(c1), "h"(mask) : "memory");
}
__device__ __forceinline__ void bulk_mc(uint32_t dst, const void* src, uint32_t bytes, uint32_t bar, uint16_t mask) {
    asm volatile("cp.async.bulk.shared::cluster.global.mbarrier::complete_tx::bytes.multicast::cluster [%0], [%1], %2, [%3], %4;"
                 :: "r"(dst), "l"(src), "r"(bytes), "r"(bar), "h"(mask) : "memory");
}
__device__ __forceinline__ void bulk_ld(uint32_t dst, const void* src, uint32_t bytes, uint32_t bar) {
    asm volatile("cp.async.bulk.shared::cluster.global.mbarrier::complete_tx::bytes [%0], [%1], %2, [%3];"
                 :: "r"(dst), "l"(src), "r"(bytes), "r"(bar) : "memory");
}
__device__ __forceinline__ uint32_t gtick() { uint64_t c; asm volatile("mov.u64 %0, %%globaltimer;" : "=l"(c)); return (uint32_t)c >> 5; }
__device__ __forceinline__ uint32_t gtick_dep(uint32_t zero) {
    uint32_t c;
    asm volatile("{\n.reg .pred p;\nsetp.eq.u32 p, %1, 0;\nmov.u32 %0, 0;\n@p mov.u32 %0, %%globaltimer_lo;\n}" : "=r"(c) : "r"(zero));
    return c >> 5;
}
__device__ __forceinline__ uint32_t ld_relaxed1(const void* p) {
    uint32_t v; asm volatile("ld.relaxed.gpu.global.u32 %0, [%1];" : "=r"(v) : "l"(p) : "memory"); return v;
}
__device__ __forceinline__ bool any_nan(float a, float b) {
    uint32_t r;
    asm volatile("{\n.reg .pred p;\nsetp.nan.f32 p, %1, %2;\nvote.sync.any.pred p, p, 0xffffffff;\nselp.u32 %0, 1, 0, p;\n}" : "=r"(r) : "f"(a), "f"(b));
    return r;
}
__device__ __forceinline__ bool bar_sync_any_nan(float a, float b) {
    uint32_t r;
    asm volatile("{\n.reg .pred p;\nsetp.nan.f32 p, %1, %2;\nbarrier.cta.red.or.aligned.pred p, 6, 256, p;\nselp.u32 %0, 1, 0, p;\n}"
                 : "=r"(r) : "f"(a), "f"(b) : "memory");
    return r;
}
__device__ __forceinline__ void bar_arrive(int id, int n) { asm volatile("bar.arrive %0, %1;" :: "r"(id), "r"(n) : "memory"); }
__device__ __forceinline__ uint32_t clk() { uint64_t c; asm volatile("mov.u64 %0, %%clock64;" : "=l"(c)); return (uint32_t)c; }
__device__ __forceinline__ void tma2d_store(const CUtensorMap* m, int c0, int c1, uint32_t src) {
    asm volatile("cp.async.bulk.tensor.2d.global.shared::cta.bulk_group [%0, {%1, %2}], [%3];"
                 :: "l"(m), "r"(c0), "r"(c1), "r"(src) : "memory");
}
__device__ __forceinline__ void bar_sync(int id, int n) { asm volatile("bar.sync %0, %1;" :: "r"(id), "r"(n) : "memory"); }
__device__ __forceinline__ void fence_async() { asm volatile("fence.proxy.async.shared::cta;" ::: "memory"); }
__device__ __forceinline__ void cluster_sync() {
    asm volatile("barrier.cluster.arrive.release.aligned;\nbarrier.cluster.wait.acquire.aligned;" ::: "memory");
}
__device__ __forceinline__ void ldsm4(uint32_t* r, uint32_t a) {
    asm volatile("ldmatrix.sync.aligned.m8n8.x4.shared.b16 {%0,%1,%2,%3}, [%4];"
                 : "=r"(r[0]), "=r"(r[1]), "=r"(r[2]), "=r"(r[3]) : "r"(a) : "memory");
}
__device__ __forceinline__ void ldsm4t(uint32_t* r, uint32_t a) {
    asm volatile("ldmatrix.sync.aligned.m8n8.x4.trans.shared.b16 {%0,%1,%2,%3}, [%4];"
                 : "=r"(r[0]), "=r"(r[1]), "=r"(r[2]), "=r"(r[3]) : "r"(a) : "memory");
}
__device__ __forceinline__ void stsm4(uint32_t a, uint32_t r0, uint32_t r1, uint32_t r2, uint32_t r3) {
    asm volatile("stmatrix.sync.aligned.m8n8.x4.shared.b16 [%0], {%1,%2,%3,%4};" :: "r"(a), "r"(r0), "r"(r1), "r"(r2), "r"(r3) : "memory");
}
__device__ __forceinline__ void stsm4f(uint32_t a, const float* v) {
    asm volatile("{\n.reg .b32 a, b, c, d;\nmov.b32 a, %1;\nmov.b32 b, %2;\nmov.b32 c, %3;\nmov.b32 d, %4;\n"
                 "stmatrix.sync.aligned.m8n8.x4.shared.b16 [%0], {a, b, c, d};\n}" :: "r"(a), "f"(v[0]), "f"(v[1]), "f"(v[2]), "f"(v[3]) : "memory");
}
__device__ __forceinline__ void ldsm4f(float* v, uint32_t a) {
    uint32_t r[4];
    ldsm4(r, a);
#pragma unroll
    for (int i = 0; i < 4; i++) v[i] = __uint_as_float(r[i]);
}
__device__ __forceinline__ void stsm4t(uint32_t a, uint32_t r0, uint32_t r1, uint32_t r2, uint32_t r3) {
    asm volatile("stmatrix.sync.aligned.m8n8.x4.trans.shared.b16 [%0], {%1,%2,%3,%4};" :: "r"(a), "r"(r0), "r"(r1), "r"(r2), "r"(r3) : "memory");
}
__device__ __forceinline__ void stsm2(uint32_t a, uint32_t r0, uint32_t r1) {
    asm volatile("stmatrix.sync.aligned.m8n8.x2.shared.b16 [%0], {%1,%2};" :: "r"(a), "r"(r0), "r"(r1) : "memory");
}
__device__ __forceinline__ void stsm2t(uint32_t a, uint32_t r0, uint32_t r1) {
    asm volatile("stmatrix.sync.aligned.m8n8.x2.trans.shared.b16 [%0], {%1,%2};" :: "r"(a), "r"(r0), "r"(r1) : "memory");
}
__device__ __forceinline__ uint32_t movm(uint32_t a) {
    uint32_t d; asm volatile("movmatrix.sync.aligned.m8n8.trans.b16 %0, %1;" : "=r"(d) : "r"(a)); return d;
}
__device__ __forceinline__ void mma16(float* d, uint32_t a0, uint32_t a1, uint32_t a2, uint32_t a3, uint32_t b0, uint32_t b1) {
    asm volatile("mma.sync.aligned.m16n8k16.row.col.f32.bf16.bf16.f32 {%0,%1,%2,%3}, {%4,%5,%6,%7}, {%8,%9}, {%0,%1,%2,%3};"
                 : "+f"(d[0]), "+f"(d[1]), "+f"(d[2]), "+f"(d[3]) : "r"(a0), "r"(a1), "r"(a2), "r"(a3), "r"(b0), "r"(b1));
}
__device__ __forceinline__ void mma8(float* d, uint32_t a0, uint32_t a1, uint32_t b0) {
    asm volatile("mma.sync.aligned.m16n8k8.row.col.f32.bf16.bf16.f32 {%0,%1,%2,%3}, {%4,%5}, {%6}, {%0,%1,%2,%3};"
                 : "+f"(d[0]), "+f"(d[1]), "+f"(d[2]), "+f"(d[3]) : "r"(a0), "r"(a1), "r"(b0));
}
__device__ __forceinline__ uint32_t pack2(float lo, float hi) {
    uint32_t r; asm("cvt.rn.bf16x2.f32 %0, %1, %2;" : "=r"(r) : "f"(hi), "f"(lo)); return r;
}
__device__ __forceinline__ float bf_lo(uint32_t v) { return __uint_as_float(v << 16); }
__device__ __forceinline__ float bf_hi(uint32_t v) { return __uint_as_float(v & 0xFFFF0000u); }
__device__ __forceinline__ float ex2(float x) { float y; asm("ex2.approx.ftz.f32 %0, %1;" : "=f"(y) : "f"(x)); return y; }
__device__ __forceinline__ float rcp(float x) { float y; asm("rcp.approx.ftz.f32 %0, %1;" : "=f"(y) : "f"(x)); return y; }
__device__ __forceinline__ void sts4f(uint32_t a, float x, float y, float z, float w) {
    asm volatile("st.shared.v4.f32 [%0], {%1,%2,%3,%4};" :: "r"(a), "f"(x), "f"(y), "f"(z), "f"(w) : "memory");
}
__device__ __forceinline__ void sts1u(uint32_t a, uint32_t v) { asm volatile("st.shared.u32 [%0], %1;" :: "r"(a), "r"(v) : "memory"); }
__device__ __forceinline__ void sts4u(uint32_t a, uint4 v) {
    asm volatile("st.shared.v4.u32 [%0], {%1,%2,%3,%4};" :: "r"(a), "r"(v.x), "r"(v.y), "r"(v.z), "r"(v.w) : "memory");
}
__device__ __forceinline__ float4 lds4f(uint32_t a) {
    float4 v; asm volatile("ld.shared.v4.f32 {%0,%1,%2,%3}, [%4];" : "=f"(v.x), "=f"(v.y), "=f"(v.z), "=f"(v.w) : "r"(a) : "memory"); return v;
}
__device__ __forceinline__ float2 lds2f(uint32_t a) {
    float2 v; asm volatile("ld.shared.v2.f32 {%0,%1}, [%2];" : "=f"(v.x), "=f"(v.y) : "r"(a) : "memory"); return v;
}
__device__ __forceinline__ uint4 lds4u(uint32_t a) {
    uint4 v; asm volatile("ld.shared.v4.u32 {%0,%1,%2,%3}, [%4];" : "=r"(v.x), "=r"(v.y), "=r"(v.z), "=r"(v.w) : "r"(a) : "memory"); return v;
}
__device__ __forceinline__ uint32_t lds1u(uint32_t a) {
    uint32_t v; asm volatile("ld.shared.u32 %0, [%1];" : "=r"(v) : "r"(a) : "memory"); return v;
}
__device__ __forceinline__ uint2 lds2u(uint32_t a) {
    uint2 v; asm volatile("ld.shared.v2.u32 {%0,%1}, [%2];" : "=r"(v.x), "=r"(v.y) : "r"(a) : "memory"); return v;
}
__device__ __forceinline__ void st_async4(uint32_t a, uint32_t bar, float x, float y, float z, float w) {
    asm volatile("st.async.shared::cluster.mbarrier::complete_tx::bytes.v4.f32 [%0], {%1,%2,%3,%4}, [%5];"
                 :: "r"(a), "f"(x), "f"(y), "f"(z), "f"(w), "r"(bar) : "memory");
}
__device__ __forceinline__ void st_async2(uint32_t a, uint32_t bar, float x, float y) {
    asm volatile("st.async.shared::cluster.mbarrier::complete_tx::bytes.v2.f32 [%0], {%1,%2}, [%3];"
                 :: "r"(a), "f"(x), "f"(y), "r"(bar) : "memory");
}
__device__ __forceinline__ void st_async1f(uint32_t a, uint32_t bar, float x) {
    asm volatile("st.async.shared::cluster.mbarrier::complete_tx::bytes.f32 [%0], %1, [%2];" :: "r"(a), "f"(x), "r"(bar) : "memory");
}
__device__ __forceinline__ void st_async1(uint32_t a, uint32_t bar, uint32_t x) {
    asm volatile("st.async.shared::cluster.mbarrier::complete_tx::bytes.b32 [%0], %1, [%2];" :: "r"(a), "r"(x), "r"(bar) : "memory");
}
__device__ __forceinline__ uint4 ld_relaxed4(const uint4* p) {
    uint4 v;
    asm volatile("ld.relaxed.gpu.global.v4.u32 {%0,%1,%2,%3}, [%4];" : "=r"(v.x), "=r"(v.y), "=r"(v.z), "=r"(v.w) : "l"(p) : "memory");
    return v;
}
__device__ __forceinline__ void st_relaxed4(uint4* p, uint4 v) {
    asm volatile("st.relaxed.gpu.global.v4.u32 [%0], {%1,%2,%3,%4};" :: "l"(p), "r"(v.x), "r"(v.y), "r"(v.z), "r"(v.w) : "memory");
}
__device__ __forceinline__ void count_up(int idx) {
    asm volatile("red.release.gpu.global.add.u32 [%0], 1;" :: "l"(&g_cnt[idx * 8]) : "memory");
}
__device__ __forceinline__ void st_pred1(void* p, uint32_t v, bool on) {
    asm volatile("{\n.reg .pred p;\nsetp.ne.u32 p, %2, 0;\n@p st.relaxed.gpu.global.u32 [%0], %1;\n}" :: "l"(p), "r"(v), "r"((uint32_t)on) : "memory");
}
__device__ __forceinline__ void st_pred4(void* p, uint4 v, bool on) {
    asm volatile("{\n.reg .pred p;\nsetp.ne.u32 p, %5, 0;\n@p st.global.v4.u32 [%0], {%1,%2,%3,%4};\n}"
                 :: "l"(p), "r"(v.x), "r"(v.y), "r"(v.z), "r"(v.w), "r"((uint32_t)on) : "memory");
}
__device__ __forceinline__ void st_relaxed1(void* p, uint32_t v) {
    asm volatile("st.relaxed.gpu.global.u32 [%0], %1;" :: "l"(p), "r"(v) : "memory");
}
__device__ __forceinline__ uint32_t umax4(uint4 v) { return max(max(v.x, v.y), max(v.z, v.w)); }
__device__ __forceinline__ void wg_fence() { asm volatile("wgmma.fence.sync.aligned;" ::: "memory"); }
__device__ __forceinline__ void wg_commit() { asm volatile("wgmma.commit_group.sync.aligned;" ::: "memory"); }
template <int N> __device__ __forceinline__ void wg_wait() { asm volatile("wgmma.wait_group.sync.aligned %0;" :: "n"(N) : "memory"); }
template <int N> __device__ __forceinline__ void reg_fence(float* d) {
#pragma unroll
    for (int i = 0; i < N; i++) asm volatile("" : "+f"(d[i]) :: "memory");
}
#define ACC16(d) "+f"(d[0]), "+f"(d[1]), "+f"(d[2]), "+f"(d[3]), "+f"(d[4]), "+f"(d[5]), "+f"(d[6]), "+f"(d[7]), \
                 "+f"(d[8]), "+f"(d[9]), "+f"(d[10]), "+f"(d[11]), "+f"(d[12]), "+f"(d[13]), "+f"(d[14]), "+f"(d[15])
#define DESC_HI_SW128 "0x40000040"
#define OUT16(d) "=f"(d[0]), "=f"(d[1]), "=f"(d[2]), "=f"(d[3]), "=f"(d[4]), "=f"(d[5]), "=f"(d[6]), "=f"(d[7]), \
                 "=f"(d[8]), "=f"(d[9]), "=f"(d[10]), "=f"(d[11]), "=f"(d[12]), "=f"(d[13]), "=f"(d[14]), "=f"(d[15])
template <int ACCUM, int BOFF>
__device__ __forceinline__ void wg32_rs(float* d, const uint32_t* a, uint64_t dsw) {
    if (ACCUM)
        asm volatile("{\n.reg .b64 db;\nadd.s64 db, %20, %21;\n"
                     "wgmma.mma_async.sync.aligned.m64n32k16.f32.bf16.bf16 {%0,%1,%2,%3,%4,%5,%6,%7,%8,%9,%10,%11,%12,%13,%14,%15}, "
                     "{%16,%17,%18,%19}, db, 1, 1, 1, 0;\n}"
                     : ACC16(d) : "r"(a[0]), "r"(a[1]), "r"(a[2]), "r"(a[3]), "l"(dsw), "n"(BOFF));
    else
        asm volatile("{\n.reg .b64 db;\nadd.s64 db, %20, %21;\n"
                     "wgmma.mma_async.sync.aligned.m64n32k16.f32.bf16.bf16 {%0,%1,%2,%3,%4,%5,%6,%7,%8,%9,%10,%11,%12,%13,%14,%15}, "
                     "{%16,%17,%18,%19}, db, 0, 1, 1, 0;\n}"
                     : OUT16(d) : "r"(a[0]), "r"(a[1]), "r"(a[2]), "r"(a[3]), "l"(dsw), "n"(BOFF));
}
template <int ACCUM, int AOFF, int BOFF>
__device__ __forceinline__ void wg32_ss(float* d, uint64_t dsw) {
    if (ACCUM)
        asm volatile("{\n.reg .b64 da, db;\nadd.s64 da, %16, %17;\nadd.s64 db, %16, %18;\n"
                     "wgmma.mma_async.sync.aligned.m64n32k16.f32.bf16.bf16 {%0,%1,%2,%3,%4,%5,%6,%7,%8,%9,%10,%11,%12,%13,%14,%15}, "
                     "da, db, 1, 1, 1, 1, 0;\n}"
                     : ACC16(d) : "l"(dsw), "n"(AOFF), "n"(BOFF));
    else
        asm volatile("{\n.reg .b64 da, db;\nadd.s64 da, %16, %17;\nadd.s64 db, %16, %18;\n"
                     "wgmma.mma_async.sync.aligned.m64n32k16.f32.bf16.bf16 {%0,%1,%2,%3,%4,%5,%6,%7,%8,%9,%10,%11,%12,%13,%14,%15}, "
                     "da, db, 0, 1, 1, 1, 0;\n}"
                     : OUT16(d) : "l"(dsw), "n"(AOFF), "n"(BOFF));
}
template <int ACCUM, int AOFF, int BOFF>
__device__ __forceinline__ void wg8_ss(float* d, uint64_t dsw, uint64_t dns) {
    if (!ACCUM)
        asm volatile("{\n.reg .b64 da, db;\nadd.s64 da, %4, %6;\nadd.s64 db, %5, %7;\n"
                     "wgmma.mma_async.sync.aligned.m64n8k16.f32.bf16.bf16 {%0,%1,%2,%3}, da, db, 0, 1, 1, 1, 0;\n}"
                     : "=f"(d[0]), "=f"(d[1]), "=f"(d[2]), "=f"(d[3]) : "l"(dsw), "l"(dns), "n"(AOFF), "n"(BOFF));
    else
        asm volatile("{\n.reg .b64 da, db;\nadd.s64 da, %4, %6;\nadd.s64 db, %5, %7;\n"
                     "wgmma.mma_async.sync.aligned.m64n8k16.f32.bf16.bf16 {%0,%1,%2,%3}, da, db, 1, 1, 1, 1, 0;\n}"
                     : "+f"(d[0]), "+f"(d[1]), "+f"(d[2]), "+f"(d[3]) : "l"(dsw), "l"(dns), "n"(AOFF), "n"(BOFF));
}
template <int I0, int I1, class F>
__device__ __forceinline__ void static_for(F&& f) {
    if constexpr (I0 < I1) { f(std::integral_constant<int, I0>{}); static_for<I0 + 1, I1>(f); }
}
template <int I0, int I1, int AOFF, int BOFF>
__device__ __forceinline__ void wg8_chain(float* d, uint64_t dsw, uint64_t dns) {
    wg_fence();
    static_for<I0, I1>([&](auto i) { wg8_ss<i.value != 0, AOFF + i.value * 128, BOFF + i.value * 16>(d, dsw, dns); });
    wg_commit();
}

__device__ __forceinline__ void ln_row(const uint4* v, int row, int lane) {
    float f[32];
#pragma unroll
    for (int j = 0; j < 4; j++) {
        f[j * 8 + 0] = bf_lo(v[j].x); f[j * 8 + 1] = bf_hi(v[j].x); f[j * 8 + 2] = bf_lo(v[j].y); f[j * 8 + 3] = bf_hi(v[j].y);
        f[j * 8 + 4] = bf_lo(v[j].z); f[j * 8 + 5] = bf_hi(v[j].z); f[j * 8 + 6] = bf_lo(v[j].w); f[j * 8 + 7] = bf_hi(v[j].w);
    }
    float s = 0.f;
#pragma unroll
    for (int i = 0; i < 32; i++) s += f[i];
#pragma unroll
    for (int o = 16; o; o >>= 1) s += __shfl_xor_sync(~0u, s, o);
    const float mean = s * (1.f / DM);
    float q = 0.f;
#pragma unroll
    for (int i = 0; i < 32; i++) { f[i] -= mean; q += f[i] * f[i]; }
#pragma unroll
    for (int o = 16; o; o >>= 1) q += __shfl_xor_sync(~0u, q, o);
    const float r = 1.f / sqrtf(q * (1.f / DM) + 1e-5f);
    uint4* dst = reinterpret_cast<uint4*>(g_xn + (size_t)row * DM);
    uint4* dst2 = g_xc + (row >> 5) * 4096 + (lane >> 3) * 256 + (row & 31) * 8 + ((lane & 7) ^ (row & 7));
#pragma unroll
    for (int j = 0; j < 4; j++) {
        const uint4 o = make_uint4(pack2(f[j * 8] * r, f[j * 8 + 1] * r), pack2(f[j * 8 + 2] * r, f[j * 8 + 3] * r),
                                   pack2(f[j * 8 + 4] * r, f[j * 8 + 5] * r), pack2(f[j * 8 + 6] * r, f[j * 8 + 7] * r));
        dst[j * 32 + lane] = o;
        dst2[(j & 1) * 2048 + (j >> 1) * 1024] = o;
    }
}
__device__ __forceinline__ void reset_exchange(const __nv_bfloat16* __restrict__ mem0) {
    const int gi = blockIdx.x * 256 + threadIdx.x;
    const uint4 poison = make_uint4(~0u, ~0u, ~0u, ~0u);
    if (gi < 1024) {
        uint4 m = reinterpret_cast<const uint4*>(mem0)[(gi & 7) * 128 + (gi >> 3)];
        if (m.x == ~0u) m.x = 0x7FFF7FFFu;
        if (m.y == ~0u) m.y = 0x7FFF7FFFu;
        if (m.z == ~0u) m.z = 0x7FFF7FFFu;
        if (m.w == ~0u) m.w = 0x7FFF7FFFu;
        g_xmem[0][gi] = m;
    } else if (gi < 4096) {
        (&g_xmem[0][0])[gi] = poison;
    } else if (gi < 4096 + 16384) {
        (&g_xo[0][0])[gi - 4096] = poison;
    } else if (gi < 4096 + 16384 + 48 * FSTR) {
        reinterpret_cast<uint4*>(&g_flag[0][0])[gi - 4096 - 16384] = poison;
    } else if (gi >= 24576 - CNT_NUM) {
        g_cnt[(24575 - gi) * 8] = 0;
    }
}

#define ONKQ 45
constexpr int ONKV = 128 - 2 * ONKQ;
constexpr uint32_t SB0 = 1024;
constexpr uint32_t C_WS = 0, C_XN = 65536, C_MB = 98304, C_WO = 114688, C_SMEM = 232448;
constexpr uint32_t C_BAR = C_SMEM - 384, C_CAL = C_BAR + 192;
constexpr uint32_t C_SLOTQ = C_WO + ONKQ * 2048, C_QX = C_SLOTQ + 8192, C_KX = C_QX + 4096,
                   C_XSL = C_KX + 4096, C_OL = C_XSL + 5120;
constexpr uint32_t C_SLOTV = C_WO + ONKV * 2048, C_V = C_SLOTV + 8192, C_PL = C_V + 20480, C_SL = C_PL + 4096;
constexpr uint32_t C_DUMP = C_BAR - 512;
static_assert(C_OL + 3072 <= C_DUMP && C_SL + 2560 <= C_DUMP, "smem overflow");
enum { B_W0 = 0, B_W1, B_W2, B_WS, B_XF0, B_XF1, B_SC, B_P0, B_P1, B_XS, B_OL, B_MF0, B_MF1, B_OF, B_RT0, B_RT1, B_VF, B_MBF, B_GO, B_DUMP, B_NUM };
struct Descs { uint64_t sw[4], ns; };
constexpr uint64_t DSW = 0x4000004000010000ull, DNS = 0x0000001000080000ull;
template <int V> using ic = std::integral_constant<int, V>;
constexpr float SM_SCALE = 0.08838834764831845f * 1.4426950408889634f;

#define TSD(i) do {} while (0)
#define TS_FLUSH(w)
#define TSX(i, c)
#define TS(i)
#define NOFILL 0
#define DLY1 2200
#define DLY2 1300
#define SWAP16 0
#define SSFIRST 1
#define EARLYB 0
#define CANARY ~0u
#define QK1 10
#define RFPOS 6
#define STPOS 14
#define OTAIL 3
#define DLYS 450
#define DLYB 1
#define VLEAD 1

#define VEARLY 8
#define QSPLIT 20
__device__ __forceinline__ bool elect() {
    uint32_t r;
    asm volatile("{\n.reg .pred p;\nelect.sync _|p, 0xffffffff;\nselp.u32 %0, 1, 0, p;\n}" : "=r"(r));
    return r;
}
__device__ __forceinline__ int uni(int v) { return __shfl_sync(~0u, v, 0); }
__device__ __forceinline__ void calibrate(uint32_t cal, float keep) {
    const uint32_t t0 = gtick();
    uint32_t t, it = 0;
    do { t = gtick(); spin_guard(it); } while (__any_sync(~0u, t == t0));
    const uint32_t c = clk();
    const uint4 p = lds4u(cal);
    const float cpt = 256.f * fminf(fmaxf(__fdividef((float)(c - p.y), (float)((t - p.x) & 0x7FFFFFF)), 16.f), 128.f);
    __syncwarp();
    sts4u(cal, make_uint4(t, c, (uint32_t)(keep > 0.f ? fmaf(keep, (float)p.z - cpt, cpt) : cpt), 0));
}
struct Stamps { uint32_t v[6]; };
__device__ __forceinline__ void load_stamps2(Stamps& t, const uint32_t* f, uint32_t l16, bool on = true) {
    const char* p = reinterpret_cast<const char*>(f) + (l16 >> 2) * FSTR;
    asm volatile("{\n.reg .pred p;\nsetp.ne.u32 p, %7, 0;\nmov.u32 %0, 63;\nmov.u32 %1, 63;\nmov.u32 %2, 63;\nmov.u32 %3, 63;\nmov.u32 %4, 63;\nmov.u32 %5, 63;\n"
                 "@p ld.relaxed.gpu.global.v2.u32 {%0, %1}, [%6];\n@p ld.relaxed.gpu.global.v2.u32 {%2, %3}, [%6 + %8];\n"
                 "@p ld.relaxed.gpu.global.v2.u32 {%4, %5}, [%6 + %9];\n}"
                 : "=&r"(t.v[0]), "=&r"(t.v[1]), "=&r"(t.v[2]), "=&r"(t.v[3]), "=&r"(t.v[4]), "=&r"(t.v[5])
                 : "l"(p), "r"((uint32_t)on), "n"(128 * FSTR), "n"(256 * FSTR) : "memory");
}
__device__ __forceinline__ void load_stamps1(uint32_t* v, const uint32_t* f, uint32_t l16, bool on = true) {
    const char* p = reinterpret_cast<const char*>(f) + (l16 >> 2) * FSTR;
    asm volatile("{\n.reg .pred p;\nsetp.ne.u32 p, %4, 0;\nmov.u32 %0, 63;\nmov.u32 %1, 63;\nmov.u32 %2, 63;\n"
                 "@p ld.relaxed.gpu.global.u32 %0, [%3];\n@p ld.relaxed.gpu.global.u32 %1, [%3 + %5];\n@p ld.relaxed.gpu.global.u32 %2, [%3 + %6];\n}"
                 : "=&r"(v[0]), "=&r"(v[1]), "=&r"(v[2]) : "l"(p), "r"((uint32_t)on), "n"(128 * FSTR), "n"(256 * FSTR) : "memory");
}
template <int N>
__device__ __forceinline__ uint32_t stamps_missing(const uint32_t* v, int s) {
    uint32_t x = 0;
#pragma unroll
    for (int i = 0; i < N; i++) x |= v[i] ^ s;
    return x & 63;
}
template <int N>
__device__ __forceinline__ uint32_t latest_stamp(const uint32_t* v, const uint4 cal) {
    int late = (int)(v[0] - (cal.x << 6));
#pragma unroll
    for (int i = 1; i < N; i++) late = max(late, (int)(v[i] - (cal.x << 6)));
    return cal.y + (((late >> 6) * (int)cal.z) >> 8);
}
__device__ __forceinline__ void wait_clock(uint32_t target) {
    while (__any_sync(~0u, target - clk() < 65536u)) {}
}

template <int BYTES>
__device__ __forceinline__ bool incomplete(uint32_t buf, uint32_t l16) {
    uint32_t m = 0;
#pragma unroll 1
    for (int o = 0; o < BYTES; o += 256) m = max(m, umax4(lds4u(buf + o + (l16 & 255))));
    return __any_sync(~0u, m == ~0u);
}
__device__ __forceinline__ void refetch(uint32_t buf, const uint4* src, uint32_t bytes, uint32_t b, int w4, int barid, uint32_t& tries) {
    spin_guard(tries);
    bar_sync(barid, 128);
    if (w4 == 0 && elect()) { mbar_expect(b, bytes); bulk_ld(buf, src, bytes, b); }
    __syncwarp();
    mbar_wait(b, 0);
    bar_sync(barid, 128);
    if (w4 == 0 && elect()) mbar_arrive(b);
    __syncwarp();
}

__device__ __forceinline__ void load_chunk(const CUtensorMap* tA, const CUtensorMap* tB, int cl, int rank, uint32_t dst, int j, uint32_t b) {
    const int colA = cl * 256 + (rank >= 4 ? (rank - 4) * 128 : rank * 64), colB = colA + (rank >= 4 ? 64 : 0);
    mbar_expect(b, 65536);
    tma2d(dst, tA, colA, j * 128, b);
    tma2d(dst + 16384, tB, colB, j * 128, b);
    tma2d(dst + 32768, tB, colB, 512 + j * 128, b);
    tma2d(dst + 49152, tA, colA, 512 + j * 128, b);
}

template <bool ISV, int WG>
__device__ __forceinline__ void chain_main(const CUtensorMap* tA, const CUtensorMap* tB, const CUtensorMap* tWo,
                                           const uint32_t sb, const int cl, const int rank, const Descs& D, const uint32_t goal) {
    const int tid = threadIdx.x;
    uint32_t l16 = __shfl_sync(~0u, (tid & 31) * 16, tid & 31);
    int w4 = uni((tid >> 5) & 3);
    const int role = ISV ? 2 : (rank & 1), hh = ISV ? rank - 4 : rank >> 1, head = 2 * cl + hh;
    const uint32_t bar = sb + C_BAR;
    constexpr int ONK = ISV ? ONKV : ONKQ;
    const int ostart = (hh * 128 + role * ONKQ);

    uint32_t wk[24][4], wv[24][4];
    uint32_t a_adr;
    {
        if (WG == 1 && w4 == 0) calibrate(sb + C_CAL, 0.f);
        const int lane = tid & 31, kr = (lane & 7) + ((lane >> 4) << 3);
        a_adr = __shfl_sync(~0u, sb + WG * 32768 + kr * 128 + (((w4 * 2 + ((lane >> 3) & 1)) ^ (kr & 7)) << 4), lane);
#pragma unroll
        for (int j = 0; j < 3; j++) {
            mbar_wait(bar + (B_W0 + j) * 8, 0);
#pragma unroll
            for (int i = 0; i < 8; i++) {
                ldsm4t(wk[j * 8 + i], a_adr + j * 65536 + i * 2048);
                ldsm4t(wv[j * 8 + i], a_adr + j * 65536 + 16384 + i * 2048);
            }
            if (j != 1) {
                bar_sync(6, 256);
                if (j == 0 && tid == 0) TL(1, 6);
                if (WG == 0 && j == 0 && w4 == 0 && elect()) load_chunk(tA, tB, cl, rank, sb + C_WS, 3, bar + B_WS * 8);
                if (WG == 0 && j == 2) {
                    if (elect())
                        for (int i = w4; i < ONK; i += 4) tma2d(sb + C_WO + i * 2048, tWo, cl * 64, (ostart + i) * 16, bar + B_OF * 8);
                }
                __syncwarp();
            }
        }
        if (NOFILL) { for (uint32_t o = C_WO + ONK * 2048 + tid * 16; o < C_BAR; o += 4096) sts4u(sb + o, make_uint4(0, 0, 0, 0)); bar_sync(6, 256); }
        if (WG == 1 && w4 == 1) {
            uint32_t v, it = 0;
            do {
                asm volatile("ld.acquire.gpu.global.u32 %0, [%1];" : "=r"(v) : "l"(&g_epoch) : "memory");
                spin_guard(it);
            } while (__any_sync(~0u, (int)(v - goal) < 0));
        }
        if (WG == 1 && w4 == 0) calibrate(sb + C_CAL, 0.f);
        __syncwarp();
        bar_sync(6, 256);
        asm volatile("fence.proxy.async.global;" ::: "memory");
    }

    constexpr uint32_t SLOT = ISV ? C_SLOTV : C_SLOTQ;
    constexpr int WS_A = (SB0 + C_WS + WG * 32768) >> 4, WO_A = (SB0 + C_WO) >> 4, MB_A = (SB0 + C_MB) >> 4;
#define XN_A(ks) (int)(((SB0 + C_XN + WG * 16384) >> 4) + ((ks) >> 2) * 256 + ((ks) & 3) * 2)
    const uint32_t slot = (sb + SLOT + w4 * 512), mbw = sb + C_MB + WG * 8192;
    const uint32_t sb_v = (mapa(sb, 4 + hh));
    const uint32_t sb_x = uni(mapa(sb, 2 * hh + (WG ? 1 : (~w4 & 1))));
    const uint32_t sb_o = (mapa(sb, w4));
    const uint32_t u_off = (ISV ? (head * 128 + w4 * 32) * 16 : (cl * 4 + rank) * 256 + (w4 & 1) * 128);
    const uint32_t v_row = (sb + C_V + (2 * WG + (w4 >> 1)) * 512), v_b = ((w4 & 1) * 64);
    const uint32_t u_flag = (blockIdx.x * FSTR);
    const uint32_t f_half = (w4 & 1) * role * (ONKV * 128), f_sb = uni(mapa(sb, rank + (w4 & 1) * (4 + hh - rank)));
    const uint32_t f_src = uni((ostart + (w4 & 1) * (2 - role) * ONKQ) * 256 + f_half), f_dst = uni(f_sb + C_MB + f_half);
    const uint32_t m_dst = (sb + C_MB + role * 8192), m_bar = (bar + (B_MF0 + role) * 8);
    uint32_t target, missing;
    int s = -1;
    uint32_t pf[4][4];
    float xk[16], xv[16];
    uint4 oxp[4];

    auto send_planes = [&](auto n, uint32_t a, int b, const float* v, bool hold) {
        const uint32_t dump = sb + C_DUMP + (l16 >> 2), to = a + (l16 >> 2), ad = hold ? dump : to;
        const uint32_t mb = hold ? (dump & 0xFF000000u) | (SB0 + C_BAR + B_DUMP * 8) : (to & 0xFF000000u) | (SB0 + C_BAR + b * 8);
#pragma unroll
        for (int i = 0; i < n.value; i++) st_async1f(ad + i * 128, mb, v[i]);
    };
    auto store_ox = [&](int ss) {
        char* orow = reinterpret_cast<char*>(g_ox) + (ss * (32 * HD * 2) + (u_off >> 3) + (l16 >> 6) * (HD * 2) + (l16 & 48));
#pragma unroll
        for (int i = 0; i < 4; i++) st_pred4(orow + i * (8 * HD * 2), oxp[i], ss >= 0);
    };
    auto load_tokens = [&](int seg, int wina, int g) {
        const int khalf = ISV ? 1 - wina : wina;
        if (!NOFILL && elect()) {
            mbar_expect(bar + (B_XF0 + g) * 8, 16384);
            bulk_ld(sb + C_XN + g * 16384, g_xc + (seg * 4 + khalf * 2 + g) * 1024, 16384, bar + (B_XF0 + g) * 8);
        }
        __syncwarp();
    };
    auto prefetch = [&]() {
#pragma unroll
        for (int i = 0; i < 4; i++) ldsm4t(pf[i], a_adr + C_WS + (i & 1) * 16384 + (i >> 1) * 2048);
    };
    constexpr int HA = ISV ? 0 : 1, NK1 = ISV ? 0 : QK1;
    auto products = [&](auto give, auto half, auto init, auto i0, auto i1, const uint64_t d) {
        static_for<i0.value, i1.value>([&](auto i) {
            constexpr int ks = half.value * 16 + i.value, acc = !(init.value && i.value == i0.value);
            if constexpr (ks >= 24) wg32_ss<acc, WS_A + give.value * 1024 + (ks - 24) * 128, XN_A(i.value)>(give.value ? xv : xk, d);
            else if constexpr (give.value) wg32_rs<acc, XN_A(i.value)>(xv, wv[ks], d);
            else wg32_rs<acc, XN_A(i.value)>(xk, wk[ks], d);
        });
    };
    auto stream_a = [&](const uint64_t dk, const uint64_t dv) {
        if (NOFILL) return;
        constexpr int F = (WG == 0 && SSFIRST) ? 8 : 0;
        wg_fence();
        products(ic<0>{}, ic<HA>{}, ic<1>{}, ic<F>{}, ic<F + 8>{}, dk);
        products(ic<1>{}, ic<HA>{}, ic<1>{}, ic<F>{}, ic<F + 8>{}, dv);
        products(ic<1>{}, ic<HA>{}, ic<0>{}, ic<8 - F>{}, ic<16 - F>{}, dv);
        products(ic<0>{}, ic<HA>{}, ic<0>{}, ic<8 - F>{}, ic<16 - F>{}, dk);
        wg_commit();
    };
    auto token_softmax = [&]() {
        const int hi = w4 - 2, lane = l16 >> 4;
        const uint32_t src = sb + C_XSL + hi * 256 + (l16 & 255) + (l16 >> 8) * 2560;
        const int d0 = 16 * role + 8 * hi + (lane >> 2) - 2 * (lane & 3);
        mbar_wait(bar + B_XS * 8, s & 1);
        float e[10];
        float m = -INFINITY;
#pragma unroll
        for (int i = 0; i < 5; i++) {
            __syncwarp();
            float a[4];
            ldsm4f(a, src + i * 512);
            e[2 * i] = (i == 0 || d0 >= 8 * (i - 1)) ? a[0] + a[2] : -INFINITY;
            e[2 * i + 1] = (i == 0 || d0 > 8 * (i - 1)) ? a[1] + a[3] : -INFINITY;
            m = fmaxf(m, fmaxf(e[2 * i], e[2 * i + 1]));
        }
        m = fmaxf(m, __shfl_xor_sync(~0u, m, 1));
        m = fmaxf(m, __shfl_xor_sync(~0u, m, 2));
        m *= -SM_SCALE;
        float l = 0.f;
#pragma unroll
        for (int i = 0; i < 10; i++) { e[i] = ex2(fmaf(e[i], SM_SCALE, m)); l += e[i]; }
        l += __shfl_xor_sync(~0u, l, 1);
        l += __shfl_xor_sync(~0u, l, 2);
        l = rcp(l);
        const uint32_t pd = sb_v + C_PL + (s & 1) * 2048 + role * 768 + hi * 128 + (l16 >> 2), pb = sb_v + C_BAR + (B_P0 + (s & 1)) * 8;
        st_async1(pd, pb, pack2(e[0] * l, e[1] * l));
        st_async1(pd + 256, pb, pack2(e[2] * l, e[3] * l));
        st_async1(pd + 512, pb, pack2(e[4] * l, e[5] * l));
        if (role) {
            st_async1(pd + 768, pb, pack2(e[6] * l, e[7] * l));
            st_async1(pd + 1024, pb, pack2(e[8] * l, e[9] * l));
        }
        if (hi == 0 && l16 == 0) mbar_expect(bar + B_XS * 8, 3072 + role * 2048);
        __syncwarp();
    };

    auto windows = [&](auto first_) {
        constexpr bool FIRST = first_.value;
        asm volatile("" : "+r"(l16), "+r"(w4));
        const uint64_t dd[4] = {FIRST ? DSW : D.sw[0], FIRST ? DSW : D.sw[1], FIRST ? DSW : D.sw[2], FIRST ? DSW : D.sw[3]};
        TS(5);
        if constexpr (WG == 1) {
            TS(6);
            if (ISV && !FIRST) bar_sync(3, 256);
            Stamps st2;
            if (!ISV && !FIRST) load_stamps2(st2, g_flag[0], l16, __any_sync(~0u, missing) && w4 < 2);
            stream_a(dd[0], dd[1]);
            if (!NOFILL) bar_arrive(7, 256);
            if (ISV && !FIRST) {
                if (!NOFILL) store_ox(s - 1);
                st_relaxed4(reinterpret_cast<uint4*>(reinterpret_cast<char*>(&g_xo[(s + 2) & 3][0]) + (u_off + l16)), make_uint4(~0u, ~0u, ~0u, ~0u));
            }
            auto fetch_o = [&]() {
            if (!FIRST && !ISV && w4 < 2) {
                const char* src = reinterpret_cast<const char*>(&g_xo[s & 3][0]) + f_src;
                if (__builtin_expect(__any_sync(~0u, missing), 0)) {
                    uint32_t it = 0;
                    while (__any_sync(~0u, stamps_missing<6>(st2.v, s))) { load_stamps2(st2, g_flag[0], l16); spin_guard(it); }
                    target = latest_stamp<6>(st2.v, lds4u(sb + C_CAL)) + DLY1;
                }
                mbar_wait(bar + B_VF * 8, s & 1);
                TS(10);
                wait_clock(target);
                if (elect()) bulk_ld(f_dst, src, ONKQ * 256 - w4 * (ONKQ * 256 - ONKV * 128), f_sb + C_BAR + B_OF * 8);
                __syncwarp();
                TS(8);
            }
            };
            if (!EARLYB) fetch_o();
            if (!NOFILL) {
                wg_wait<0>();
                reg_fence<16>(xk); reg_fence<16>(xv);
                if (w4 == 3) { bar_sync(2, 128); load_tokens(s + 1, 0, 1); }
                else bar_arrive(2, 128);
            }
            if (EARLYB) fetch_o();
            TS(7);
        } else {
            if (!NOFILL) {
                mbar_wait(bar + B_XF0 * 8, 0);
                bar_sync(7, 256);
            }
            TS(6);
            stream_a(dd[0], dd[1]);
        }
        uint32_t st[6];
        uint4 cal;
        if constexpr (WG == 0) {
            if constexpr (!FIRST) {
                const uint32_t dst = sb_o + C_OL + rank * 512;
                const uint32_t can = sb + C_MB + l16 * 8 + (l16 >> 2), can2 = can + (l16 < (ONK * 2 - 64) * 16 ? 8192 : 0);
                float co[4];
                TS(7);
                uint32_t tries = 0;
                for (;; tries |= 1) {
                    asm volatile("" : "+r"(tries));
                    if (__builtin_expect(tries, 0)) {
                        wg_wait<0>();
                        refetch(sb + C_MB, &g_xo[s & 3][ostart * 16], ONK * 256, bar + B_RT0 * 8, w4, 1, tries);
                    }
                    mbar_wait(bar + B_OF * 8, s & 1);
                    TS(8);
                    wg8_chain<0, 8, WO_A, MB_A>(co, D.sw[0], D.ns);
                    if (__builtin_expect(!__any_sync(~0u, max(max(lds1u(can), lds1u(can + 4096)), lds1u(can2)) == CANARY), 1)) break;
                }
                wg_wait<1>();
                if (l16 == 0) mbar_arrive(bar + B_GO * 8);
                wg8_chain<8, ONK - OTAIL, WO_A, MB_A>(co, D.sw[0], D.ns);
                static_for<ONK - OTAIL, ONK>([&](auto i) { wg8_ss<1, WO_A + i.value * 128, MB_A + i.value * 16>(co, D.sw[0], D.ns); });
                wg_commit();
                wg_wait<1>();
                bar_arrive(5, 256);
                wg_wait<0>();
                reg_fence<4>(co);
                const bool nan = any_nan(co[0], co[1]);
                send_planes(ic<4>{}, dst, B_OL, co, nan);
                if (__builtin_expect(nan, 0)) {
                    while (incomplete<ONK * 256>(sb + C_MB, l16)) {
                        refetch(sb + C_MB, &g_xo[s & 3][ostart * 16], ONK * 256, bar + B_RT0 * 8, w4, 1, tries);
                        co[0] = co[1] = co[2] = co[3] = 0.f;
#pragma unroll 1
                        for (int i = 0; i < ONK; i++) {
                            wg_fence();
                            wg8_ss<1, WO_A, MB_A>(co, DSW + i * 128, DNS + i * 16);
                            wg_commit();
                            wg_wait<0>();
                        }
                        reg_fence<4>(co);
                    }
                    send_planes(ic<4>{}, dst, B_OL, co, false);
                }
                TS(9);
                if (l16 < 48 && w4 == 3) mbar_expect(bar + B_MF0 * 8 + (l16 >> 1), l16 == 32 ? ONK * 256 : 8192);
            } else {
                wg_wait<0>();
                if (l16 == 0) mbar_arrive(bar + B_GO * 8);
                bar_arrive(5, 256);
            }
            if (l16 < 32) mbar_arrive_cluster(mapa(bar + B_MBF * 8, 2 * hh + (l16 >> 4)));
            __syncwarp();
            if (!NOFILL) { reg_fence<16>(xk); reg_fence<16>(xv); }
        } else {
            if (w4 < 2) {
                mbar_wait(bar + B_GO * 8, (s + 1) & 1);
                const uint32_t v = ((gtick() - (ISV ? (ONKQ - ONKV) * 18 / 64 : 0)) << 6) | s, c = clk();
                if (w4 == 0) {
                    if (!FIRST) {
                        if (l16 == 0) st_relaxed1(&g_flag[1][u_flag + (l16 >> 1)], v);
                        if (!ISV) calibrate(sb + C_CAL, 0.75f);
                    }
                } else {
                    if (!FIRST) wait_clock(c + DLYB);
                    load_tokens(s + 1, 0, 0);
                }
                if (!ISV && !FIRST) st_relaxed1(reinterpret_cast<char*>(&g_xmem[(s + 3) & 3][0]) + (u_off + (l16 >> 2)), ~0u);
            } else if (!FIRST && !NOFILL) {
                if (ISV && w4 == 2 && (s & 3) == 1 && s > 1 && l16 == 0) count_up(CNT_OX + (s >> 2) - 1);
                __syncwarp();
                if (!ISV) token_softmax();
                TSX(9, w4 == 2);
            }
            if (!NOFILL) mbar_wait(bar + B_XF1 * 8, 1);
            if (!ISV && !FIRST) cal = lds4u(sb + C_CAL);
            bar_sync(5, 256);
            if (!ISV && !FIRST) load_stamps1(st, g_flag[1], l16, w4 == 0);
        }
        asm volatile("" : "+r"(l16), "+r"(w4));
        TSX(11, w4 == 0 && (WG || ISV));
        constexpr int NR = SWAP16 ? 2 : 4;
        constexpr uint32_t OUT = SWAP16 ? WG * 4096 : 0, IN = SWAP16 ? (WG ^ 1) * 4096 : 0;
        auto give = [&]() {
#pragma unroll
            for (int j = 0; j < NR; j++) {
                if (SWAP16) stsm4(slot + OUT + l16 + j * 2048, pack2(xv[8 * j], xv[8 * j + 1]), pack2(xv[8 * j + 2], xv[8 * j + 3]),
                                  pack2(xv[8 * j + 4], xv[8 * j + 5]), pack2(xv[8 * j + 6], xv[8 * j + 7]));
                else stsm4f(slot + l16 + j * 2048, xv + 4 * j);
            }
        };
        auto take = [&](uint32_t (*r)[4]) {
#pragma unroll
            for (int j = 0; j < NR; j++) ldsm4(r[j], slot + IN + l16 + j * 2048);
        };
        auto store_tokens = [&](const uint32_t (*r)[4]) {
            uint32_t lo[4], hi[4];
#pragma unroll
            for (int j = 0; j < 4; j++) {
                if (SWAP16) {
                    const uint32_t a = r[j >> 1][(j & 1) * 2], b = r[j >> 1][(j & 1) * 2 + 1];
                    lo[j] = pack2(xk[4 * j] + bf_lo(a), xk[4 * j + 1] + bf_hi(a));
                    hi[j] = pack2(xk[4 * j + 2] + bf_lo(b), xk[4 * j + 3] + bf_hi(b));
                } else {
                    lo[j] = pack2(xk[4 * j] + __uint_as_float(r[j % NR][0]), xk[4 * j + 1] + __uint_as_float(r[j % NR][1]));
                    hi[j] = pack2(xk[4 * j + 2] + __uint_as_float(r[j % NR][2]), xk[4 * j + 3] + __uint_as_float(r[j % NR][3]));
                }
            }
            if (!ISV) {
                const uint32_t d = sb + C_QX + WG * 4096 + w4 * 1024 + l16;
                stsm4t(d, lo[0], lo[1], lo[2], lo[3]);
                stsm4t(d + 512, hi[0], hi[1], hi[2], hi[3]);
            } else {
                const uint32_t d = v_row + ((s + 1) & 1) * 10240 + ((l16 & 384) << 4) + ((l16 & 96) << 2) + ((l16 & 112) ^ v_b);
                stsm4(d, lo[0], lo[1], lo[2], lo[3]);
                stsm4(d ^ 32, hi[0], hi[1], hi[2], hi[3]);
            }
        };
        if constexpr (WG == 1) {
            if (!NOFILL) {
                wg_fence();
                products(ic<1>{}, ic<1 - HA>{}, ic<0>{}, ic<0>{}, ic<16>{}, dd[3]);
                products(ic<0>{}, ic<1 - HA>{}, ic<0>{}, ic<0>{}, ic<NK1>{}, dd[2]);
                wg_commit();
                if (ISV) bar_arrive(7, 256);
                else {
                    if (!FIRST) load_stamps1(st + 3, g_flag[1], l16, w4 == 0);
                    mbar_wait(bar + B_MBF * 8, (s + 1) & 1);
                    bar_sync(7, 256);
                }
                wg_wait<0>();
                reg_fence<16>(xv); reg_fence<16>(xk);
                give();
                bar_arrive(8, 256);
            }
            TS(12);
            if (!ISV && w4 == 0) {
                const uint4* src = &g_xmem[(s + 1) & 3][role * 512];
                if (NOFILL) mbar_wait(bar + B_MBF * 8, (s + 1) & 1);
                if (!FIRST) {
                    if (__builtin_expect(__any_sync(~0u, stamps_missing<3>(st, s)), 0)) {
                        uint32_t it = 0;
                        if (!NOFILL) { st[0] = st[3]; st[1] = st[4]; st[2] = st[5]; }
                        while (__any_sync(~0u, stamps_missing<3>(st, s))) { load_stamps1(st, g_flag[1], l16); spin_guard(it); }
                    }
                    TS(3);
                    wait_clock(latest_stamp<3>(st, cal) + DLY2);
                }
                if (hh) { if (elect()) bulk_mc(m_dst, src, 8192, m_bar, 0x2C); }
                else if (elect()) bulk_mc(m_dst, src, 8192, m_bar, 0x13);
                __syncwarp();
                TS(4);
            }
            prefetch();
            if (!NOFILL) {
                bar_sync(9, 256);
                uint32_t r[NR][4];
                take(r);
                bar_sync(14, 256);
                wg_fence();
                products(ic<0>{}, ic<1 - HA>{}, ic<0>{}, ic<NK1>{}, ic<16>{}, dd[2]);
                wg_commit();
                wg_wait<0>();
                reg_fence<16>(xk);
                TS(13);
                store_tokens(r);
                bar_arrive(10, 256);
                if (w4 != 3) bar_arrive(13, 128);
            }
        } else {
            uint32_t r[NR][4];
            if (!NOFILL) mbar_wait(bar + B_XF0 * 8, 1);
            if (!ISV && !FIRST && w4 < 2) {
                char* gd = reinterpret_cast<char*>(&g_xmem[(s + 1) & 3][0]) + (u_off + (l16 >> 2));
                const uint32_t src = sb + C_OL + w4 * 256 + l16 + (l16 & 256);
                mbar_wait(bar + B_OL * 8, s & 1);
                TSD(3);
                float a[3][4];
#pragma unroll
                for (int i = 0; i < 3; i++) ldsm4f(a[i], src + i * 1024);
                st_relaxed1(gd, movm(pack2((a[0][0] + a[0][2]) + (a[1][0] + a[1][2]) + (a[2][0] + a[2][2]),
                                           (a[0][1] + a[0][3]) + (a[1][1] + a[1][3]) + (a[2][1] + a[2][3]))));
                TS(11);
                if (w4 == 0 && l16 == 0) mbar_expect(bar + B_OL * 8, 3072);
                __syncwarp();
            }
            if (!NOFILL) {
                bar_sync(7, 256);
                TS(12);
                wg_fence();
                products(ic<1>{}, ic<1 - HA>{}, ic<0>{}, ic<0>{}, ic<16>{}, dd[3]);
                wg_commit();
                products(ic<0>{}, ic<1 - HA>{}, ic<0>{}, ic<0>{}, ic<6>{}, dd[2]);
                wg_commit();
                bar_sync(8, 256);
                take(r);
                wg_wait<1>();
                reg_fence<16>(xv);
                give();
                bar_arrive(9, 256);
                products(ic<0>{}, ic<1 - HA>{}, ic<0>{}, ic<6>{}, ic<16>{}, dd[2]);
                wg_commit();
                bar_arrive(14, 256);
                wg_wait<0>();
                reg_fence<16>(xk);
            }
            TS(13);
            if (!NOFILL) store_tokens(r);
            prefetch();
        }
    };

    if (tid == 0) TL(1, 2);
    if (w4 == 0) load_tokens(0, 1, WG);
    mbar_wait(bar + B_WS * 8, 0);
    if (WG == 1 && !NOFILL) mbar_wait(bar + B_XF1 * 8, 0);
    windows(ic<1>{});
    if (tid == 0) TL(1, 3);

#pragma unroll 1
    while (true) {
        s++;
        asm volatile("" : "+r"(l16), "+r"(a_adr), "+r"(w4));
        TS_FLUSH(WG);
        TS(0);
        float ck[4], cv[4], dk[4], dv[4];
        uint32_t b[3][4], tries = 0;
        const uint32_t kl = sb + C_KX + ((l16 & 384) << 2) + (l16 & 112);
        auto load_b = [&](auto kp) { ldsm4(b[kp.value % 3], mbw + l16 + ((kp.value & 3) ? (kp.value >> 2) * 3 + (kp.value & 3) - 1 : 12 + (kp.value >> 2)) * 512); };
        auto kpair = [&](auto kp_) {
            constexpr int kp = kp_.value, grp = kp >> 2, ph = kp & 3;
            if constexpr (kp > 0 && kp < 14) load_b(ic<kp + 2>{});
            const uint32_t* bb = b[kp % 3];
            if constexpr (ph != 0) {
                constexpr int q = (grp * 3 + ph - 1) * 2;
                static_for<(ph == 1 ? 0 : ph), ph + 1>([&](auto i) {
                    if constexpr (grp < 3) ldsm4t(pf[i.value], a_adr + C_WS + (i.value & 1) * 16384 + (grp * 2 + 2 + (i.value >> 1)) * 2048);
                });
                __syncwarp();
                mma16(cv, wv[q][0], wv[q][1], wv[q][2], wv[q][3], bb[0], bb[1]);
                mma16(ck, wk[q][0], wk[q][1], wk[q][2], wk[q][3], bb[0], bb[1]);
                mma16(dv, wv[q + 1][0], wv[q + 1][1], wv[q + 1][2], wv[q + 1][3], bb[2], bb[3]);
                mma16(dk, wk[q + 1][0], wk[q + 1][1], wk[q + 1][2], wk[q + 1][3], bb[2], bb[3]);
            } else {
                if constexpr (kp == 0) {
#pragma unroll
                    for (int i = 0; i < 4; i++) ck[i] = cv[i] = dk[i] = dv[i] = 0.f;
                }
                mma16(ck, pf[0][0], pf[0][1], pf[0][2], pf[0][3], bb[0], bb[1]);
                mma16(cv, pf[1][0], pf[1][1], pf[1][2], pf[1][3], bb[0], bb[1]);
                mma16(dk, pf[2][0], pf[2][1], pf[2][2], pf[2][3], bb[2], bb[3]);
                mma16(dv, pf[3][0], pf[3][1], pf[3][2], pf[3][3], bb[2], bb[3]);
            }
        };
        auto hand_over = [&]() {
#pragma unroll
            for (int i = 0; i < 4; i++) { cv[i] += dv[i]; ck[i] += dk[i]; }
            if (ISV) {
                stsm4f(slot + WG * 2048 + l16, cv);
            } else {
                const float *q = WG ? cv : ck, *k = WG ? ck : cv;
                stsm4t(slot + WG * 2048 + l16, pack2(q[0], q[1]), pack2(q[2], q[3]), pack2(k[0], k[1]), pack2(k[2], k[3]));
            }
        };
        auto repair = [&]() {
            bar_sync(6, 256);
            while (incomplete<8192>(mbw, l16)) {
                refetch(mbw, &g_xmem[s & 3][WG * 512], 8192, bar + (B_RT0 + WG) * 8, w4, 1 + WG, tries);
                prefetch();
                static_for<0, 3>(load_b);
                static_for<0, 16>(kpair);
                hand_over();
            }
            bar_sync(6, 256);
        };
        {
            const uint32_t can = mbw + l16 * 8 + (l16 >> 2);
            uint32_t* const flag = &g_flag[0][u_flag + WG + l16];
            for (;; tries |= 1) {
                asm volatile("" : "+r"(tries));
                if (__builtin_expect(tries, 0)) {
                    refetch(mbw, &g_xmem[s & 3][WG * 512], 8192, bar + (B_RT0 + WG) * 8, w4, 1 + WG, tries);
                }
                mbar_wait(bar + (B_MF0 + WG) * 8, s & 1);
                TS(1);
                static_for<0, 3>(load_b);
                const uint32_t c0 = lds1u(can), c1 = lds1u(can + 4096);
                const uint32_t v = ((gtick() - (ISV ? VLEAD : 0)) << 6) | s;
                kpair(ic<0>{});
                const bool early = __any_sync(~0u, max(c0, c1) == CANARY);
                st_pred1(flag, v, w4 * 512 + l16 == 1536 && !early);
                if (__builtin_expect(!early, 1)) break;
            }
            static_for<1, RFPOS>(kpair);
            if (WG == 0 && !NOFILL) bar_sync(10, 256);
            if (WG == 1 && !NOFILL && w4 == 3) {
                bar_sync(13, 128);
                if (s < NSEG - 1) load_tokens(s + 1, 1, 1);
            }
            static_for<RFPOS, 13>(kpair);
        }
        auto finish_projections = [&]() {
            static_for<13, 16>(kpair);
            hand_over();
            TS(2);
            return bar_sync_any_nan(cv[0], cv[1]);
        };
        if constexpr (!ISV) {
            const uint32_t qa = sb + C_SLOTQ + ((l16 >> 1) & 128) + ((l16 & 128) << 3) + (l16 & 112);
            const uint32_t ma = sb + C_SLOTQ + 256 + l16 + (l16 & 256);
            const uint32_t qx = sb + C_QX + l16 + (l16 & 256);
            auto ldsm_sum = [&](uint32_t* r, uint32_t a) {
                uint32_t t[4];
                ldsm4(r, a); ldsm4(t, a + 2048);
#pragma unroll
                for (int i = 0; i < 4; i++) asm("add.rn.bf16x2 %0, %0, %1;" : "+r"(r[i]) : "r"(t[i]));
            };
            auto tile = [&](float* d, const uint32_t (*q)[4], const uint32_t (*k)[4]) {
                d[0] = d[1] = d[2] = d[3] = 0.f;
#pragma unroll
                for (int i = 0; i < 4; i++) mma16(d, q[i][0], q[i][1], q[i][2], q[i][3], k[i >> 1][(i & 1) * 2], k[i >> 1][(i & 1) * 2 + 1]);
            };
            auto send = [&](int ti, const float* d, bool hold) {
                send_planes(ic<4>{}, sb_x + C_XSL + role * 2560 + ti * 512, B_XS, d, hold);
            };
            if constexpr (WG == 0) {
                auto scores = [&](auto again) {
                    bool nan = false;
                    if (w4 < 2) {
                        uint32_t k0[2][4], k1[2][4], q0[4], q1[4];
                        const uint32_t ka = kl + w4 * 256, dst = sb_v + C_SL + role * 1024 + w4 * 512;
                        ldsm4(k0[0], ka); ldsm4(k0[1], ka + 2048);
                        ldsm4(k1[0], ka + 128); ldsm4(k1[1], ka + 128 + 2048);
                        __syncwarp();
                        if (!again.value) nan = finish_projections();
                        TS(3);
                        ldsm_sum(q0, qa); ldsm_sum(q1, qa + 512);
                        float s0[4] = {0.f, 0.f, 0.f, 0.f}, s1[4] = {0.f, 0.f, 0.f, 0.f}, s2[4] = {0.f, 0.f, 0.f, 0.f}, s3[4] = {0.f, 0.f, 0.f, 0.f};
                        mma16(s0, q0[0], q0[1], q0[2], q0[3], k0[0][0], k0[0][1]);
                        mma16(s1, q0[0], q0[1], q0[2], q0[3], k0[1][0], k0[1][1]);
                        mma16(s2, q0[0], q0[1], q0[2], q0[3], k1[0][0], k1[0][1]);
                        mma16(s3, q0[0], q0[1], q0[2], q0[3], k1[1][0], k1[1][1]);
                        mma16(s0, q1[0], q1[1], q1[2], q1[3], k0[0][2], k0[0][3]);
                        mma16(s1, q1[0], q1[1], q1[2], q1[3], k0[1][2], k0[1][3]);
                        mma16(s2, q1[0], q1[1], q1[2], q1[3], k1[0][2], k1[0][3]);
                        mma16(s3, q1[0], q1[1], q1[2], q1[3], k1[1][2], k1[1][3]);
                        const float out[4] = {s0[0] + s1[2], s0[1] + s1[3], s2[0] + s3[2], s2[1] + s3[3]};
                        send_planes(ic<4>{}, dst, B_SC, out, nan);
                        if (!again.value) bar_arrive(12, 256);
                        TS(4);
                    } else if (w4 == 2) {
                        uint32_t q0[4], q1[4], km[2][4], q[4][4];
                        const uint32_t dst = sb_v + C_SL + 2048 + role * 256;
                        if (!again.value) nan = finish_projections();
                        ldsm_sum(q0, qa); ldsm_sum(km[0], ma); ldsm_sum(km[1], ma + 1024); ldsm_sum(q1, qa + 512);
                        __syncwarp();
#pragma unroll
                        for (int i = 0; i < 4; i++) ldsm4(q[i], qx + 256 + i * 1024);
                        float s0[4] = {0.f, 0.f, 0.f, 0.f}, s1[4] = {0.f, 0.f, 0.f, 0.f}, d0[4];
                        mma16(s0, q0[0], q0[1], q0[2], q0[3], km[0][0], km[0][1]);
                        mma16(s1, q0[0], q0[1], q0[2], q0[3], km[1][0], km[1][1]);
                        mma16(s0, q1[0], q1[1], q1[2], q1[3], km[0][2], km[0][3]);
                        mma16(s1, q1[0], q1[1], q1[2], q1[3], km[1][2], km[1][3]);
                        const float out[2] = {s0[0] + s1[2], s0[1] + s1[3]};
                        send_planes(ic<2>{}, dst, B_SC, out, nan);
                        if (!NOFILL) tile(d0, q, km);
                        if (!again.value) bar_sync(12, 256);
                        if (!NOFILL) send(0, d0, nan);
                    } else {
                        if (!again.value) {
                            nan = finish_projections();
                            if (s < NSEG - 1) load_tokens(s + 1, 1, 0);
                        }
                        uint32_t q[4][4], k0[2][4], k1[2][4], km[2][4];
                        float d0[4], d1[4], d2[4];
                        if (!NOFILL) {
#pragma unroll
                            for (int i = 0; i < 4; i++) ldsm4(q[i], qx + i * 1024);
                            ldsm4(k0[0], kl); ldsm4(k0[1], kl + 2048);
                            ldsm4(k1[0], kl + 128); ldsm4(k1[1], kl + 128 + 2048);
                            tile(d1, q, k0); tile(d2, q, k1);
                            ldsm_sum(km[0], ma); ldsm_sum(km[1], ma + 1024);
                            tile(d0, q, km);
                        }
                        if (!again.value) bar_sync(12, 256);
                        if (!NOFILL) { send(0, d0, nan); send(1, d1, nan); send(2, d2, nan); }
                    }
                    return nan;
                };
                if (__builtin_expect(__any_sync(~0u, scores(ic<0>{})), 0)) { repair(); scores(ic<1>{}); }
                if (__builtin_expect(s == NSEG - 1, 0)) break;
            } else {
                Stamps st1;
                load_stamps2(st1, g_flag[0], l16, w4 < 2);
                const bool nan = finish_projections();
                mbar_wait(bar + B_WS * 8, 0);
                missing = stamps_missing<6>(st1.v, s);
                target = latest_stamp<6>(st1.v, lds4u(sb + C_CAL)) + DLY1;
                if (!NOFILL) {
                    uint32_t q[4][4], k0[2][4];
                    float d1[4];
#pragma unroll
                    for (int i = 0; i < 4; i++) ldsm4(q[i], qx + 256 + i * 1024);
                    ldsm4(k0[0], kl + w4 * 128); ldsm4(k0[1], kl + w4 * 128 + 2048);
                    tile(d1, q, k0);
                    mbar_wait(bar + B_XF1 * 8, s == NSEG - 1);
                    bar_sync(12, 256);
                    send(1 + w4, d1, false);
                } else {
                    bar_sync(12, 256);
                }
                if (__builtin_expect(__any_sync(~0u, nan), 0)) repair();
                if (__builtin_expect(s == NSEG - 1, 0)) {
                    asm volatile("" : "+r"(l16));
                    if (w4 >= 2 && !NOFILL) token_softmax();
                    break;
                }
            }
        } else {
            const uint32_t lane_b = sb + C_V + w4 * 512 + ((l16 & 384) << 4) + (l16 & 112);
            auto load_values = [&](uint32_t (*vx)[4], uint32_t* vm, int ss) {
#pragma unroll
                for (int j = 0; j < 4; j++) ldsm4(vx[j], ((lane_b + (ss & 1) * 10240) ^ (j * 32)) + j * 128);
                ldsm4(vm, sb + C_V + (ss & 1) * 10240 + w4 * 512 + 8192 + (l16 ^ ((l16 >> 2) & 96)));
            };
            auto token_output = [&](int ss, auto mid) {
                uint32_t vx[4][4], vm[4];
                const uint32_t pl = sb + C_PL + (ss & 1) * 2048 + l16;
                auto lds_frag = [&](uint32_t a) { uint32_t r[4]; ldsm4(r, a); return make_uint4(r[0], r[1], r[2], r[3]); };
                load_values(vx, vm, ss);
                mid();
                uint32_t dep = 0;
#pragma unroll
                for (int mh = 1; mh >= 0; mh--) {
                    uint2 pm;
                    asm volatile("ldmatrix.sync.aligned.m8n8.x2.shared.b16 {%0,%1}, [%2];" : "=r"(pm.x), "=r"(pm.y) : "r"(pl + mh * 768 + dep) : "memory");
                    const uint4 p0 = lds_frag(pl + mh * 768 + 256);
                    float o[4][4];
#pragma unroll
                    for (int j = 0; j < 4; j++) { o[j][0] = o[j][1] = o[j][2] = o[j][3] = 0.f; mma8(o[j], pm.x, pm.y, vm[j]); }
#pragma unroll
                    for (int j = 0; j < 4; j++) mma16(o[j], p0.x, p0.y, p0.z, p0.w, vx[j][0], vx[j][1]);
                    if (mh) {
                        const uint4 p1 = lds_frag(pl + 1536);
#pragma unroll
                        for (int j = 0; j < 4; j++) mma16(o[j], p1.x, p1.y, p1.z, p1.w, vx[j][2], vx[j][3]);
                    }
                    oxp[2 * mh] = make_uint4(pack2(o[0][0], o[0][1]), pack2(o[1][0], o[1][1]), pack2(o[2][0], o[2][1]), pack2(o[3][0], o[3][1]));
                    oxp[2 * mh + 1] = make_uint4(pack2(o[0][2], o[0][3]), pack2(o[1][2], o[1][3]), pack2(o[2][2], o[2][3]), pack2(o[3][2], o[3][3]));
                    dep = oxp[2].x == ~0u ? 16 : 0;
                }
            };
            const uint32_t vd = v_row + (s & 1) * 10240 + 8192 + ((l16 & 96) << 2) + ((l16 & 112) ^ v_b ^ ((l16 & 128) >> 2));
            if (__builtin_expect(__any_sync(~0u, finish_projections()), 0)) repair();
            float r[4];
            ldsm4f(r, slot + (WG ^ 1) * 2048 + l16);
            __syncwarp();
            auto finish = [&]() {
                stsm2(vd, pack2(ck[0] + r[0], ck[1] + r[1]), pack2(ck[2] + r[2], ck[3] + r[3]));
                if (WG == 1) {
                    bar_arrive(11, 256);
                    if (w4 == 3 && l16 < 32) mbar_arrive_cluster(mapa(bar + B_VF * 8, 2 * hh + (l16 >> 4)));
                }
                TSX(3, WG == 0 && w4 == 0);
            };
            if (!NOFILL && WG == 1) {
                token_output(s - 1, [&]() { finish(); mbar_wait(bar + (B_P0 + ((s - 1) & 1)) * 8, ((s - 1) >> 1) & 1); });
                if (w4 == 1 && l16 == 0 && s > 0) mbar_expect(bar + (B_P0 + ((s - 1) & 1)) * 8, 2048);
                mbar_wait(bar + B_XF1 * 8, s == NSEG - 1);
            } else {
                finish();
            }
            if (WG == 0) bar_sync(11, 256);
            if (__builtin_expect(s == NSEG - 1, 0)) {
                bar_sync(6, 256);
                if (WG == 1) {
                    if (!NOFILL) {
                        store_ox(s - 1);
                        token_output(s, [&]() { mbar_wait(bar + (B_P0 + (s & 1)) * 8, (s >> 1) & 1); });
                        store_ox(s);
                    }
                    bar_sync(2, 128);
                    if (w4 == 0 && l16 == 0) {
                        if (NOFILL) for (int i = 0; i < 15; i++) count_up(CNT_OX + i);
                        count_up(CNT_OX + 15);
                    }
                    __syncwarp();
                }
                mbar_wait(bar + B_SC * 8, s & 1);
                break;
            }
            if constexpr (WG == 0) {
                uint32_t vx[4][4], vm[4];
                load_values(vx, vm, s);
                const uint32_t oo = u_off + ((l16 & 48) << 3) + ((l16 >> 2) & 112);
                char* dst = reinterpret_cast<char*>(&g_xo[s & 3][0]) + oo;
                if (w4 == 3) load_tokens(s + 1, 1, 0);
                mbar_wait(bar + B_SC * 8, s & 1);
                TS(4);
                float a0[4], b0[4], a1[4], b1[4], a2[4];
                ldsm4f(a0, sb + C_SL + l16); ldsm4f(b0, sb + C_SL + 1024 + l16);
                ldsm4f(a1, sb + C_SL + 512 + l16); ldsm4f(b1, sb + C_SL + 1536 + l16);
                ldsm4f(a2, sb + C_SL + 2048 + l16);
                const float e[10] = {a0[0] + b0[0], a0[1] + b0[1], a0[2] + b0[2], a0[3] + b0[3], a1[0] + b1[0], a1[1] + b1[1], a1[2] + b1[2], a1[3] + b1[3],
                                     a2[0] + a2[2], a2[1] + a2[3]};
                float m = fmaxf(fmaxf(fmaxf(e[0], e[1]), fmaxf(e[2], e[3])), fmaxf(fmaxf(e[4], e[5]), fmaxf(e[6], e[7])));
                m = fmaxf(m, fmaxf(e[8], e[9]));
                m = fmaxf(fmaxf(m, __shfl_xor_sync(~0u, m, 1)), fmaxf(__shfl_xor_sync(~0u, m, 2), __shfl_xor_sync(~0u, m, 3)));
                m *= -SM_SCALE;
                float x[10];
#pragma unroll
                for (int i = 0; i < 10; i++) x[i] = ex2(fmaf(e[i], SM_SCALE, m));
                float o[4][4];
                const uint32_t p0 = pack2(x[0], x[1]), p1 = pack2(x[2], x[3]), j0 = __float_as_uint(x[1]), j1 = __float_as_uint(x[3]);
#pragma unroll
                for (int j = 0; j < 4; j++) { o[j][0] = o[j][1] = o[j][2] = o[j][3] = 0.f; mma16(o[j], p0, j0, p1, j1, vx[j][0], vx[j][1]); }
                const uint32_t p2 = pack2(x[4], x[5]), p3 = pack2(x[6], x[7]), j2 = __float_as_uint(x[5]), j3 = __float_as_uint(x[7]);
#pragma unroll
                for (int j = 0; j < 4; j++) mma16(o[j], p2, j2, p3, j3, vx[j][2], vx[j][3]);
                const uint32_t p4 = pack2(x[8], x[9]), j4 = __float_as_uint(x[9]);
                float l = (((x[0] + x[1]) + (x[2] + x[3])) + ((x[4] + x[5]) + (x[6] + x[7]))) + (x[8] + x[9]);
                l = (l + __shfl_xor_sync(~0u, l, 1)) + (__shfl_xor_sync(~0u, l, 2) + __shfl_xor_sync(~0u, l, 3));
#pragma unroll
                for (int j = 0; j < 4; j++) mma8(o[j], p4, j4, vm[j]);
                l = rcp(l);
                st_relaxed4(reinterpret_cast<uint4*>(dst), make_uint4(pack2(o[0][0] * l, o[0][1] * l), pack2(o[1][0] * l, o[1][1] * l),
                                                                      pack2(o[2][0] * l, o[2][1] * l), pack2(o[3][0] * l, o[3][1] * l)));
                bar_arrive(3, 256);
                if (w4 == 0 && l16 == 0) mbar_expect(bar + B_SC * 8, 2560);
            }
        }
        windows(ic<0>{});
    }
}

__global__ void __cluster_dims__(6, 1, 1) __launch_bounds__(256, 1)
chain_kernel(const __grid_constant__ CUtensorMap tq, const __grid_constant__ CUtensorMap tk, const __grid_constant__ CUtensorMap tv,
             const __grid_constant__ CUtensorMap two, const __grid_constant__ Descs D, const __grid_constant__ Descs DV,
             const __nv_bfloat16* __restrict__ x, const __nv_bfloat16* __restrict__ mem0) {
    extern __shared__ __align__(1024) uint8_t smem[];
    const uint32_t sb = smem_u32(smem);
    const int rank = blockIdx.x % 6, cl = blockIdx.x / 6, role = rank >= 4 ? 2 : rank & 1;
    const int tid = threadIdx.x, lane = tid & 31, gw = blockIdx.x * 8 + uni(tid >> 5);
    const CUtensorMap *tA = role == 2 ? &tv : &tq, *tB = role == 2 ? &tv : &tk;
    uint4 cur[4], nxt[4];
#pragma unroll
    for (int j = 0; j < 4; j++) {
        cur[j] = reinterpret_cast<const uint4*>(x)[gw * 128 + j * 32 + lane];
        nxt[j] = reinterpret_cast<const uint4*>(x)[(gw + 768) * 128 + j * 32 + lane];
    }
    if (gw < 512 && lane < 16) asm volatile("prefetch.global.L2 [%0];" :: "l"(x + (gw + 1536) * DM + lane * 64));
    if (threadIdx.x == 0) {
        TL(1, 0); TLSM(1);
        if ((sb & 0xFFFFFF) != SB0 || mapa(sb, 5) != (SB0 | 0x5000000u)) __trap();
        const uint32_t bar = sb + C_BAR;
        for (int i = 0; i < B_NUM; i++) mbar_init(bar + i * 8, i == B_MBF ? 12 : (i == B_GO ? 4 : 1));
        mbar_expect(bar + B_MF0 * 8, 8192);
        mbar_expect(bar + B_MF1 * 8, 8192);
        if (role == 2) {
            mbar_expect(bar + B_SC * 8, 2560);
            mbar_expect(bar + B_P0 * 8, 2048);
            mbar_expect(bar + B_P1 * 8, 2048);
            mbar_expect(bar + B_OF * 8, ONKV * (256 + 2048));
        } else {
            mbar_expect(bar + B_XS * 8, role ? 5120 : 3072);
            mbar_expect(bar + B_OL * 8, 3072);
            mbar_expect(bar + B_OF * 8, ONKQ * (256 + 2048));
        }
        asm volatile("fence.mbarrier_init.release.cluster;" ::: "memory");
        fence_async();
        for (int j = 0; j < 3; j++) load_chunk(tA, tB, cl, rank, sb + j * 65536, j, bar + (B_W0 + j) * 8);
    }
    __syncwarp();
    asm volatile("barrier.cluster.arrive.release.aligned;" ::: "memory");
    reset_exchange(mem0);
#pragma unroll 1
    for (int row = gw; row < SEQ; row += 768) {
        uint4 v[4];
#pragma unroll
        for (int j = 0; j < 4; j++) {
            v[j] = cur[j]; cur[j] = nxt[j];
            if (row + 1536 < SEQ) nxt[j] = reinterpret_cast<const uint4*>(x)[(row + 1536) * 128 + j * 32 + lane];
        }
        ln_row(v, row, lane);
    }
    if (tid == 0) TL(1, 5);
    __syncthreads();
    uint32_t goal = 0;
    if (tid == 160) {
        __threadfence();
        goal = (atomicAdd(&g_epoch, 1u) / 96 + 1) * 96;
        asm volatile("griddepcontrol.launch_dependents;" ::: "memory");
        TL(1, 4);
    }
    __syncwarp();
    asm volatile("barrier.cluster.wait.acquire.aligned;" ::: "memory");
    goal = uni(goal);
    const int wg = uni(threadIdx.x >> 7);
    if (role == 2) {
        if (wg == 0) chain_main<true, 0>(&tv, &tv, &two, sb, cl, rank, DV, goal);
        else chain_main<true, 1>(&tv, &tv, &two, sb, cl, rank, DV, goal);
    } else {
        if (wg == 0) chain_main<false, 0>(&tq, &tk, &two, sb, cl, rank, D, goal);
        else chain_main<false, 1>(&tq, &tk, &two, sb, cl, rank, D, goal);
    }
    __syncwarp();
    cluster_sync();
    if (threadIdx.x == 0) TL(1, 1);
}

__device__ __forceinline__ void wg256(float* d, uint32_t da, uint32_t db, uint32_t accum) {
    asm volatile("{\n.reg .b64 da, db;\n.reg .pred p;\nsetp.ne.u32 p, %130, 0;\nmov.b64 da, {%128, " DESC_HI_SW128 "};\nmov.b64 db, {%129, " DESC_HI_SW128 "};\n"
                 "wgmma.mma_async.sync.aligned.m64n256k16.f32.bf16.bf16 {"
                 "%0,%1,%2,%3,%4,%5,%6,%7,%8,%9,%10,%11,%12,%13,%14,%15,%16,%17,%18,%19,%20,%21,%22,%23,%24,%25,%26,%27,%28,%29,%30,%31,"
                 "%32,%33,%34,%35,%36,%37,%38,%39,%40,%41,%42,%43,%44,%45,%46,%47,%48,%49,%50,%51,%52,%53,%54,%55,%56,%57,%58,%59,%60,%61,%62,%63,"
                 "%64,%65,%66,%67,%68,%69,%70,%71,%72,%73,%74,%75,%76,%77,%78,%79,%80,%81,%82,%83,%84,%85,%86,%87,%88,%89,%90,%91,%92,%93,%94,%95,"
                 "%96,%97,%98,%99,%100,%101,%102,%103,%104,%105,%106,%107,%108,%109,%110,%111,%112,%113,%114,%115,%116,%117,%118,%119,%120,%121,%122,%123,%124,%125,%126,%127"
                 "}, da, db, p, 1, 1, 0, 1;\n}"
                 : ACC16(d), ACC16((d + 16)), ACC16((d + 32)), ACC16((d + 48)), ACC16((d + 64)), ACC16((d + 80)), ACC16((d + 96)), ACC16((d + 112))
                 : "r"(da), "r"(db), "r"(accum));
}
__device__ __forceinline__ void wg128(float* d, uint32_t da, uint32_t db, uint32_t accum) {
    asm volatile("{\n.reg .b64 da, db;\n.reg .pred p;\nsetp.ne.u32 p, %66, 0;\nmov.b64 da, {%64, " DESC_HI_SW128 "};\nmov.b64 db, {%65, " DESC_HI_SW128 "};\n"
                 "wgmma.mma_async.sync.aligned.m64n128k16.f32.bf16.bf16 {"
                 "%0,%1,%2,%3,%4,%5,%6,%7,%8,%9,%10,%11,%12,%13,%14,%15,%16,%17,%18,%19,%20,%21,%22,%23,%24,%25,%26,%27,%28,%29,%30,%31,"
                 "%32,%33,%34,%35,%36,%37,%38,%39,%40,%41,%42,%43,%44,%45,%46,%47,%48,%49,%50,%51,%52,%53,%54,%55,%56,%57,%58,%59,%60,%61,%62,%63"
                 "}, da, db, p, 1, 1, 0, 1;\n}"
                 : ACC16(d), ACC16((d + 16)), ACC16((d + 32)), ACC16((d + 48))
                 : "r"(da), "r"(db), "r"(accum));
}
__device__ __forceinline__ float sigmoidf_(float v) { return rcp(1.f + ex2(-1.4426950408889634f * v)); }
__device__ __forceinline__ void wait_count(int idx, uint32_t n) {
    uint32_t v, it = 0;
    while (true) {
        asm volatile("ld.acquire.gpu.global.u32 %0, [%1];" : "=r"(v) : "l"(&g_cnt[idx * 8]) : "memory");
        if (v >= n) break;
        __nanosleep(100);
        spin_guard(it);
    }
    asm volatile("fence.proxy.async.global;" ::: "memory");
}

constexpr int G_STAGES = 4, G_PAIRS = 18;
constexpr uint32_t G_STAGE = 49152, G_EPI = G_STAGES * G_STAGE, G_BAR = G_EPI + 32768, G_SMEM = G_BAR + 256;
__device__ __forceinline__ int glu_job(int p, int j) {
    if (j < 12) return j * G_PAIRS + p;
    if (p < 14) return j == 12 ? 224 + p : (j == 13 ? 242 + p : -1);
    return j < 14 ? 216 + (j - 12) * 4 + (p - 14) : (j == 14 ? 224 + p : -1);
}

__global__ void __cluster_dims__(2, 1, 1) __launch_bounds__(384, 1)
glu_kernel(const __grid_constant__ CUtensorMap tXn, const __grid_constant__ CUtensorMap tG, const __grid_constant__ CUtensorMap tU,
           const __grid_constant__ CUtensorMap tHst, const __grid_constant__ CUtensorMap tHld, const __grid_constant__ CUtensorMap tD,
           const __grid_constant__ CUtensorMap tYst) {
    extern __shared__ __align__(1024) uint8_t smem[];
    const uint32_t sb = smem_u32(smem);
    const uint32_t full = sb + G_BAR, empty = full + 64;
    const int tid = threadIdx.x, lane = tid & 31;
    const int warp = uni(tid >> 5), wg = warp >> 2;
    const int rank = blockIdx.x & 1, pair = blockIdx.x >> 1;
    asm volatile("griddepcontrol.launch_dependents;" ::: "memory");
    if (tid == 0) {
        TL(2, 0); TLSM(2);
        for (int i = 0; i < G_STAGES; i++) { mbar_init(full + i * 8, 1); mbar_init(empty + i * 8, 16); }
        asm volatile("fence.mbarrier_init.release.cluster;" ::: "memory");
        fence_async();
    }
    __syncthreads();
    cluster_sync();
    if (wg == 0) {
        asm volatile("setmaxnreg.dec.sync.aligned.u32 40;");
        if (warp == 0) {
            if (lane == 0) {
                uint32_t st = 0, ph = 1;
                asm volatile("fence.acq_rel.gpu;\nfence.proxy.async.global;" ::: "memory");
                for (int j = 0, job; (job = glu_job(pair, j)) >= 0; j++) {
                    const bool dn = job >= 224;
                    const int mp = dn ? (job - 224) >> 2 : job / 28, nt = dn ? job & 3 : job % 28, rb = mp * 2 + rank;
                    const CUtensorMap* tA = dn ? &tHld : &tXn;
                    const CUtensorMap* tB = dn ? &tD : (rank ? &tU : &tG);
                    const int bcol = dn ? nt * 256 + rank * 128 : nt * 128, nkb = dn ? FF / 64 : DM / 64;
                    if (j == 12) TL(2, 2);
                    if (dn) wait_count(CNT_H + rb, 56);
                    for (int kb = 0; kb < nkb; kb++) {
                        mbar_wait(empty + st * 8, ph);
                        const uint32_t base = sb + st * G_STAGE;
                        mbar_expect(full + st * 8, G_STAGE);
                        tma2d(base, tA, kb * 64, rb * 128, full + st * 8);
                        tma2d_mc(base + 16384 + rank * 16384, tB, bcol, kb * 64, full + st * 8, 3);
                        tma2d_mc(base + 16384 + rank * 16384 + 8192, tB, bcol + 64, kb * 64, full + st * 8, 3);
                        if (++st == G_STAGES) { st = 0; ph ^= 1; }
                    }
                }
            }
        } else if (warp < 3) {
            const int cw = warp - 1;
            const uint32_t epi = sb + G_EPI + cw * 16384;
            bar_arrive(3 + cw, 160);
            for (int j = 0, job; (job = glu_job(pair, j)) >= 0; j++) {
                const bool dn = job >= 224;
                const int mp = dn ? (job - 224) >> 2 : job / 28, nt = dn ? job & 3 : job % 28, rb = mp * 2 + rank;
                for (int hp = 0; hp <= (int)dn; hp++) {
                    bar_sync(1 + cw, 160);
                    if (lane == 0) {
                        const int col = dn ? nt * 256 + hp * 128 : nt * 128;
                        tma2d_store(dn ? &tYst : &tHst, col, rb * 128 + cw * 64, epi);
                        tma2d_store(dn ? &tYst : &tHst, col + 64, rb * 128 + cw * 64, epi + 8192);
                        asm volatile("cp.async.bulk.commit_group;\ncp.async.bulk.wait_group.read 0;" ::: "memory");
                    }
                    __syncwarp();
                    bar_arrive(3 + cw, 160);
                    if (lane == 0) {
                        asm volatile("cp.async.bulk.wait_group 0;\nfence.proxy.async.global;" ::: "memory");
                        count_up(dn ? CNT_Y + rb * 8 + nt * 2 + hp : CNT_H + rb);
                    }
                    __syncwarp();
                }
            }
        }
        cluster_sync();
    } else {
        asm volatile("setmaxnreg.inc.sync.aligned.u32 232;");
        const int cw = wg - 1, w4 = warp & 3;
        const uint32_t empty_dst = mapa(empty, lane & 1);
        const int er = w4 * 16 + (lane & 15), ec = lane >> 4;
        const uint32_t epi = sb + G_EPI + cw * 16384 + er * 128;
        uint32_t st = 0, ph = 0;
        float acc[128];
        auto put = [&](const uint32_t* o) {
            bar_sync(3 + cw, 160);
#pragma unroll
            for (int q = 0; q < 8; q++) stsm4(epi + (q >> 2) * 8192 + (((2 * (q & 3) + ec) ^ (er & 7)) << 4), o[q * 4], o[q * 4 + 1], o[q * 4 + 2], o[q * 4 + 3]);
            fence_async();
            bar_arrive(1 + cw, 160);
        };
        for (int j = 0, job; (job = glu_job(pair, j)) >= 0; j++) {
            const bool dn = job >= 224;
            const int nkb = dn ? FF / 64 : DM / 64;
            uint32_t prev = 0;
#pragma unroll 1
            for (int kb = 0; kb < nkb; kb++) {
                mbar_wait(full + st * 8, ph);
                const uint32_t base = sb + st * G_STAGE;
                const uint32_t da = (((base + cw * 8192) & 0x3FFFF) >> 4) | (1u << 16);
                const uint32_t db = (((base + 16384) & 0x3FFFF) >> 4) | (512u << 16);
                wg_fence();
#pragma unroll
                for (int k = 0; k < 4; k++) wg256(acc, da + k * 2, db + k * 128, (kb | k) != 0);
                wg_commit();
                if (kb > 0) {
                    wg_wait<1>();
                    if (lane < 2) mbar_arrive_cluster(empty_dst + prev * 8);
                }
                prev = st;
                if (++st == G_STAGES) { st = 0; ph ^= 1; }
            }
            wg_wait<0>();
            reg_fence<128>(acc);
            if (lane < 2) mbar_arrive_cluster(empty_dst + prev * 8);
            uint32_t o[32];
            if (!dn) {
#pragma unroll
                for (int i = 0; i < 32; i++) o[i] = pack2(sigmoidf_(acc[2 * i]) * acc[64 + 2 * i], sigmoidf_(acc[2 * i + 1]) * acc[65 + 2 * i]);
                put(o);
            } else {
#pragma unroll
                for (int hp = 0; hp < 2; hp++) {
#pragma unroll
                    for (int i = 0; i < 32; i++) {
                        const float a = acc[hp * 64 + 2 * i], b = acc[hp * 64 + 2 * i + 1];
                        o[i] = pack2(sigmoidf_(a) * a, sigmoidf_(b) * b);
                    }
                    put(o);
                }
            }
        }
        bar_sync(3 + cw, 160);
        if (tid == 128) TL(2, 1);
        cluster_sync();
    }
}

constexpr int O_STAGES = 7;
constexpr uint32_t O_STAGE = 32768, O_BAR = O_STAGES * O_STAGE, O_SMEM = O_BAR + 256;

__global__ void __cluster_dims__(2, 1, 1) __launch_bounds__(384, 1)
out_kernel(const __grid_constant__ CUtensorMap tOx, const __grid_constant__ CUtensorMap tWo, const __grid_constant__ CUtensorMap tX,
           const __grid_constant__ CUtensorMap tY, const __grid_constant__ CUtensorMap tOut) {
    extern __shared__ __align__(1024) uint8_t smem[];
    const uint32_t sb = smem_u32(smem);
    const uint32_t full = sb + O_BAR, empty = full + 64;
    const int tid = threadIdx.x, lane = tid & 31;
    const int warp = uni(tid >> 5), wg = warp >> 2;
    const int rank = blockIdx.x & 1, nt = (blockIdx.x >> 1) & 7, rb = (blockIdx.x >> 4) * 2 + rank;
    constexpr int NKB = HD / 64;
    if (tid == 0) {
        TL(3, 0); TLSM(3);
        for (int i = 0; i < O_STAGES; i++) { mbar_init(full + i * 8, 1); mbar_init(empty + i * 8, 16); }
        asm volatile("fence.mbarrier_init.release.cluster;" ::: "memory");
        fence_async();
    }
    __syncthreads();
    cluster_sync();
    if (wg == 0) {
        if (tid == 0) {
            uint32_t st = 0, ph = 1;
            for (int kb = 0; kb < O_STAGES; kb++) {
                mbar_expect(full + kb * 8, O_STAGE);
                tma2d_mc(sb + kb * O_STAGE + 16384 + rank * 8192, &tWo, nt * 128 + rank * 64, kb * 64, full + kb * 8, 3);
            }
            wait_count(CNT_OX + rb, 32);
            TL(3, 2);
            for (int kb = 0; kb < NKB + 2; kb++) {
                const uint32_t base = sb + st * O_STAGE;
                if (kb >= O_STAGES) {
                    mbar_wait(empty + st * 8, ph);
                    mbar_expect(full + st * 8, O_STAGE);
                }
                if (kb < NKB) {
                    tma2d(base, &tOx, kb * 64, rb * 128, full + st * 8);
                    if (kb >= O_STAGES) tma2d_mc(base + 16384 + rank * 8192, &tWo, nt * 128 + rank * 64, kb * 64, full + st * 8, 3);
                } else {
                    if (kb == NKB) wait_count(CNT_Y + rb * 8 + nt, 2);
                    tma2d(base, &tX, nt * 128 + (kb - NKB) * 64, rb * 128, full + st * 8);
                    tma2d(base + 16384, &tY, nt * 128 + (kb - NKB) * 64, rb * 128, full + st * 8);
                }
                if (++st == O_STAGES) { st = 0; ph ^= 1; }
            }
        }
        __syncwarp();
    } else {
        const int cw = wg - 1, w4 = warp & 3;
        const uint32_t empty_dst = mapa(empty, lane & 1);
        const int er = cw * 64 + w4 * 16 + (lane & 15), ec = lane >> 4;
        uint32_t st = 0, ph = 0, prev = 0;
        float acc[64];
#pragma unroll 1
        for (int kb = 0; kb < NKB; kb++) {
            mbar_wait(full + st * 8, ph);
            const uint32_t base = sb + st * O_STAGE;
            const uint32_t da = (((base + cw * 8192) & 0x3FFFF) >> 4) | (1u << 16);
            const uint32_t db = (((base + 16384) & 0x3FFFF) >> 4) | (512u << 16);
            wg_fence();
#pragma unroll
            for (int k = 0; k < 4; k++) wg128(acc, da + k * 2, db + k * 128, (kb | k) != 0);
            wg_commit();
            if (kb > 0) {
                wg_wait<1>();
                if (lane < 2) mbar_arrive_cluster(empty_dst + prev * 8);
            }
            prev = st;
            if (++st == O_STAGES) { st = 0; ph ^= 1; }
        }
        wg_wait<0>();
        reg_fence<64>(acc);
#pragma unroll
        for (int bx = 0; bx < 2; bx++) {
            mbar_wait(full + st * 8, ph);
            const uint32_t base = sb + st * O_STAGE;
#pragma unroll
            for (int j = 0; j < 4; j++) {
                uint32_t xv[4], yv[4];
                const uint32_t ad = base + er * 128 + (((2 * j + ec) ^ (er & 7)) << 4);
                ldsm4(xv, ad); ldsm4(yv, ad + 16384);
                const float* a = acc + bx * 32 + j * 8;
#pragma unroll
                for (int i = 0; i < 4; i++)
                    xv[i] = pack2(fmaf(a[2 * i], bf_lo(yv[i]), bf_lo(xv[i])), fmaf(a[2 * i + 1], bf_hi(yv[i]), bf_hi(xv[i])));
                stsm4(ad, xv[0], xv[1], xv[2], xv[3]);
            }
            fence_async();
            bar_sync(1 + cw, 128);
            if ((tid & 127) == 0) {
                tma2d_store(&tOut, nt * 128 + bx * 64, rb * 128 + cw * 64, base + cw * 8192);
                asm volatile("cp.async.bulk.commit_group;" ::: "memory");
            }
            if (++st == O_STAGES) { st = 0; ph ^= 1; }
        }
        if ((tid & 127) == 0) asm volatile("cp.async.bulk.wait_group 0;" ::: "memory");
        if (tid == 128) TL(3, 1);
        __syncwarp();
    }
    cluster_sync();
}

typedef CUresult (*EncodeFn)(CUtensorMap*, CUtensorMapDataType, cuuint32_t, void*, const cuuint64_t*, const cuuint64_t*, const cuuint32_t*,
                             const cuuint32_t*, CUtensorMapInterleave, CUtensorMapSwizzle, CUtensorMapL2promotion, CUtensorMapFloatOOBfill);

CUtensorMap make_map(EncodeFn enc, const void* p, int rows, int cols, int box_rows) {
    CUtensorMap m;
    cuuint64_t dims[2] = {(cuuint64_t)cols, (cuuint64_t)rows}, strides[1] = {(cuuint64_t)cols * 2};
    cuuint32_t box[2] = {64, (cuuint32_t)box_rows}, es[2] = {1, 1};
    enc(&m, CU_TENSOR_MAP_DATA_TYPE_BFLOAT16, 2, const_cast<void*>(p), dims, strides, box, es, CU_TENSOR_MAP_INTERLEAVE_NONE,
        CU_TENSOR_MAP_SWIZZLE_128B, CU_TENSOR_MAP_L2_PROMOTION_L2_128B, CU_TENSOR_MAP_FLOAT_OOB_FILL_NONE);
    return m;
}

}

#define PDL 7
extern "C" void kernel_launch(void* const* d_in, const int* in_sizes, int n_in, void* d_out, int out_size) {
    const __nv_bfloat16* x = (const __nv_bfloat16*)d_in[0];
    const __nv_bfloat16* mem0 = (const __nv_bfloat16*)d_in[1];
    void* fn = nullptr;
    cudaDriverEntryPointQueryResult qr;
    cudaGetDriverEntryPoint("cuTensorMapEncodeTiled", &fn, cudaEnableDefault, &qr);
    EncodeFn enc = (EncodeFn)fn;
    void *xn, *ox, *h, *y;
    cudaGetSymbolAddress(&xn, g_xn); cudaGetSymbolAddress(&ox, g_ox); cudaGetSymbolAddress(&h, g_h); cudaGetSymbolAddress(&y, g_y);

    const CUtensorMap tq = make_map(enc, d_in[2], DM, HD, 128), tk = make_map(enc, d_in[3], DM, HD, 128), tv = make_map(enc, d_in[4], DM, HD, 128);
    const CUtensorMap two16 = make_map(enc, d_in[5], HD, DM, 16);
    const CUtensorMap txn128 = make_map(enc, xn, SEQ, DM, 128), tg = make_map(enc, d_in[8], DM, FF, 64), tu = make_map(enc, d_in[9], DM, FF, 64);
    const CUtensorMap th64 = make_map(enc, h, SEQ, FF, 64), th128 = make_map(enc, h, SEQ, FF, 128), td = make_map(enc, d_in[10], FF, DM, 64);
    const CUtensorMap ty64 = make_map(enc, y, SEQ, DM, 64), ty128 = make_map(enc, y, SEQ, DM, 128), tx128 = make_map(enc, x, SEQ, DM, 128);
    const CUtensorMap tox = make_map(enc, ox, SEQ, HD, 128), two64 = make_map(enc, d_in[5], HD, DM, 64), tout = make_map(enc, d_out, SEQ, DM, 64);

    cudaFuncSetAttribute(chain_kernel, cudaFuncAttributeMaxDynamicSharedMemorySize, C_SMEM);
    cudaFuncSetAttribute(glu_kernel, cudaFuncAttributeMaxDynamicSharedMemorySize, G_SMEM);
    cudaFuncSetAttribute(out_kernel, cudaFuncAttributeMaxDynamicSharedMemorySize, O_SMEM);

    Descs D;
    for (int i = 0; i < 4; i++) D.sw[i] = DSW;
    D.ns = DNS;
    cudaStream_t st = cudaStreamPerThread;
    cudaLaunchAttribute at;
    at.id = cudaLaunchAttributeProgrammaticStreamSerialization;
    at.val.programmaticStreamSerializationAllowed = 1;
    cudaLaunchConfig_t cfg = {};
    cfg.stream = st; cfg.attrs = &at; cfg.numAttrs = 0;
    cfg.gridDim = dim3(96); cfg.blockDim = dim3(256); cfg.dynamicSmemBytes = C_SMEM;
    cudaLaunchKernelEx(&cfg, chain_kernel, tq, tk, tv, two16, D, D, x, mem0);
    cfg.gridDim = dim3(2 * G_PAIRS); cfg.blockDim = dim3(384); cfg.dynamicSmemBytes = G_SMEM; cfg.numAttrs = (PDL >> 1) & 1;
    cudaLaunchKernelEx(&cfg, glu_kernel, txn128, tg, tu, th64, th128, td, ty64);
    cfg.gridDim = dim3(128); cfg.dynamicSmemBytes = O_SMEM; cfg.numAttrs = (PDL >> 2) & 1;
    cudaLaunchKernelEx(&cfg, out_kernel, tox, two64, tx128, ty128, tout);
}
```

```cpp
#include <cuda_runtime.h>
#include <cuda_bf16.h>
#include <cuda.h>
#include <stdint.h>
#include <type_traits>

namespace {

constexpr int SEQ = 2048, DM = 1024, HD = 4096, FF = 3584, NSEG = 64;

__device__ __align__(1024) __nv_bfloat16 g_xn[SEQ * DM];
__device__ __align__(1024) uint4 g_xc[SEQ * DM / 8];
__device__ __align__(1024) __nv_bfloat16 g_ox[SEQ * HD];
__device__ __align__(1024) __nv_bfloat16 g_h[SEQ * FF];
__device__ __align__(1024) __nv_bfloat16 g_y[SEQ * DM];
__device__ __align__(1024) uint4 g_xmem[4][1024];
__device__ __align__(1024) uint4 g_xo[4][4096];
#define FSTR 8
__device__ __align__(1024) uint32_t g_flag[2][96 * FSTR];
enum { CNT_H = 0, CNT_OX = 16, CNT_Y = 32, CNT_NUM = 160 };
__device__ __align__(1024) uint32_t g_cnt[CNT_NUM * 8];
__device__ __align__(128) uint32_t g_epoch;
#define TL(k, i)
#define TLSM(k)

__device__ __forceinline__ uint32_t smem_u32(const void* p) { return (uint32_t)__cvta_generic_to_shared(p); }
__device__ __forceinline__ uint32_t mapa(uint32_t a, uint32_t r) {
    uint32_t o; asm("mapa.shared::cluster.u32 %0, %1, %2;" : "=r"(o) : "r"(a), "r"(r)); return o;
}
__device__ __forceinline__ void mbar_init(uint32_t a, uint32_t cnt) {
    asm volatile("mbarrier.init.shared.b64 [%0], %1;" :: "r"(a), "r"(cnt) : "memory");
}
__device__ __forceinline__ void mbar_expect(uint32_t a, uint32_t bytes) {
    asm volatile("mbarrier.arrive.expect_tx.shared.b64 _, [%0], %1;" :: "r"(a), "r"(bytes) : "memory");
}
__device__ __forceinline__ void mbar_arrive_cluster(uint32_t a) {
    asm volatile("mbarrier.arrive.shared::cluster.b64 _, [%0];" :: "r"(a) : "memory");
}
__device__ __forceinline__ void spin_guard(uint32_t& it) {
    asm volatile("{\n.reg .pred p;\nadd.u32 %0, %0, 1;\nsetp.gt.u32 p, %0, 0x400000;\n@p st.shared.u32 [%0], %0;\n}" : "+r"(it));
}
__device__ __forceinline__ void mbar_wait(uint32_t a, uint32_t par) {
    asm volatile("{\n.reg .pred p;\n.reg .u32 i;\nmov.u32 i, 0;\n"
                 "WL:\nadd.u32 i, i, 1;\nsetp.gt.u32 p, i, 0x400000;\n@p st.shared.u32 [i], i;\n"
                 "mbarrier.try_wait.parity.shared::cta.b64 p, [%0], %1;\n@!p bra WL;\n}" :: "r"(a), "r"(par) : "memory");
}
__device__ __forceinline__ void mbar_arrive(uint32_t a) { asm volatile("mbarrier.arrive.shared.b64 _, [%0];" :: "r"(a) : "memory"); }
__device__ __forceinline__ void tma2d(uint32_t dst, const CUtensorMap* m, int c0, int c1, uint32_t bar) {
    asm volatile("cp.async.bulk.tensor.2d.shared::cluster.global.mbarrier::complete_tx::bytes [%0], [%1, {%3, %4}], [%2];"
                 :: "r"(dst), "l"(m), "r"(bar), "r"(c0), "r"(c1) : "memory");
}
__device__ __forceinline__ void tma2d_mc(uint32_t dst, const CUtensorMap* m, int c0, int c1, uint32_t bar, uint16_t mask) {
    asm volatile("cp.async.bulk.tensor.2d.shared::cluster.global.mbarrier::complete_tx::bytes.multicast::cluster [%0], [%1, {%3, %4}], [%2], %5;"
                 :: "r"(dst), "l"(m), "r"(bar), "r"(c0), "r"(c1), "h"(mask) : "memory");
}
__device__ __forceinline__ void bulk_mc(uint32_t dst, const void* src, uint32_t bytes, uint32_t bar, uint16_t mask) {
    asm volatile("cp.async.bulk.shared::cluster.global.mbarrier::complete_tx::bytes.multicast::cluster [%0], [%1], %2, [%3], %4;"
                 :: "r"(dst), "l"(src), "r"(bytes), "r"(bar), "h"(mask) : "memory");
}
__device__ __forceinline__ void bulk_ld(uint32_t dst, const void* src, uint32_t bytes, uint32_t bar) {
    asm volatile("cp.async.bulk.shared::cluster.global.mbarrier::complete_tx::bytes [%0], [%1], %2, [%3];"
                 :: "r"(dst), "l"(src), "r"(bytes), "r"(bar) : "memory");
}
__device__ __forceinline__ uint32_t gtick() { uint64_t c; asm volatile("mov.u64 %0, %%globaltimer;" : "=l"(c)); return (uint32_t)c >> 5; }
__device__ __forceinline__ uint32_t gtick_dep(uint32_t zero) {
    uint32_t c;
    asm volatile("{\n.reg .pred p;\nsetp.eq.u32 p, %1, 0;\nmov.u32 %0, 0;\n@p mov.u32 %0, %%globaltimer_lo;\n}" : "=r"(c) : "r"(zero));
    return c >> 5;
}
__device__ __forceinline__ uint32_t ld_relaxed1(const void* p) {
    uint32_t v; asm volatile("ld.relaxed.gpu.global.u32 %0, [%1];" : "=r"(v) : "l"(p) : "memory"); return v;
}
__device__ __forceinline__ bool any_nan(float a, float b) {
    uint32_t r;
    asm volatile("{\n.reg .pred p;\nsetp.nan.f32 p, %1, %2;\nvote.sync.any.pred p, p, 0xffffffff;\nselp.u32 %0, 1, 0, p;\n}" : "=r"(r) : "f"(a), "f"(b));
    return r;
}
__device__ __forceinline__ bool bar_sync_any_nan(float a, float b) {
    uint32_t r;
    asm volatile("{\n.reg .pred p;\nsetp.nan.f32 p, %1, %2;\nbarrier.cta.red.or.aligned.pred p, 6, 256, p;\nselp.u32 %0, 1, 0, p;\n}"
                 : "=r"(r) : "f"(a), "f"(b) : "memory");
    return r;
}
__device__ __forceinline__ void bar_arrive(int id, int n) { asm volatile("bar.arrive %0, %1;" :: "r"(id), "r"(n) : "memory"); }
__device__ __forceinline__ uint32_t clk() { uint64_t c; asm volatile("mov.u64 %0, %%clock64;" : "=l"(c)); return (uint32_t)c; }
__device__ __forceinline__ void tma2d_store(const CUtensorMap* m, int c0, int c1, uint32_t src) {
    asm volatile("cp.async.bulk.tensor.2d.global.shared::cta.bulk_group [%0, {%1, %2}], [%3];"
                 :: "l"(m), "r"(c0), "r"(c1), "r"(src) : "memory");
}
__device__ __forceinline__ void bar_sync(int id, int n) { asm volatile("bar.sync %0, %1;" :: "r"(id), "r"(n) : "memory"); }
__device__ __forceinline__ void fence_async() { asm volatile("fence.proxy.async.shared::cta;" ::: "memory"); }
__device__ __forceinline__ void cluster_sync() {
    asm volatile("barrier.cluster.arrive.release.aligned;\nbarrier.cluster.wait.acquire.aligned;" ::: "memory");
}
__device__ __forceinline__ void ldsm4(uint32_t* r, uint32_t a) {
    asm volatile("ldmatrix.sync.aligned.m8n8.x4.shared.b16 {%0,%1,%2,%3}, [%4];"
                 : "=r"(r[0]), "=r"(r[1]), "=r"(r[2]), "=r"(r[3]) : "r"(a) : "memory");
}
__device__ __forceinline__ void ldsm4t(uint32_t* r, uint32_t a) {
    asm volatile("ldmatrix.sync.aligned.m8n8.x4.trans.shared.b16 {%0,%1,%2,%3}, [%4];"
                 : "=r"(r[0]), "=r"(r[1]), "=r"(r[2]), "=r"(r[3]) : "r"(a) : "memory");
}
__device__ __forceinline__ void stsm4(uint32_t a, uint32_t r0, uint32_t r1, uint32_t r2, uint32_t r3) {
    asm volatile("stmatrix.sync.aligned.m8n8.x4.shared.b16 [%0], {%1,%2,%3,%4};" :: "r"(a), "r"(r0), "r"(r1), "r"(r2), "r"(r3) : "memory");
}
__device__ __forceinline__ void stsm4f(uint32_t a, const float* v) {
    asm volatile("{\n.reg .b32 a, b, c, d;\nmov.b32 a, %1;\nmov.b32 b, %2;\nmov.b32 c, %3;\nmov.b32 d, %4;\n"
                 "stmatrix.sync.aligned.m8n8.x4.shared.b16 [%0], {a, b, c, d};\n}" :: "r"(a), "f"(v[0]), "f"(v[1]), "f"(v[2]), "f"(v[3]) : "memory");
}
__device__ __forceinline__ void ldsm4f(float* v, uint32_t a) {
    uint32_t r[4];
    ldsm4(r, a);
#pragma unroll
    for (int i = 0; i < 4; i++) v[i] = __uint_as_float(r[i]);
}
__device__ __forceinline__ void stsm4t(uint32_t a, uint32_t r0, uint32_t r1, uint32_t r2, uint32_t r3) {
    asm volatile("stmatrix.sync.aligned.m8n8.x4.trans.shared.b16 [%0], {%1,%2,%3,%4};" :: "r"(a), "r"(r0), "r"(r1), "r"(r2), "r"(r3) : "memory");
}
__device__ __forceinline__ void stsm2(uint32_t a, uint32_t r0, uint32_t r1) {
    asm volatile("stmatrix.sync.aligned.m8n8.x2.shared.b16 [%0], {%1,%2};" :: "r"(a), "r"(r0), "r"(r1) : "memory");
}
__device__ __forceinline__ void stsm2t(uint32_t a, uint32_t r0, uint32_t r1) {
    asm volatile("stmatrix.sync.aligned.m8n8.x2.trans.shared.b16 [%0], {%1,%2};" :: "r"(a), "r"(r0), "r"(r1) : "memory");
}
__device__ __forceinline__ uint32_t movm(uint32_t a) {
    uint32_t d; asm volatile("movmatrix.sync.aligned.m8n8.trans.b16 %0, %1;" : "=r"(d) : "r"(a)); return d;
}
__device__ __forceinline__ void mma16(float* d, uint32_t a0, uint32_t a1, uint32_t a2, uint32_t a3, uint32_t b0, uint32_t b1) {
    asm volatile("mma.sync.aligned.m16n8k16.row.col.f32.bf16.bf16.f32 {%0,%1,%2,%3}, {%4,%5,%6,%7}, {%8,%9}, {%0,%1,%2,%3};"
                 : "+f"(d[0]), "+f"(d[1]), "+f"(d[2]), "+f"(d[3]) : "r"(a0), "r"(a1), "r"(a2), "r"(a3), "r"(b0), "r"(b1));
}
__device__ __forceinline__ void mma8(float* d, uint32_t a0, uint32_t a1, uint32_t b0) {
    asm volatile("mma.sync.aligned.m16n8k8.row.col.f32.bf16.bf16.f32 {%0,%1,%2,%3}, {%4,%5}, {%6}, {%0,%1,%2,%3};"
                 : "+f"(d[0]), "+f"(d[1]), "+f"(d[2]), "+f"(d[3]) : "r"(a0), "r"(a1), "r"(b0));
}
__device__ __forceinline__ uint32_t pack2(float lo, float hi) {
    uint32_t r; asm("cvt.rn.bf16x2.f32 %0, %1, %2;" : "=r"(r) : "f"(hi), "f"(lo)); return r;
}
__device__ __forceinline__ float bf_lo(uint32_t v) { return __uint_as_float(v << 16); }
__device__ __forceinline__ float bf_hi(uint32_t v) { return __uint_as_float(v & 0xFFFF0000u); }
__device__ __forceinline__ float ex2(float x) { float y; asm("ex2.approx.ftz.f32 %0, %1;" : "=f"(y) : "f"(x)); return y; }
__device__ __forceinline__ float rcp(float x) { float y; asm("rcp.approx.ftz.f32 %0, %1;" : "=f"(y) : "f"(x)); return y; }
__device__ __forceinline__ void sts4f(uint32_t a, float x, float y, float z, float w) {
    asm volatile("st.shared.v4.f32 [%0], {%1,%2,%3,%4};" :: "r"(a), "f"(x), "f"(y), "f"(z), "f"(w) : "memory");
}
__device__ __forceinline__ void sts1u(uint32_t a, uint32_t v) { asm volatile("st.shared.u32 [%0], %1;" :: "r"(a), "r"(v) : "memory"); }
__device__ __forceinline__ void sts4u(uint32_t a, uint4 v) {
    asm volatile("st.shared.v4.u32 [%0], {%1,%2,%3,%4};" :: "r"(a), "r"(v.x), "r"(v.y), "r"(v.z), "r"(v.w) : "memory");
}
__device__ __forceinline__ float4 lds4f(uint32_t a) {
    float4 v; asm volatile("ld.shared.v4.f32 {%0,%1,%2,%3}, [%4];" : "=f"(v.x), "=f"(v.y), "=f"(v.z), "=f"(v.w) : "r"(a) : "memory"); return v;
}
__device__ __forceinline__ float2 lds2f(uint32_t a) {
    float2 v; asm volatile("ld.shared.v2.f32 {%0,%1}, [%2];" : "=f"(v.x), "=f"(v.y) : "r"(a) : "memory"); return v;
}
__device__ __forceinline__ uint4 lds4u(uint32_t a) {
    uint4 v; asm volatile("ld.shared.v4.u32 {%0,%1,%2,%3}, [%4];" : "=r"(v.x), "=r"(v.y), "=r"(v.z), "=r"(v.w) : "r"(a) : "memory"); return v;
}
__device__ __forceinline__ uint32_t lds1u(uint32_t a) {
    uint32_t v; asm volatile("ld.shared.u32 %0, [%1];" : "=r"(v) : "r"(a) : "memory"); return v;
}
__device__ __forceinline__ uint2 lds2u(uint32_t a) {
    uint2 v; asm volatile("ld.shared.v2.u32 {%0,%1}, [%2];" : "=r"(v.x), "=r"(v.y) : "r"(a) : "memory"); return v;
}
__device__ __forceinline__ void st_async4(uint32_t a, uint32_t bar, float x, float y, float z, float w) {
    asm volatile("st.async.shared::cluster.mbarrier::complete_tx::bytes.v4.f32 [%0], {%1,%2,%3,%4}, [%5];"
                 :: "r"(a), "f"(x), "f"(y), "f"(z), "f"(w), "r"(bar) : "memory");
}
__device__ __forceinline__ void st_async2(uint32_t a, uint32_t bar, float x, float y) {
    asm volatile("st.async.shared::cluster.mbarrier::complete_tx::bytes.v2.f32 [%0], {%1,%2}, [%3];"
                 :: "r"(a), "f"(x), "f"(y), "r"(bar) : "memory");
}
__device__ __forceinline__ void st_async1f(uint32_t a, uint32_t bar, float x) {
    asm volatile("st.async.shared::cluster.mbarrier::complete_tx::bytes.f32 [%0], %1, [%2];" :: "r"(a), "f"(x), "r"(bar) : "memory");
}
__device__ __forceinline__ void st_async1(uint32_t a, uint32_t bar, uint32_t x) {
    asm volatile("st.async.shared::cluster.mbarrier::complete_tx::bytes.b32 [%0], %1, [%2];" :: "r"(a), "r"(x), "r"(bar) : "memory");
}
__device__ __forceinline__ uint4 ld_relaxed4(const uint4* p) {
    uint4 v;
    asm volatile("ld.relaxed.gpu.global.v4.u32 {%0,%1,%2,%3}, [%4];" : "=r"(v.x), "=r"(v.y), "=r"(v.z), "=r"(v.w) : "l"(p) : "memory");
    return v;
}
__device__ __forceinline__ void st_relaxed4(uint4* p, uint4 v) {
    asm volatile("st.relaxed.gpu.global.v4.u32 [%0], {%1,%2,%3,%4};" :: "l"(p), "r"(v.x), "r"(v.y), "r"(v.z), "r"(v.w) : "memory");
}
__device__ __forceinline__ void count_up(int idx) {
    asm volatile("red.release.gpu.global.add.u32 [%0], 1;" :: "l"(&g_cnt[idx * 8]) : "memory");
}
__device__ __forceinline__ void st_pred1(void* p, uint32_t v, bool on) {
    asm volatile("{\n.reg .pred p;\nsetp.ne.u32 p, %2, 0;\n@p st.relaxed.gpu.global.u32 [%0], %1;\n}" :: "l"(p), "r"(v), "r"((uint32_t)on) : "memory");
}
__device__ __forceinline__ void st_pred4(void* p, uint4 v, bool on) {
    asm volatile("{\n.reg .pred p;\nsetp.ne.u32 p, %5, 0;\n@p st.global.v4.u32 [%0], {%1,%2,%3,%4};\n}"
                 :: "l"(p), "r"(v.x), "r"(v.y), "r"(v.z), "r"(v.w), "r"((uint32_t)on) : "memory");
}
__device__ __forceinline__ void st_relaxed1(void* p, uint32_t v) {
    asm volatile("st.relaxed.gpu.global.u32 [%0], %1;" :: "l"(p), "r"(v) : "memory");
}
__device__ __forceinline__ uint32_t umax4(uint4 v) { return max(max(v.x, v.y), max(v.z, v.w)); }
__device__ __forceinline__ void wg_fence() { asm volatile("wgmma.fence.sync.aligned;" ::: "memory"); }
__device__ __forceinline__ void wg_commit() { asm volatile("wgmma.commit_group.sync.aligned;" ::: "memory"); }
template <int N> __device__ __forceinline__ void wg_wait() { asm volatile("wgmma.wait_group.sync.aligned %0;" :: "n"(N) : "memory"); }
template <int N> __device__ __forceinline__ void reg_fence(float* d) {
#pragma unroll
    for (int i = 0; i < N; i++) asm volatile("" : "+f"(d[i]) :: "memory");
}
#define ACC16(d) "+f"(d[0]), "+f"(d[1]), "+f"(d[2]), "+f"(d[3]), "+f"(d[4]), "+f"(d[5]), "+f"(d[6]), "+f"(d[7]), \
                 "+f"(d[8]), "+f"(d[9]), "+f"(d[10]), "+f"(d[11]), "+f"(d[12]), "+f"(d[13]), "+f"(d[14]), "+f"(d[15])
#define DESC_HI_SW128 "0x40000040"
#define OUT16(d) "=f"(d[0]), "=f"(d[1]), "=f"(d[2]), "=f"(d[3]), "=f"(d[4]), "=f"(d[5]), "=f"(d[6]), "=f"(d[7]), \
                 "=f"(d[8]), "=f"(d[9]), "=f"(d[10]), "=f"(d[11]), "=f"(d[12]), "=f"(d[13]), "=f"(d[14]), "=f"(d[15])
template <int ACCUM, int BOFF>
__device__ __forceinline__ void wg32_rs(float* d, const uint32_t* a, uint64_t dsw) {
    if (ACCUM)
        asm volatile("{\n.reg .b64 db;\nadd.s64 db, %20, %21;\n"
                     "wgmma.mma_async.sync.aligned.m64n32k16.f32.bf16.bf16 {%0,%1,%2,%3,%4,%5,%6,%7,%8,%9,%10,%11,%12,%13,%14,%15}, "
                     "{%16,%17,%18,%19}, db, 1, 1, 1, 0;\n}"
                     : ACC16(d) : "r"(a[0]), "r"(a[1]), "r"(a[2]), "r"(a[3]), "l"(dsw), "n"(BOFF));
    else
        asm volatile("{\n.reg .b64 db;\nadd.s64 db, %20, %21;\n"
                     "wgmma.mma_async.sync.aligned.m64n32k16.f32.bf16.bf16 {%0,%1,%2,%3,%4,%5,%6,%7,%8,%9,%10,%11,%12,%13,%14,%15}, "
                     "{%16,%17,%18,%19}, db, 0, 1, 1, 0;\n}"
                     : OUT16(d) : "r"(a[0]), "r"(a[1]), "r"(a[2]), "r"(a[3]), "l"(dsw), "n"(BOFF));
}
template <int ACCUM, int AOFF, int BOFF>
__device__ __forceinline__ void wg32_ss(float* d, uint64_t dsw) {
    if (ACCUM)
        asm volatile("{\n.reg .b64 da, db;\nadd.s64 da, %16, %17;\nadd.s64 db, %16, %18;\n"
                     "wgmma.mma_async.sync.aligned.m64n32k16.f32.bf16.bf16 {%0,%1,%2,%3,%4,%5,%6,%7,%8,%9,%10,%11,%12,%13,%14,%15}, "
                     "da, db, 1, 1, 1, 1, 0;\n}"
                     : ACC16(d) : "l"(dsw), "n"(AOFF), "n"(BOFF));
    else
        asm volatile("{\n.reg .b64 da, db;\nadd.s64 da, %16, %17;\nadd.s64 db, %16, %18;\n"
                     "wgmma.mma_async.sync.aligned.m64n32k16.f32.bf16.bf16 {%0,%1,%2,%3,%4,%5,%6,%7,%8,%9,%10,%11,%12,%13,%14,%15}, "
                     "da, db, 0, 1, 1, 1, 0;\n}"
                     : OUT16(d) : "l"(dsw), "n"(AOFF), "n"(BOFF));
}
template <int ACCUM, int AOFF, int BOFF>
__device__ __forceinline__ void wg8_ss(float* d, uint64_t dsw, uint64_t dns) {
    if (!ACCUM)
        asm volatile("{\n.reg .b64 da, db;\nadd.s64 da, %4, %6;\nadd.s64 db, %5, %7;\n"
                     "wgmma.mma_async.sync.aligned.m64n8k16.f32.bf16.bf16 {%0,%1,%2,%3}, da, db, 0, 1, 1, 1, 0;\n}"
                     : "=f"(d[0]), "=f"(d[1]), "=f"(d[2]), "=f"(d[3]) : "l"(dsw), "l"(dns), "n"(AOFF), "n"(BOFF));
    else
        asm volatile("{\n.reg .b64 da, db;\nadd.s64 da, %4, %6;\nadd.s64 db, %5, %7;\n"
                     "wgmma.mma_async.sync.aligned.m64n8k16.f32.bf16.bf16 {%0,%1,%2,%3}, da, db, 1, 1, 1, 1, 0;\n}"
                     : "+f"(d[0]), "+f"(d[1]), "+f"(d[2]), "+f"(d[3]) : "l"(dsw), "l"(dns), "n"(AOFF), "n"(BOFF));
}
template <int I0, int I1, class F>
__device__ __forceinline__ void static_for(F&& f) {
    if constexpr (I0 < I1) { f(std::integral_constant<int, I0>{}); static_for<I0 + 1, I1>(f); }
}
template <int I0, int I1, int AOFF, int BOFF>
__device__ __forceinline__ void wg8_chain(float* d, uint64_t dsw, uint64_t dns) {
    wg_fence();
    static_for<I0, I1>([&](auto i) { wg8_ss<i.value != 0, AOFF + i.value * 128, BOFF + i.value * 16>(d, dsw, dns); });
    wg_commit();
}

__device__ __forceinline__ void ln_row(const uint4* v, int row, int lane) {
    float f[32];
#pragma unroll
    for (int j = 0; j < 4; j++) {
        f[j * 8 + 0] = bf_lo(v[j].x); f[j * 8 + 1] = bf_hi(v[j].x); f[j * 8 + 2] = bf_lo(v[j].y); f[j * 8 + 3] = bf_hi(v[j].y);
        f[j * 8 + 4] = bf_lo(v[j].z); f[j * 8 + 5] = bf_hi(v[j].z); f[j * 8 + 6] = bf_lo(v[j].w); f[j * 8 + 7] = bf_hi(v[j].w);
    }
    float s = 0.f;
#pragma unroll
    for (int i = 0; i < 32; i++) s += f[i];
#pragma unroll
    for (int o = 16; o; o >>= 1) s += __shfl_xor_sync(~0u, s, o);
    const float mean = s * (1.f / DM);
    float q = 0.f;
#pragma unroll
    for (int i = 0; i < 32; i++) { f[i] -= mean; q += f[i] * f[i]; }
#pragma unroll
    for (int o = 16; o; o >>= 1) q += __shfl_xor_sync(~0u, q, o);
    const float r = 1.f / sqrtf(q * (1.f / DM) + 1e-5f);
    uint4* dst = reinterpret_cast<uint4*>(g_xn + (size_t)row * DM);
    uint4* dst2 = g_xc + (row >> 5) * 4096 + (lane >> 3) * 256 + (row & 31) * 8 + ((lane & 7) ^ (row & 7));
#pragma unroll
    for (int j = 0; j < 4; j++) {
        const uint4 o = make_uint4(pack2(f[j * 8] * r, f[j * 8 + 1] * r), pack2(f[j * 8 + 2] * r, f[j * 8 + 3] * r),
                                   pack2(f[j * 8 + 4] * r, f[j * 8 + 5] * r), pack2(f[j * 8 + 6] * r, f[j * 8 + 7] * r));
        dst[j * 32 + lane] = o;
        dst2[(j & 1) * 2048 + (j >> 1) * 1024] = o;
    }
}
__device__ __forceinline__ void reset_exchange(const __nv_bfloat16* __restrict__ mem0) {
    const int gi = blockIdx.x * 256 + threadIdx.x;
    const uint4 poison = make_uint4(~0u, ~0u, ~0u, ~0u);
    if (gi < 1024) {
        uint4 m = reinterpret_cast<const uint4*>(mem0)[(gi & 7) * 128 + (gi >> 3)];
        if (m.x == ~0u) m.x = 0x7FFF7FFFu;
        if (m.y == ~0u) m.y = 0x7FFF7FFFu;
        if (m.z == ~0u) m.z = 0x7FFF7FFFu;
        if (m.w == ~0u) m.w = 0x7FFF7FFFu;
        g_xmem[0][gi] = m;
    } else if (gi < 4096) {
        (&g_xmem[0][0])[gi] = poison;
    } else if (gi < 4096 + 16384) {
        (&g_xo[0][0])[gi - 4096] = poison;
    } else if (gi < 4096 + 16384 + 48 * FSTR) {
        reinterpret_cast<uint4*>(&g_flag[0][0])[gi - 4096 - 16384] = poison;
    } else if (gi >= 24576 - CNT_NUM) {
        g_cnt[(24575 - gi) * 8] = 0;
    }
}

#define ONKQ 45
constexpr int ONKV = 128 - 2 * ONKQ;
constexpr uint32_t SB0 = 1024;
constexpr uint32_t C_WS = 0, C_XN = 65536, C_MB = 98304, C_WO = 114688, C_SMEM = 232448;
constexpr uint32_t C_BAR = C_SMEM - 384, C_CAL = C_BAR + 192;
constexpr uint32_t C_SLOTQ = C_WO + ONKQ * 2048, C_QX = C_SLOTQ + 8192, C_KX = C_QX + 4096,
                   C_XSL = C_KX + 4096, C_OL = C_XSL + 5120;
constexpr uint32_t C_SLOTV = C_WO + ONKV * 2048, C_V = C_SLOTV + 8192, C_PL = C_V + 20480, C_SL = C_PL + 4096;
constexpr uint32_t C_DUMP = C_BAR - 512;
static_assert(C_OL + 3072 <= C_DUMP && C_SL + 2560 <= C_DUMP, "smem overflow");
enum { B_W0 = 0, B_W1, B_W2, B_WS, B_XF0, B_XF1, B_SC, B_P0, B_P1, B_XS, B_OL, B_MF0, B_MF1, B_OF, B_RT0, B_RT1, B_VF, B_MBF, B_GO, B_DUMP, B_NUM };
struct Descs { uint64_t sw[4], ns; };
constexpr uint64_t DSW = 0x4000004000010000ull, DNS = 0x0000001000080000ull;
template <int V> using ic = std::integral_constant<int, V>;
constexpr float SM_SCALE = 0.08838834764831845f * 1.4426950408889634f;

#define TSD(i) do {} while (0)
#define TS_FLUSH(w)
#define TSX(i, c)
#define TS(i)
#define NOFILL 0
#define DLY1 2170
#define DLY2 1310
#define SWAP16 0
#define SSFIRST 1
#define EARLYB 0
#define CANARY ~0u
#define QK1 10
#define RFPOS 6
#define STPOS 14
#define OTAIL 3
#define DLYS 450
#define DLYB 1
#define VLEAD 1

#define VEARLY 8
#define QSPLIT 20
__device__ __forceinline__ bool elect() {
    uint32_t r;
    asm volatile("{\n.reg .pred p;\nelect.sync _|p, 0xffffffff;\nselp.u32 %0, 1, 0, p;\n}" : "=r"(r));
    return r;
}
__device__ __forceinline__ int uni(int v) { return __shfl_sync(~0u, v, 0); }
__device__ __forceinline__ void calibrate(uint32_t cal, float keep) {
    const uint32_t t0 = gtick();
    uint32_t t, it = 0;
    do { t = gtick(); spin_guard(it); } while (__any_sync(~0u, t == t0));
    const uint32_t c = clk();
    const uint4 p = lds4u(cal);
    const float cpt = 256.f * fminf(fmaxf(__fdividef((float)(c - p.y), (float)((t - p.x) & 0x7FFFFFF)), 16.f), 128.f);
    __syncwarp();
    sts4u(cal, make_uint4(t, c, (uint32_t)(keep > 0.f ? fmaf(keep, (float)p.z - cpt, cpt) : cpt), 0));
}
struct Stamps { uint32_t v[6]; };
__device__ __forceinline__ void load_stamps2(Stamps& t, const uint32_t* f, uint32_t l16, bool on = true) {
    const char* p = reinterpret_cast<const char*>(f) + (l16 >> 2) * FSTR;
    asm volatile("{\n.reg .pred p;\nsetp.ne.u32 p, %7, 0;\nmov.u32 %0, 63;\nmov.u32 %1, 63;\nmov.u32 %2, 63;\nmov.u32 %3, 63;\nmov.u32 %4, 63;\nmov.u32 %5, 63;\n"
                 "@p ld.relaxed.gpu.global.v2.u32 {%0, %1}, [%6];\n@p ld.relaxed.gpu.global.v2.u32 {%2, %3}, [%6 + %8];\n"
                 "@p ld.relaxed.gpu.global.v2.u32 {%4, %5}, [%6 + %9];\n}"
                 : "=&r"(t.v[0]), "=&r"(t.v[1]), "=&r"(t.v[2]), "=&r"(t.v[3]), "=&r"(t.v[4]), "=&r"(t.v[5])
                 : "l"(p), "r"((uint32_t)on), "n"(128 * FSTR), "n"(256 * FSTR) : "memory");
}
__device__ __forceinline__ void load_stamps1(uint32_t* v, const uint32_t* f, uint32_t l16, bool on = true) {
    const char* p = reinterpret_cast<const char*>(f) + (l16 >> 2) * FSTR;
    asm volatile("{\n.reg .pred p;\nsetp.ne.u32 p, %4, 0;\nmov.u32 %0, 63;\nmov.u32 %1, 63;\nmov.u32 %2, 63;\n"
                 "@p ld.relaxed.gpu.global.u32 %0, [%3];\n@p ld.relaxed.gpu.global.u32 %1, [%3 + %5];\n@p ld.relaxed.gpu.global.u32 %2, [%3 + %6];\n}"
                 : "=&r"(v[0]), "=&r"(v[1]), "=&r"(v[2]) : "l"(p), "r"((uint32_t)on), "n"(128 * FSTR), "n"(256 * FSTR) : "memory");
}
template <int N>
__device__ __forceinline__ uint32_t stamps_missing(const uint32_t* v, int s) {
    uint32_t x = 0;
#pragma unroll
    for (int i = 0; i < N; i++) x |= v[i] ^ s;
    return x & 63;
}
template <int N>
__device__ __forceinline__ uint32_t latest_stamp(const uint32_t* v, const uint4 cal) {
    int late = (int)(v[0] - (cal.x << 6));
#pragma unroll
    for (int i = 1; i < N; i++) late = max(late, (int)(v[i] - (cal.x << 6)));
    return cal.y + (((late >> 6) * (int)cal.z) >> 8);
}
__device__ __forceinline__ void wait_clock(uint32_t target) {
    while (__any_sync(~0u, target - clk() < 65536u)) {}
}

template <int BYTES>
__device__ __forceinline__ bool incomplete(uint32_t buf, uint32_t l16) {
    uint32_t m = 0;
#pragma unroll 1
    for (int o = 0; o < BYTES; o += 256) m = max(m, umax4(lds4u(buf + o + (l16 & 255))));
    return __any_sync(~0u, m == ~0u);
}
__device__ __forceinline__ void refetch(uint32_t buf, const uint4* src, uint32_t bytes, uint32_t b, int w4, int barid, uint32_t& tries) {
    spin_guard(tries);
    bar_sync(barid, 128);
    if (w4 == 0 && elect()) { mbar_expect(b, bytes); bulk_ld(buf, src, bytes, b); }
    __syncwarp();
    mbar_wait(b, 0);
    bar_sync(barid, 128);
    if (w4 == 0 && elect()) mbar_arrive(b);
    __syncwarp();
}

__device__ __forceinline__ void load_box(const CUtensorMap* tA, const CUtensorMap* tB, int cl, int rank, uint32_t dst, int j, int q, uint32_t b) {
    const bool isb = (q ^ (q >> 1)) & 1;
    tma2d(dst + q * 16384, isb ? tB : tA, cl * 256 + (rank >= 4 ? (rank - 4) * 128 + isb * 64 : rank * 64), (q >> 1) * 512 + j * 128, b);
}

template <bool ISV, int WG>
__device__ __forceinline__ void chain_main(const CUtensorMap* tA, const CUtensorMap* tB, const CUtensorMap* tWo,
                                           const uint32_t sb, const int cl, const int rank, const Descs& D, const uint32_t goal) {
    const int tid = threadIdx.x;
    uint32_t l16 = __shfl_sync(~0u, (tid & 31) * 16, tid & 31);
    int w4 = uni((tid >> 5) & 3);
    const int role = ISV ? 2 : (rank & 1), hh = ISV ? rank - 4 : rank >> 1, head = 2 * cl + hh;
    const uint32_t bar = sb + C_BAR;
    constexpr int ONK = ISV ? ONKV : ONKQ;
    const int ostart = (hh * 128 + role * ONKQ);

    uint32_t wk[24][4], wv[24][4];
    uint32_t a_adr;
    {
        if (WG == 1 && w4 == 0) calibrate(sb + C_CAL, 0.f);
        const int lane = tid & 31, kr = (lane & 7) + ((lane >> 4) << 3);
        a_adr = __shfl_sync(~0u, sb + WG * 32768 + kr * 128 + (((w4 * 2 + ((lane >> 3) & 1)) ^ (kr & 7)) << 4), lane);
#pragma unroll
        for (int j = 0; j < 3; j++) {
            mbar_wait(bar + (B_W0 + j) * 8, 0);
#pragma unroll
            for (int i = 0; i < 8; i++) {
                ldsm4t(wk[j * 8 + i], a_adr + j * 65536 + i * 2048);
                ldsm4t(wv[j * 8 + i], a_adr + j * 65536 + 16384 + i * 2048);
            }
            if (j != 1) {
                bar_sync(6, 256);
                if (j == 0 && tid == 0) TL(1, 6);
                if (WG == 0 && j == 0 && elect()) load_box(tA, tB, cl, rank, sb + C_WS, 3, w4, bar + B_WS * 8);
                if (WG == 0 && j == 2) {
                    if (elect())
                        for (int i = w4; i < ONK; i += 4) tma2d(sb + C_WO + i * 2048, tWo, cl * 64, (ostart + i) * 16, bar + B_OF * 8);
                }
                __syncwarp();
            }
        }
        if (NOFILL) { for (uint32_t o = C_WO + ONK * 2048 + tid * 16; o < C_BAR; o += 4096) sts4u(sb + o, make_uint4(0, 0, 0, 0)); bar_sync(6, 256); }
        if (WG == 1 && w4 == 1) {
            uint32_t v, it = 0;
            do {
                asm volatile("ld.acquire.gpu.global.u32 %0, [%1];" : "=r"(v) : "l"(&g_epoch) : "memory");
                spin_guard(it);
            } while (__any_sync(~0u, (int)(v - goal) < 0));
        }
        if (WG == 1 && w4 == 0) calibrate(sb + C_CAL, 0.f);
        __syncwarp();
        bar_sync(6, 256);
        asm volatile("fence.proxy.async.global;" ::: "memory");
    }

    constexpr uint32_t SLOT = ISV ? C_SLOTV : C_SLOTQ;
    constexpr int WS_A = (SB0 + C_WS + WG * 32768) >> 4, WO_A = (SB0 + C_WO) >> 4, MB_A = (SB0 + C_MB) >> 4;
#define XN_A(ks) (int)(((SB0 + C_XN + WG * 16384) >> 4) + ((ks) >> 2) * 256 + ((ks) & 3) * 2)
    const uint32_t slot = (sb + SLOT + w4 * 512), mbw = sb + C_MB + WG * 8192;
    const uint32_t sb_v = (mapa(sb, 4 + hh));
    const uint32_t sb_x = uni(mapa(sb, 2 * hh + (WG ? 1 : (~w4 & 1))));
    const uint32_t sb_o = (mapa(sb, w4));
    const uint32_t u_off = (ISV ? (head * 128 + w4 * 32) * 16 : (cl * 4 + rank) * 256 + (w4 & 1) * 128);
    const uint32_t v_row = (sb + C_V + (2 * WG + (w4 >> 1)) * 512), v_b = ((w4 & 1) * 64);
    const uint32_t u_flag = (blockIdx.x * FSTR);
    const uint32_t f_half = (w4 & 1) * role * (ONKV * 128), f_sb = uni(mapa(sb, rank + (w4 & 1) * (4 + hh - rank)));
    const uint32_t f_src = uni((ostart + (w4 & 1) * (2 - role) * ONKQ) * 256 + f_half), f_dst = uni(f_sb + C_MB + f_half);
    const uint32_t m_dst = (sb + C_MB + role * 8192), m_bar = (bar + (B_MF0 + role) * 8);
    uint32_t target, missing;
    int s = -1;
    uint32_t pf[4][4];
    float xk[16], xv[16];
    uint4 oxp[4];

    auto send_planes = [&](auto n, uint32_t a, int b, const float* v, bool hold) {
        const uint32_t dump = sb + C_DUMP + (l16 >> 2), to = a + (l16 >> 2), ad = hold ? dump : to;
        const uint32_t mb = hold ? (dump & 0xFF000000u) | (SB0 + C_BAR + B_DUMP * 8) : (to & 0xFF000000u) | (SB0 + C_BAR + b * 8);
#pragma unroll
        for (int i = 0; i < n.value; i++) st_async1f(ad + i * 128, mb, v[i]);
    };
    auto store_ox = [&](int ss) {
        char* orow = reinterpret_cast<char*>(g_ox) + (ss * (32 * HD * 2) + (u_off >> 3) + (l16 >> 6) * (HD * 2) + (l16 & 48));
#pragma unroll
        for (int i = 0; i < 4; i++) st_pred4(orow + i * (8 * HD * 2), oxp[i], ss >= 0);
    };
    auto load_tokens = [&](int seg, int wina, int g) {
        const int khalf = ISV ? 1 - wina : wina;
        if (!NOFILL && elect()) {
            mbar_expect(bar + (B_XF0 + g) * 8, 16384);
            bulk_ld(sb + C_XN + g * 16384, g_xc + (seg * 4 + khalf * 2 + g) * 1024, 16384, bar + (B_XF0 + g) * 8);
        }
        __syncwarp();
    };
    auto prefetch = [&]() {
#pragma unroll
        for (int i = 0; i < 4; i++) ldsm4t(pf[i], a_adr + C_WS + (i & 1) * 16384 + (i >> 1) * 2048);
    };
    constexpr int HA = ISV ? 0 : 1, NK1 = ISV ? 0 : QK1;
    auto products = [&](auto give, auto half, auto init, auto i0, auto i1, const uint64_t d) {
        static_for<i0.value, i1.value>([&](auto i) {
            constexpr int ks = half.value * 16 + i.value, acc = !(init.value && i.value == i0.value);
            if constexpr (ks >= 24) wg32_ss<acc, WS_A + give.value * 1024 + (ks - 24) * 128, XN_A(i.value)>(give.value ? xv : xk, d);
            else if constexpr (give.value) wg32_rs<acc, XN_A(i.value)>(xv, wv[ks], d);
            else wg32_rs<acc, XN_A(i.value)>(xk, wk[ks], d);
        });
    };
    auto stream_a = [&](const uint64_t dk, const uint64_t dv) {
        if (NOFILL) return;
        constexpr int F = (WG == 0 && SSFIRST) ? 8 : 0;
        wg_fence();
        products(ic<0>{}, ic<HA>{}, ic<1>{}, ic<F>{}, ic<F + 8>{}, dk);
        products(ic<1>{}, ic<HA>{}, ic<1>{}, ic<F>{}, ic<F + 8>{}, dv);
        products(ic<1>{}, ic<HA>{}, ic<0>{}, ic<8 - F>{}, ic<16 - F>{}, dv);
        products(ic<0>{}, ic<HA>{}, ic<0>{}, ic<8 - F>{}, ic<16 - F>{}, dk);
        wg_commit();
    };
    auto token_softmax = [&]() {
        const int hi = w4 - 2, lane = l16 >> 4;
        const uint32_t src = sb + C_XSL + hi * 256 + (l16 & 255) + (l16 >> 8) * 2560;
        const int d0 = 16 * role + 8 * hi + (lane >> 2) - 2 * (lane & 3);
        mbar_wait(bar + B_XS * 8, s & 1);
        float e[10];
        float m = -INFINITY;
#pragma unroll
        for (int i = 0; i < 5; i++) {
            __syncwarp();
            float a[4];
            ldsm4f(a, src + i * 512);
            e[2 * i] = (i == 0 || d0 >= 8 * (i - 1)) ? a[0] + a[2] : -INFINITY;
            e[2 * i + 1] = (i == 0 || d0 > 8 * (i - 1)) ? a[1] + a[3] : -INFINITY;
            m = fmaxf(m, fmaxf(e[2 * i], e[2 * i + 1]));
        }
        m = fmaxf(m, __shfl_xor_sync(~0u, m, 1));
        m = fmaxf(m, __shfl_xor_sync(~0u, m, 2));
        m *= -SM_SCALE;
        float l = 0.f;
#pragma unroll
        for (int i = 0; i < 10; i++) { e[i] = ex2(fmaf(e[i], SM_SCALE, m)); l += e[i]; }
        l += __shfl_xor_sync(~0u, l, 1);
        l += __shfl_xor_sync(~0u, l, 2);
        l = rcp(l);
        const uint32_t pd = sb_v + C_PL + (s & 1) * 2048 + role * 768 + hi * 128 + (l16 >> 2), pb = sb_v + C_BAR + (B_P0 + (s & 1)) * 8;
        st_async1(pd, pb, pack2(e[0] * l, e[1] * l));
        st_async1(pd + 256, pb, pack2(e[2] * l, e[3] * l));
        st_async1(pd + 512, pb, pack2(e[4] * l, e[5] * l));
        if (role) {
            st_async1(pd + 768, pb, pack2(e[6] * l, e[7] * l));
            st_async1(pd + 1024, pb, pack2(e[8] * l, e[9] * l));
        }
        if (hi == 0 && l16 == 0) mbar_expect(bar + B_XS * 8, 3072 + role * 2048);
        __syncwarp();
    };

    auto windows = [&]() {
        asm volatile("" : "+r"(l16), "+r"(w4));
        const uint64_t* const dd = D.sw;
        TS(5);
        if constexpr (WG == 1) {
            TS(6);
            if (ISV) bar_sync(3, 256);
            Stamps st2;
            if (!ISV) load_stamps2(st2, g_flag[0], l16, __any_sync(~0u, missing) && w4 < 2);
            stream_a(dd[0], dd[1]);
            if (!NOFILL) bar_arrive(7, 256);
            if (ISV) {
                if (!NOFILL) store_ox(s - 1);
                st_relaxed4(reinterpret_cast<uint4*>(reinterpret_cast<char*>(&g_xo[(s + 2) & 3][0]) + (u_off + l16)), make_uint4(~0u, ~0u, ~0u, ~0u));
            }
            auto fetch_o = [&]() {
            if (!ISV && w4 < 2 && s >= 0) {
                const char* src = reinterpret_cast<const char*>(&g_xo[s & 3][0]) + f_src;
                if (__builtin_expect(__any_sync(~0u, missing), 0)) {
                    uint32_t it = 0;
                    while (__any_sync(~0u, stamps_missing<6>(st2.v, s))) { load_stamps2(st2, g_flag[0], l16); spin_guard(it); }
                    target = latest_stamp<6>(st2.v, lds4u(sb + C_CAL)) + DLY1;
                }
                mbar_wait(bar + B_VF * 8, s & 1);
                TS(10);
                wait_clock(target);
                if (elect()) bulk_ld(f_dst, src, ONKQ * 256 - w4 * (ONKQ * 256 - ONKV * 128), f_sb + C_BAR + B_OF * 8);
                __syncwarp();
                TS(8);
            }
            };
            if (!EARLYB) fetch_o();
            if (!NOFILL) {
                wg_wait<0>();
                reg_fence<16>(xk); reg_fence<16>(xv);
                if (w4 == 3) { bar_sync(2, 128); load_tokens(s + 1, 0, 1); }
                else bar_arrive(2, 128);
            }
            if (EARLYB) fetch_o();
            TS(7);
        } else {
            if (!NOFILL) {
                mbar_wait(bar + B_XF0 * 8, 0);
                bar_sync(7, 256);
            }
            TS(6);
            stream_a(dd[0], dd[1]);
        }
        uint32_t st[6];
        uint4 cal;
        if constexpr (WG == 0) {
            if (s >= 0) {
                const uint32_t dst = sb_o + C_OL + rank * 512;
                const uint32_t can = sb + C_MB + l16 * 8 + (l16 >> 2), can2 = can + (l16 < (ONK * 2 - 64) * 16 ? 8192 : 0);
                float co[4];
                TS(7);
                uint32_t tries = 0;
                for (;; tries |= 1) {
                    asm volatile("" : "+r"(tries));
                    if (__builtin_expect(tries, 0)) {
                        wg_wait<0>();
                        refetch(sb + C_MB, &g_xo[s & 3][ostart * 16], ONK * 256, bar + B_RT0 * 8, w4, 1, tries);
                    }
                    mbar_wait(bar + B_OF * 8, s & 1);
                    TS(8);
                    wg8_chain<0, 8, WO_A, MB_A>(co, D.sw[0], D.ns);
                    if (__builtin_expect(!__any_sync(~0u, max(max(lds1u(can), lds1u(can + 4096)), lds1u(can2)) == CANARY), 1)) break;
                }
                wg_wait<1>();
                if (l16 == 0) mbar_arrive(bar + B_GO * 8);
                wg8_chain<8, ONK - OTAIL, WO_A, MB_A>(co, D.sw[0], D.ns);
                static_for<ONK - OTAIL, ONK>([&](auto i) { wg8_ss<1, WO_A + i.value * 128, MB_A + i.value * 16>(co, D.sw[0], D.ns); });
                wg_commit();
                wg_wait<1>();
                bar_arrive(5, 256);
                wg_wait<0>();
                reg_fence<4>(co);
                const bool nan = any_nan(co[0], co[1]);
                send_planes(ic<4>{}, dst, B_OL, co, nan);
                if (__builtin_expect(nan, 0)) {
                    while (incomplete<ONK * 256>(sb + C_MB, l16)) {
                        refetch(sb + C_MB, &g_xo[s & 3][ostart * 16], ONK * 256, bar + B_RT0 * 8, w4, 1, tries);
                        co[0] = co[1] = co[2] = co[3] = 0.f;
#pragma unroll 1
                        for (int i = 0; i < ONK; i++) {
                            wg_fence();
                            wg8_ss<1, WO_A, MB_A>(co, DSW + i * 128, DNS + i * 16);
                            wg_commit();
                            wg_wait<0>();
                        }
                        reg_fence<4>(co);
                    }
                    send_planes(ic<4>{}, dst, B_OL, co, false);
                }
                TS(9);
                if (l16 < 48 && w4 == 3) mbar_expect(bar + B_MF0 * 8 + (l16 >> 1), l16 == 32 ? ONK * 256 : 8192);
            } else {
                wg_wait<0>();
                if (l16 == 0) mbar_arrive(bar + B_GO * 8);
                bar_arrive(5, 256);
            }
            if (l16 < 32) mbar_arrive_cluster(mapa(bar + B_MBF * 8, 2 * hh + (l16 >> 4)));
            __syncwarp();
            if (!NOFILL) { reg_fence<16>(xk); reg_fence<16>(xv); }
        } else {
            if (w4 < 2) {
                mbar_wait(bar + B_GO * 8, (s + 1) & 1);
                const uint32_t v = ((gtick() - (ISV ? (ONKQ - ONKV) * 18 / 64 : 0)) << 6) | s, c = clk();
                if (w4 == 0) {
                    if (l16 == 0) st_relaxed1(&g_flag[1][u_flag + (l16 >> 1)], v);
                    if (!ISV) calibrate(sb + C_CAL, 0.75f);
                } else {
                    wait_clock(c + DLYB);
                    load_tokens(s + 1, 0, 0);
                }
                if (!ISV) st_relaxed1(reinterpret_cast<char*>(&g_xmem[(s + 3) & 3][0]) + (u_off + (l16 >> 2)), ~0u);
            } else if (!NOFILL && s >= 0) {
                if (ISV && w4 == 2 && (s & 3) == 1 && s > 1 && l16 == 0) count_up(CNT_OX + (s >> 2) - 1);
                __syncwarp();
                if (!ISV) token_softmax();
                TSX(9, w4 == 2);
            }
            if (!NOFILL) mbar_wait(bar + B_XF1 * 8, 1);
            if (!ISV) cal = lds4u(sb + C_CAL);
            bar_sync(5, 256);
            if (!ISV) load_stamps1(st, g_flag[1], l16, w4 == 0);
        }
        asm volatile("" : "+r"(l16), "+r"(w4));
        TSX(11, w4 == 0 && (WG || ISV));
        constexpr int NR = SWAP16 ? 2 : 4;
        constexpr uint32_t OUT = SWAP16 ? WG * 4096 : 0, IN = SWAP16 ? (WG ^ 1) * 4096 : 0;
        auto give = [&]() {
#pragma unroll
            for (int j = 0; j < NR; j++) {
                if (SWAP16) stsm4(slot + OUT + l16 + j * 2048, pack2(xv[8 * j], xv[8 * j + 1]), pack2(xv[8 * j + 2], xv[8 * j + 3]),
                                  pack2(xv[8 * j + 4], xv[8 * j + 5]), pack2(xv[8 * j + 6], xv[8 * j + 7]));
                else stsm4f(slot + l16 + j * 2048, xv + 4 * j);
            }
        };
        auto take = [&](uint32_t (*r)[4]) {
#pragma unroll
            for (int j = 0; j < NR; j++) ldsm4(r[j], slot + IN + l16 + j * 2048);
        };
        auto store_tokens = [&](const uint32_t (*r)[4]) {
            uint32_t lo[4], hi[4];
#pragma unroll
            for (int j = 0; j < 4; j++) {
                if (SWAP16) {
                    const uint32_t a = r[j >> 1][(j & 1) * 2], b = r[j >> 1][(j & 1) * 2 + 1];
                    lo[j] = pack2(xk[4 * j] + bf_lo(a), xk[4 * j + 1] + bf_hi(a));
                    hi[j] = pack2(xk[4 * j + 2] + bf_lo(b), xk[4 * j + 3] + bf_hi(b));
                } else {
                    lo[j] = pack2(xk[4 * j] + __uint_as_float(r[j % NR][0]), xk[4 * j + 1] + __uint_as_float(r[j % NR][1]));
                    hi[j] = pack2(xk[4 * j + 2] + __uint_as_float(r[j % NR][2]), xk[4 * j + 3] + __uint_as_float(r[j % NR][3]));
                }
            }
            if (!ISV) {
                const uint32_t d = sb + C_QX + WG * 4096 + w4 * 1024 + l16;
                stsm4t(d, lo[0], lo[1], lo[2], lo[3]);
                stsm4t(d + 512, hi[0], hi[1], hi[2], hi[3]);
            } else {
                const uint32_t d = v_row + ((s + 1) & 1) * 10240 + ((l16 & 384) << 4) + ((l16 & 96) << 2) + ((l16 & 112) ^ v_b);
                stsm4(d, lo[0], lo[1], lo[2], lo[3]);
                stsm4(d ^ 32, hi[0], hi[1], hi[2], hi[3]);
            }
        };
        if constexpr (WG == 1) {
            if (!NOFILL) {
                wg_fence();
                products(ic<1>{}, ic<1 - HA>{}, ic<0>{}, ic<0>{}, ic<16>{}, dd[3]);
                products(ic<0>{}, ic<1 - HA>{}, ic<0>{}, ic<0>{}, ic<NK1>{}, dd[2]);
                wg_commit();
                if (ISV) bar_arrive(7, 256);
                else {
                    load_stamps1(st + 3, g_flag[1], l16, w4 == 0);
                    mbar_wait(bar + B_MBF * 8, (s + 1) & 1);
                    bar_sync(7, 256);
                }
                wg_wait<0>();
                reg_fence<16>(xv); reg_fence<16>(xk);
                give();
                bar_arrive(8, 256);
            }
            TS(12);
            if (!ISV && w4 == 0) {
                const uint4* src = &g_xmem[(s + 1) & 3][role * 512];
                if (NOFILL) mbar_wait(bar + B_MBF * 8, (s + 1) & 1);
                {
                    if (__builtin_expect(__any_sync(~0u, stamps_missing<3>(st, s)), 0)) {
                        uint32_t it = 0;
                        if (!NOFILL) { st[0] = st[3]; st[1] = st[4]; st[2] = st[5]; }
                        while (__any_sync(~0u, stamps_missing<3>(st, s))) { load_stamps1(st, g_flag[1], l16); spin_guard(it); }
                    }
                    TS(3);
                    wait_clock(s >= 0 ? latest_stamp<3>(st, cal) + DLY2 : cal.y);
                }
                if (hh) { if (elect()) bulk_mc(m_dst, src, 8192, m_bar, 0x2C); }
                else if (elect()) bulk_mc(m_dst, src, 8192, m_bar, 0x13);
                __syncwarp();
                TS(4);
            }
            prefetch();
            if (!NOFILL) {
                bar_sync(9, 256);
                uint32_t r[NR][4];
                take(r);
                bar_sync(14, 256);
                wg_fence();
                products(ic<0>{}, ic<1 - HA>{}, ic<0>{}, ic<NK1>{}, ic<16>{}, dd[2]);
                wg_commit();
                wg_wait<0>();
                reg_fence<16>(xk);
                TS(13);
                store_tokens(r);
                bar_arrive(10, 256);
                if (w4 != 3) bar_arrive(13, 128);
            }
        } else {
            uint32_t r[NR][4];
            if (!NOFILL) mbar_wait(bar + B_XF0 * 8, 1);
            if (!ISV && w4 < 2 && s >= 0) {
                char* gd = reinterpret_cast<char*>(&g_xmem[(s + 1) & 3][0]) + (u_off + (l16 >> 2));
                const uint32_t src = sb + C_OL + w4 * 256 + l16 + (l16 & 256);
                mbar_wait(bar + B_OL * 8, s & 1);
                TSD(3);
                float a[3][4];
#pragma unroll
                for (int i = 0; i < 3; i++) ldsm4f(a[i], src + i * 1024);
                st_relaxed1(gd, movm(pack2((a[0][0] + a[0][2]) + (a[1][0] + a[1][2]) + (a[2][0] + a[2][2]),
                                           (a[0][1] + a[0][3]) + (a[1][1] + a[1][3]) + (a[2][1] + a[2][3]))));
                TS(11);
                if (w4 == 0 && l16 == 0) mbar_expect(bar + B_OL * 8, 3072);
                __syncwarp();
            }
            if (!NOFILL) {
                bar_sync(7, 256);
                TS(12);
                wg_fence();
                products(ic<1>{}, ic<1 - HA>{}, ic<0>{}, ic<0>{}, ic<16>{}, dd[3]);
                wg_commit();
                products(ic<0>{}, ic<1 - HA>{}, ic<0>{}, ic<0>{}, ic<6>{}, dd[2]);
                wg_commit();
                bar_sync(8, 256);
                take(r);
                wg_wait<1>();
                reg_fence<16>(xv);
                give();
                bar_arrive(9, 256);
                products(ic<0>{}, ic<1 - HA>{}, ic<0>{}, ic<6>{}, ic<16>{}, dd[2]);
                wg_commit();
                bar_arrive(14, 256);
                wg_wait<0>();
                reg_fence<16>(xk);
            }
            TS(13);
            if (!NOFILL) store_tokens(r);
            prefetch();
        }
    };

    if (tid == 0) TL(1, 2);
    if (w4 == 0) load_tokens(0, 1, WG);
    mbar_wait(bar + B_WS * 8, 0);
    if (WG == 1 && !NOFILL) mbar_wait(bar + B_XF1 * 8, 0);
    if (ISV && WG == 0) bar_arrive(3, 256);
    target = missing = 0;
    oxp[0] = oxp[1] = oxp[2] = oxp[3] = make_uint4(0, 0, 0, 0);

#pragma unroll 1
    while (true) {
        windows();
        s++;
        asm volatile("" : "+r"(l16), "+r"(a_adr), "+r"(w4));
        TS_FLUSH(WG);
        TS(0);
        float ck[4], cv[4], dk[4], dv[4];
        uint32_t b[3][4], tries = 0;
        const uint32_t kl = sb + C_KX + ((l16 & 384) << 2) + (l16 & 112);
        auto load_b = [&](auto kp) { ldsm4(b[kp.value % 3], mbw + l16 + ((kp.value & 3) ? (kp.value >> 2) * 3 + (kp.value & 3) - 1 : 12 + (kp.value >> 2)) * 512); };
        auto kpair = [&](auto kp_) {
            constexpr int kp = kp_.value, grp = kp >> 2, ph = kp & 3;
            if constexpr (kp > 0 && kp < 14) load_b(ic<kp + 2>{});
            const uint32_t* bb = b[kp % 3];
            if constexpr (ph != 0) {
                constexpr int q = (grp * 3 + ph - 1) * 2;
                static_for<(ph == 1 ? 0 : ph), ph + 1>([&](auto i) {
                    if constexpr (grp < 3) ldsm4t(pf[i.value], a_adr + C_WS + (i.value & 1) * 16384 + (grp * 2 + 2 + (i.value >> 1)) * 2048);
                });
                __syncwarp();
                mma16(cv, wv[q][0], wv[q][1], wv[q][2], wv[q][3], bb[0], bb[1]);
                mma16(ck, wk[q][0], wk[q][1], wk[q][2], wk[q][3], bb[0], bb[1]);
                mma16(dv, wv[q + 1][0], wv[q + 1][1], wv[q + 1][2], wv[q + 1][3], bb[2], bb[3]);
                mma16(dk, wk[q + 1][0], wk[q + 1][1], wk[q + 1][2], wk[q + 1][3], bb[2], bb[3]);
            } else {
                if constexpr (kp == 0) {
#pragma unroll
                    for (int i = 0; i < 4; i++) ck[i] = cv[i] = dk[i] = dv[i] = 0.f;
                }
                mma16(ck, pf[0][0], pf[0][1], pf[0][2], pf[0][3], bb[0], bb[1]);
                mma16(cv, pf[1][0], pf[1][1], pf[1][2], pf[1][3], bb[0], bb[1]);
                mma16(dk, pf[2][0], pf[2][1], pf[2][2], pf[2][3], bb[2], bb[3]);
                mma16(dv, pf[3][0], pf[3][1], pf[3][2], pf[3][3], bb[2], bb[3]);
            }
        };
        auto hand_over = [&]() {
#pragma unroll
            for (int i = 0; i < 4; i++) { cv[i] += dv[i]; ck[i] += dk[i]; }
            if (ISV) {
                stsm4f(slot + WG * 2048 + l16, cv);
            } else {
                const float *q = WG ? cv : ck, *k = WG ? ck : cv;
                stsm4t(slot + WG * 2048 + l16, pack2(q[0], q[1]), pack2(q[2], q[3]), pack2(k[0], k[1]), pack2(k[2], k[3]));
            }
        };
        auto repair = [&]() {
            bar_sync(6, 256);
            while (incomplete<8192>(mbw, l16)) {
                refetch(mbw, &g_xmem[s & 3][WG * 512], 8192, bar + (B_RT0 + WG) * 8, w4, 1 + WG, tries);
                prefetch();
                static_for<0, 3>(load_b);
                static_for<0, 16>(kpair);
                hand_over();
            }
            bar_sync(6, 256);
        };
        {
            const uint32_t can = mbw + l16 * 8 + (l16 >> 2);
            uint32_t* const flag = &g_flag[0][u_flag + WG + l16];
            for (;; tries |= 1) {
                asm volatile("" : "+r"(tries));
                if (__builtin_expect(tries, 0)) {
                    refetch(mbw, &g_xmem[s & 3][WG * 512], 8192, bar + (B_RT0 + WG) * 8, w4, 1 + WG, tries);
                }
                mbar_wait(bar + (B_MF0 + WG) * 8, s & 1);
                TS(1);
                static_for<0, 3>(load_b);
                const uint32_t c0 = lds1u(can), c1 = lds1u(can + 4096);
                const uint32_t v = ((gtick() - (ISV ? VLEAD : 0)) << 6) | s;
                kpair(ic<0>{});
                const bool early = __any_sync(~0u, max(c0, c1) == CANARY);
                st_pred1(flag, v, w4 * 512 + l16 == 1536 && !early);
                if (__builtin_expect(!early, 1)) break;
            }
            static_for<1, RFPOS>(kpair);
            if (WG == 0 && !NOFILL) bar_sync(10, 256);
            if (WG == 1 && !NOFILL && w4 == 3) {
                bar_sync(13, 128);
                if (s < NSEG - 1) load_tokens(s + 1, 1, 1);
            }
            static_for<RFPOS, 13>(kpair);
        }
        auto finish_projections = [&]() {
            static_for<13, 16>(kpair);
            hand_over();
            TS(2);
            return bar_sync_any_nan(cv[0], cv[1]);
        };
        if constexpr (!ISV) {
            const uint32_t qa = sb + C_SLOTQ + ((l16 >> 1) & 128) + ((l16 & 128) << 3) + (l16 & 112);
            const uint32_t ma = sb + C_SLOTQ + 256 + l16 + (l16 & 256);
            const uint32_t qx = sb + C_QX + l16 + (l16 & 256);
            auto ldsm_sum = [&](uint32_t* r, uint32_t a) {
                uint32_t t[4];
                ldsm4(r, a); ldsm4(t, a + 2048);
#pragma unroll
                for (int i = 0; i < 4; i++) asm("add.rn.bf16x2 %0, %0, %1;" : "+r"(r[i]) : "r"(t[i]));
            };
            auto tile = [&](float* d, const uint32_t (*q)[4], const uint32_t (*k)[4]) {
                d[0] = d[1] = d[2] = d[3] = 0.f;
#pragma unroll
                for (int i = 0; i < 4; i++) mma16(d, q[i][0], q[i][1], q[i][2], q[i][3], k[i >> 1][(i & 1) * 2], k[i >> 1][(i & 1) * 2 + 1]);
            };
            auto send = [&](int ti, const float* d, bool hold) {
                send_planes(ic<4>{}, sb_x + C_XSL + role * 2560 + ti * 512, B_XS, d, hold);
            };
            if constexpr (WG == 0) {
                auto scores = [&](auto again) {
                    bool nan = false;
                    if (w4 < 2) {
                        uint32_t k0[2][4], k1[2][4], q0[4], q1[4];
                        const uint32_t ka = kl + w4 * 256, dst = sb_v + C_SL + role * 1024 + w4 * 512;
                        ldsm4(k0[0], ka); ldsm4(k0[1], ka + 2048);
                        ldsm4(k1[0], ka + 128); ldsm4(k1[1], ka + 128 + 2048);
                        __syncwarp();
                        if (!again.value) nan = finish_projections();
                        TS(3);
                        ldsm_sum(q0, qa); ldsm_sum(q1, qa + 512);
                        float s0[4] = {0.f, 0.f, 0.f, 0.f}, s1[4] = {0.f, 0.f, 0.f, 0.f}, s2[4] = {0.f, 0.f, 0.f, 0.f}, s3[4] = {0.f, 0.f, 0.f, 0.f};
                        mma16(s0, q0[0], q0[1], q0[2], q0[3], k0[0][0], k0[0][1]);
                        mma16(s1, q0[0], q0[1], q0[2], q0[3], k0[1][0], k0[1][1]);
                        mma16(s2, q0[0], q0[1], q0[2], q0[3], k1[0][0], k1[0][1]);
                        mma16(s3, q0[0], q0[1], q0[2], q0[3], k1[1][0], k1[1][1]);
                        mma16(s0, q1[0], q1[1], q1[2], q1[3], k0[0][2], k0[0][3]);
                        mma16(s1, q1[0], q1[1], q1[2], q1[3], k0[1][2], k0[1][3]);
                        mma16(s2, q1[0], q1[1], q1[2], q1[3], k1[0][2], k1[0][3]);
                        mma16(s3, q1[0], q1[1], q1[2], q1[3], k1[1][2], k1[1][3]);
                        const float out[4] = {s0[0] + s1[2], s0[1] + s1[3], s2[0] + s3[2], s2[1] + s3[3]};
                        send_planes(ic<4>{}, dst, B_SC, out, nan);
                        if (!again.value) bar_arrive(12, 256);
                        TS(4);
                    } else if (w4 == 2) {
                        uint32_t q0[4], q1[4], km[2][4], q[4][4];
                        const uint32_t dst = sb_v + C_SL + 2048 + role * 256;
                        if (!again.value) nan = finish_projections();
                        ldsm_sum(q0, qa); ldsm_sum(km[0], ma); ldsm_sum(km[1], ma + 1024); ldsm_sum(q1, qa + 512);
                        __syncwarp();
#pragma unroll
                        for (int i = 0; i < 4; i++) ldsm4(q[i], qx + 256 + i * 1024);
                        float s0[4] = {0.f, 0.f, 0.f, 0.f}, s1[4] = {0.f, 0.f, 0.f, 0.f}, d0[4];
                        mma16(s0, q0[0], q0[1], q0[2], q0[3], km[0][0], km[0][1]);
                        mma16(s1, q0[0], q0[1], q0[2], q0[3], km[1][0], km[1][1]);
                        mma16(s0, q1[0], q1[1], q1[2], q1[3], km[0][2], km[0][3]);
                        mma16(s1, q1[0], q1[1], q1[2], q1[3], km[1][2], km[1][3]);
                        const float out[2] = {s0[0] + s1[2], s0[1] + s1[3]};
                        send_planes(ic<2>{}, dst, B_SC, out, nan);
                        if (!NOFILL) tile(d0, q, km);
                        if (!again.value) bar_sync(12, 256);
                        if (!NOFILL) send(0, d0, nan);
                    } else {
                        if (!again.value) {
                            nan = finish_projections();
                            if (s < NSEG - 1) load_tokens(s + 1, 1, 0);
                        }
                        uint32_t q[4][4], k0[2][4], k1[2][4], km[2][4];
                        float d0[4], d1[4], d2[4];
                        if (!NOFILL) {
#pragma unroll
                            for (int i = 0; i < 4; i++) ldsm4(q[i], qx + i * 1024);
                            ldsm4(k0[0], kl); ldsm4(k0[1], kl + 2048);
                            ldsm4(k1[0], kl + 128); ldsm4(k1[1], kl + 128 + 2048);
                            tile(d1, q, k0); tile(d2, q, k1);
                            ldsm_sum(km[0], ma); ldsm_sum(km[1], ma + 1024);
                            tile(d0, q, km);
                        }
                        if (!again.value) bar_sync(12, 256);
                        if (!NOFILL) { send(0, d0, nan); send(1, d1, nan); send(2, d2, nan); }
                    }
                    return nan;
                };
                if (__builtin_expect(__any_sync(~0u, scores(ic<0>{})), 0)) { repair(); scores(ic<1>{}); }
                if (__builtin_expect(s == NSEG - 1, 0)) break;
            } else {
                Stamps st1;
                load_stamps2(st1, g_flag[0], l16, w4 < 2);
                const bool nan = finish_projections();
                mbar_wait(bar + B_WS * 8, 0);
                missing = stamps_missing<6>(st1.v, s);
                target = latest_stamp<6>(st1.v, lds4u(sb + C_CAL)) + DLY1;
                if (!NOFILL) {
                    uint32_t q[4][4], k0[2][4];
                    float d1[4];
#pragma unroll
                    for (int i = 0; i < 4; i++) ldsm4(q[i], qx + 256 + i * 1024);
                    ldsm4(k0[0], kl + w4 * 128); ldsm4(k0[1], kl + w4 * 128 + 2048);
                    tile(d1, q, k0);
                    mbar_wait(bar + B_XF1 * 8, s == NSEG - 1);
                    bar_sync(12, 256);
                    send(1 + w4, d1, false);
                } else {
                    bar_sync(12, 256);
                }
                if (__builtin_expect(__any_sync(~0u, nan), 0)) repair();
                if (__builtin_expect(s == NSEG - 1, 0)) {
                    asm volatile("" : "+r"(l16));
                    if (w4 >= 2 && !NOFILL) token_softmax();
                    break;
                }
            }
        } else {
            const uint32_t lane_b = sb + C_V + w4 * 512 + ((l16 & 384) << 4) + (l16 & 112);
            auto load_values = [&](uint32_t (*vx)[4], uint32_t* vm, int ss) {
#pragma unroll
                for (int j = 0; j < 4; j++) ldsm4(vx[j], ((lane_b + (ss & 1) * 10240) ^ (j * 32)) + j * 128);
                ldsm4(vm, sb + C_V + (ss & 1) * 10240 + w4 * 512 + 8192 + (l16 ^ ((l16 >> 2) & 96)));
            };
            auto token_output = [&](int ss, auto mid) {
                uint32_t vx[4][4], vm[4];
                const uint32_t pl = sb + C_PL + (ss & 1) * 2048 + l16;
                auto lds_frag = [&](uint32_t a) { uint32_t r[4]; ldsm4(r, a); return make_uint4(r[0], r[1], r[2], r[3]); };
                load_values(vx, vm, ss);
                mid();
                uint32_t dep = 0;
#pragma unroll
                for (int mh = 1; mh >= 0; mh--) {
                    uint2 pm;
                    asm volatile("ldmatrix.sync.aligned.m8n8.x2.shared.b16 {%0,%1}, [%2];" : "=r"(pm.x), "=r"(pm.y) : "r"(pl + mh * 768 + dep) : "memory");
                    const uint4 p0 = lds_frag(pl + mh * 768 + 256);
                    float o[4][4];
#pragma unroll
                    for (int j = 0; j < 4; j++) { o[j][0] = o[j][1] = o[j][2] = o[j][3] = 0.f; mma8(o[j], pm.x, pm.y, vm[j]); }
#pragma unroll
                    for (int j = 0; j < 4; j++) mma16(o[j], p0.x, p0.y, p0.z, p0.w, vx[j][0], vx[j][1]);
                    if (mh) {
                        const uint4 p1 = lds_frag(pl + 1536);
#pragma unroll
                        for (int j = 0; j < 4; j++) mma16(o[j], p1.x, p1.y, p1.z, p1.w, vx[j][2], vx[j][3]);
                    }
                    oxp[2 * mh] = make_uint4(pack2(o[0][0], o[0][1]), pack2(o[1][0], o[1][1]), pack2(o[2][0], o[2][1]), pack2(o[3][0], o[3][1]));
                    oxp[2 * mh + 1] = make_uint4(pack2(o[0][2], o[0][3]), pack2(o[1][2], o[1][3]), pack2(o[2][2], o[2][3]), pack2(o[3][2], o[3][3]));
                    dep = oxp[2].x == ~0u ? 16 : 0;
                }
            };
            const uint32_t vd = v_row + (s & 1) * 10240 + 8192 + ((l16 & 96) << 2) + ((l16 & 112) ^ v_b ^ ((l16 & 128) >> 2));
            if (__builtin_expect(__any_sync(~0u, finish_projections()), 0)) repair();
            float r[4];
            ldsm4f(r, slot + (WG ^ 1) * 2048 + l16);
            __syncwarp();
            auto finish = [&]() {
                stsm2(vd, pack2(ck[0] + r[0], ck[1] + r[1]), pack2(ck[2] + r[2], ck[3] + r[3]));
                if (WG == 1) {
                    bar_arrive(11, 256);
                    if (w4 == 3 && l16 < 32) mbar_arrive_cluster(mapa(bar + B_VF * 8, 2 * hh + (l16 >> 4)));
                }
                TSX(3, WG == 0 && w4 == 0);
            };
            if (!NOFILL && WG == 1) {
                token_output(s - 1, [&]() { finish(); mbar_wait(bar + (B_P0 + ((s - 1) & 1)) * 8, ((s - 1) >> 1) & 1); });
                if (w4 == 1 && l16 == 0 && s > 0) mbar_expect(bar + (B_P0 + ((s - 1) & 1)) * 8, 2048);
                mbar_wait(bar + B_XF1 * 8, s == NSEG - 1);
            } else {
                finish();
            }
            if (WG == 0) bar_sync(11, 256);
            if (__builtin_expect(s == NSEG - 1, 0)) {
                bar_sync(6, 256);
                if (WG == 1) {
                    if (!NOFILL) {
                        store_ox(s - 1);
                        token_output(s, [&]() { mbar_wait(bar + (B_P0 + (s & 1)) * 8, (s >> 1) & 1); });
                        store_ox(s);
                    }
                    bar_sync(2, 128);
                    if (w4 == 0 && l16 == 0) {
                        if (NOFILL) for (int i = 0; i < 15; i++) count_up(CNT_OX + i);
                        count_up(CNT_OX + 15);
                    }
                    __syncwarp();
                }
                mbar_wait(bar + B_SC * 8, s & 1);
                break;
            }
            if constexpr (WG == 0) {
                uint32_t vx[4][4], vm[4];
                load_values(vx, vm, s);
                const uint32_t oo = u_off + ((l16 & 48) << 3) + ((l16 >> 2) & 112);
                char* dst = reinterpret_cast<char*>(&g_xo[s & 3][0]) + oo;
                if (w4 == 3) load_tokens(s + 1, 1, 0);
                mbar_wait(bar + B_SC * 8, s & 1);
                TS(4);
                float a0[4], b0[4], a1[4], b1[4], a2[4];
                ldsm4f(a0, sb + C_SL + l16); ldsm4f(b0, sb + C_SL + 1024 + l16);
                ldsm4f(a1, sb + C_SL + 512 + l16); ldsm4f(b1, sb + C_SL + 1536 + l16);
                ldsm4f(a2, sb + C_SL + 2048 + l16);
                const float e[10] = {a0[0] + b0[0], a0[1] + b0[1], a0[2] + b0[2], a0[3] + b0[3], a1[0] + b1[0], a1[1] + b1[1], a1[2] + b1[2], a1[3] + b1[3],
                                     a2[0] + a2[2], a2[1] + a2[3]};
                float m = fmaxf(fmaxf(fmaxf(e[0], e[1]), fmaxf(e[2], e[3])), fmaxf(fmaxf(e[4], e[5]), fmaxf(e[6], e[7])));
                m = fmaxf(m, fmaxf(e[8], e[9]));
                m = fmaxf(fmaxf(m, __shfl_xor_sync(~0u, m, 1)), fmaxf(__shfl_xor_sync(~0u, m, 2), __shfl_xor_sync(~0u, m, 3)));
                m *= -SM_SCALE;
                float x[10];
#pragma unroll
                for (int i = 0; i < 10; i++) x[i] = ex2(fmaf(e[i], SM_SCALE, m));
                float o[4][4];
                const uint32_t p0 = pack2(x[0], x[1]), p1 = pack2(x[2], x[3]), j0 = __float_as_uint(x[1]), j1 = __float_as_uint(x[3]);
#pragma unroll
                for (int j = 0; j < 4; j++) { o[j][0] = o[j][1] = o[j][2] = o[j][3] = 0.f; mma16(o[j], p0, j0, p1, j1, vx[j][0], vx[j][1]); }
                const uint32_t p2 = pack2(x[4], x[5]), p3 = pack2(x[6], x[7]), j2 = __float_as_uint(x[5]), j3 = __float_as_uint(x[7]);
#pragma unroll
                for (int j = 0; j < 4; j++) mma16(o[j], p2, j2, p3, j3, vx[j][2], vx[j][3]);
                const uint32_t p4 = pack2(x[8], x[9]), j4 = __float_as_uint(x[9]);
                float l = (((x[0] + x[1]) + (x[2] + x[3])) + ((x[4] + x[5]) + (x[6] + x[7]))) + (x[8] + x[9]);
                l = (l + __shfl_xor_sync(~0u, l, 1)) + (__shfl_xor_sync(~0u, l, 2) + __shfl_xor_sync(~0u, l, 3));
#pragma unroll
                for (int j = 0; j < 4; j++) mma8(o[j], p4, j4, vm[j]);
                l = rcp(l);
                st_relaxed4(reinterpret_cast<uint4*>(dst), make_uint4(pack2(o[0][0] * l, o[0][1] * l), pack2(o[1][0] * l, o[1][1] * l),
                                                                      pack2(o[2][0] * l, o[2][1] * l), pack2(o[3][0] * l, o[3][1] * l)));
                bar_arrive(3, 256);
                if (w4 == 0 && l16 == 0) mbar_expect(bar + B_SC * 8, 2560);
            }
        }
    }
}

__global__ void __cluster_dims__(6, 1, 1) __launch_bounds__(256, 1)
chain_kernel(const __grid_constant__ CUtensorMap tq, const __grid_constant__ CUtensorMap tk, const __grid_constant__ CUtensorMap tv,
             const __grid_constant__ CUtensorMap two, const __grid_constant__ Descs D, const __grid_constant__ Descs DV,
             const __nv_bfloat16* __restrict__ x, const __nv_bfloat16* __restrict__ mem0) {
    extern __shared__ __align__(1024) uint8_t smem[];
    const uint32_t sb = smem_u32(smem);
    const int rank = blockIdx.x % 6, cl = blockIdx.x / 6, role = rank >= 4 ? 2 : rank & 1;
    const int tid = threadIdx.x, lane = tid & 31, gw = blockIdx.x * 8 + uni(tid >> 5);
    const CUtensorMap *tA = role == 2 ? &tv : &tq, *tB = role == 2 ? &tv : &tk;
    uint4 cur[4], nxt[4];
#pragma unroll
    for (int j = 0; j < 4; j++) {
        cur[j] = reinterpret_cast<const uint4*>(x)[gw * 128 + j * 32 + lane];
        nxt[j] = reinterpret_cast<const uint4*>(x)[(gw + 768) * 128 + j * 32 + lane];
    }
    if (gw < 512 && lane < 16) asm volatile("prefetch.global.L2 [%0];" :: "l"(x + (gw + 1536) * DM + lane * 64));
    if ((gw & 7) == 0) {
        if (tid == 0) { TL(1, 0); TLSM(1); }
        if ((sb & 0xFFFFFF) != SB0 || mapa(sb, 5) != (SB0 | 0x5000000u)) sts1u(1, 0);
        const uint32_t b = sb + C_BAR + lane * 8;
        uint32_t tx = 0;
        if (lane <= B_WS) tx = 65536;
        if (lane == B_MF0 || lane == B_MF1) tx = 8192;
        if (lane == B_OF) tx = (role == 2 ? ONKV : ONKQ) * (256 + 2048);
        if (lane == B_SC) tx = 2560;
        if (lane == B_P0 || lane == B_P1) tx = 2048;
        if (lane == B_XS || lane == B_OL) tx = (lane == B_XS && role) ? 5120 : 3072;
        if (lane < B_NUM) mbar_init(b, lane == B_MBF ? 12 : (lane == B_GO ? 4 : 1));
        if (tx) mbar_expect(b, tx);
        asm volatile("fence.mbarrier_init.release.cluster;" ::: "memory");
        fence_async();
        __syncwarp();
#pragma unroll 1
        for (int i = 0; i < 12; i++)
            if (elect()) load_box(tA, tB, cl, rank, sb + (i >> 2) * 65536, i >> 2, i & 3, sb + C_BAR + (i >> 2) * 8);
    }
    __syncwarp();
    asm volatile("barrier.cluster.arrive.release.aligned;" ::: "memory");
    reset_exchange(mem0);
#pragma unroll 1
    for (int row = gw; row < SEQ; row += 768) {
        uint4 v[4];
#pragma unroll
        for (int j = 0; j < 4; j++) {
            v[j] = cur[j]; cur[j] = nxt[j];
            if (row + 1536 < SEQ) nxt[j] = reinterpret_cast<const uint4*>(x)[(row + 1536) * 128 + j * 32 + lane];
        }
        ln_row(v, row, lane);
    }
    if (tid == 0) TL(1, 5);
    __syncthreads();
    uint32_t goal = 0;
    if (tid == 160) {
        __threadfence();
        goal = (atomicAdd(&g_epoch, 1u) / 96 + 1) * 96;
        asm volatile("griddepcontrol.launch_dependents;" ::: "memory");
        TL(1, 4);
    }
    __syncwarp();
    asm volatile("barrier.cluster.wait.acquire.aligned;" ::: "memory");
    goal = uni(goal);
    const int wg = uni(threadIdx.x >> 7);
    if (role == 2) {
        if (wg == 0) chain_main<true, 0>(&tv, &tv, &two, sb, cl, rank, DV, goal);
        else chain_main<true, 1>(&tv, &tv, &two, sb, cl, rank, DV, goal);
    } else {
        if (wg == 0) chain_main<false, 0>(&tq, &tk, &two, sb, cl, rank, D, goal);
        else chain_main<false, 1>(&tq, &tk, &two, sb, cl, rank, D, goal);
    }
    __syncwarp();
    cluster_sync();
    if (threadIdx.x == 0) TL(1, 1);
}

__device__ __forceinline__ void wg256(float* d, uint32_t da, uint32_t db, uint32_t accum) {
    asm volatile("{\n.reg .b64 da, db;\n.reg .pred p;\nsetp.ne.u32 p, %130, 0;\nmov.b64 da, {%128, " DESC_HI_SW128 "};\nmov.b64 db, {%129, " DESC_HI_SW128 "};\n"
                 "wgmma.mma_async.sync.aligned.m64n256k16.f32.bf16.bf16 {"
                 "%0,%1,%2,%3,%4,%5,%6,%7,%8,%9,%10,%11,%12,%13,%14,%15,%16,%17,%18,%19,%20,%21,%22,%23,%24,%25,%26,%27,%28,%29,%30,%31,"
                 "%32,%33,%34,%35,%36,%37,%38,%39,%40,%41,%42,%43,%44,%45,%46,%47,%48,%49,%50,%51,%52,%53,%54,%55,%56,%57,%58,%59,%60,%61,%62,%63,"
                 "%64,%65,%66,%67,%68,%69,%70,%71,%72,%73,%74,%75,%76,%77,%78,%79,%80,%81,%82,%83,%84,%85,%86,%87,%88,%89,%90,%91,%92,%93,%94,%95,"
                 "%96,%97,%98,%99,%100,%101,%102,%103,%104,%105,%106,%107,%108,%109,%110,%111,%112,%113,%114,%115,%116,%117,%118,%119,%120,%121,%122,%123,%124,%125,%126,%127"
                 "}, da, db, p, 1, 1, 0, 1;\n}"
                 : ACC16(d), ACC16((d + 16)), ACC16((d + 32)), ACC16((d + 48)), ACC16((d + 64)), ACC16((d + 80)), ACC16((d + 96)), ACC16((d + 112))
                 : "r"(da), "r"(db), "r"(accum));
}
__device__ __forceinline__ void wg128(float* d, uint32_t da, uint32_t db, uint32_t accum) {
    asm volatile("{\n.reg .b64 da, db;\n.reg .pred p;\nsetp.ne.u32 p, %66, 0;\nmov.b64 da, {%64, " DESC_HI_SW128 "};\nmov.b64 db, {%65, " DESC_HI_SW128 "};\n"
                 "wgmma.mma_async.sync.aligned.m64n128k16.f32.bf16.bf16 {"
                 "%0,%1,%2,%3,%4,%5,%6,%7,%8,%9,%10,%11,%12,%13,%14,%15,%16,%17,%18,%19,%20,%21,%22,%23,%24,%25,%26,%27,%28,%29,%30,%31,"
                 "%32,%33,%34,%35,%36,%37,%38,%39,%40,%41,%42,%43,%44,%45,%46,%47,%48,%49,%50,%51,%52,%53,%54,%55,%56,%57,%58,%59,%60,%61,%62,%63"
                 "}, da, db, p, 1, 1, 0, 1;\n}"
                 : ACC16(d), ACC16((d + 16)), ACC16((d + 32)), ACC16((d + 48))
                 : "r"(da), "r"(db), "r"(accum));
}
__device__ __forceinline__ float sigmoidf_(float v) { return rcp(1.f + ex2(-1.4426950408889634f * v)); }
__device__ __forceinline__ void wait_count(int idx, uint32_t n) {
    uint32_t v, it = 0;
    while (true) {
        asm volatile("ld.acquire.gpu.global.u32 %0, [%1];" : "=r"(v) : "l"(&g_cnt[idx * 8]) : "memory");
        if (v >= n) break;
        __nanosleep(100);
        spin_guard(it);
    }
    asm volatile("fence.proxy.async.global;" ::: "memory");
}

constexpr int G_STAGES = 4, G_PAIRS = 18;
constexpr uint32_t G_STAGE = 49152, G_EPI = G_STAGES * G_STAGE, G_BAR = G_EPI + 32768, G_SMEM = G_BAR + 256;
__device__ __forceinline__ int glu_job(int p, int j) {
    if (j < 12) return j * G_PAIRS + p;
    if (p < 14) return j == 12 ? 224 + p : (j == 13 ? 242 + p : -1);
    return j < 14 ? 216 + (j - 12) * 4 + (p - 14) : (j == 14 ? 224 + p : -1);
}

__global__ void __cluster_dims__(2, 1, 1) __launch_bounds__(384, 1)
glu_kernel(const __grid_constant__ CUtensorMap tXn, const __grid_constant__ CUtensorMap tG, const __grid_constant__ CUtensorMap tU,
           const __grid_constant__ CUtensorMap tHst, const __grid_constant__ CUtensorMap tHld, const __grid_constant__ CUtensorMap tD,
           const __grid_constant__ CUtensorMap tYst) {
    extern __shared__ __align__(1024) uint8_t smem[];
    const uint32_t sb = smem_u32(smem);
    const uint32_t full = sb + G_BAR, empty = full + 64;
    const int tid = threadIdx.x, lane = tid & 31;
    const int warp = uni(tid >> 5), wg = warp >> 2;
    const int rank = blockIdx.x & 1, pair = blockIdx.x >> 1;
    asm volatile("griddepcontrol.launch_dependents;" ::: "memory");
    if (tid == 0) {
        TL(2, 0); TLSM(2);
        for (int i = 0; i < G_STAGES; i++) { mbar_init(full + i * 8, 1); mbar_init(empty + i * 8, 16); }
        asm volatile("fence.mbarrier_init.release.cluster;" ::: "memory");
        fence_async();
    }
    __syncthreads();
    cluster_sync();
    if (wg == 0) {
        asm volatile("setmaxnreg.dec.sync.aligned.u32 40;");
        if (warp == 0) {
            if (lane == 0) {
                uint32_t st = 0, ph = 1;
                asm volatile("fence.acq_rel.gpu;\nfence.proxy.async.global;" ::: "memory");
                for (int j = 0, job; (job = glu_job(pair, j)) >= 0; j++) {
                    const bool dn = job >= 224;
                    const int mp = dn ? (job - 224) >> 2 : job / 28, nt = dn ? job & 3 : job % 28, rb = mp * 2 + rank;
                    const CUtensorMap* tA = dn ? &tHld : &tXn;
                    const CUtensorMap* tB = dn ? &tD : (rank ? &tU : &tG);
                    const int bcol = dn ? nt * 256 + rank * 128 : nt * 128, nkb = dn ? FF / 64 : DM / 64;
                    if (j == 12) TL(2, 2);
                    if (dn) wait_count(CNT_H + rb, 56);
                    for (int kb = 0; kb < nkb; kb++) {
                        mbar_wait(empty + st * 8, ph);
                        const uint32_t base = sb + st * G_STAGE;
                        mbar_expect(full + st * 8, G_STAGE);
                        tma2d(base, tA, kb * 64, rb * 128, full + st * 8);
                        tma2d_mc(base + 16384 + rank * 16384, tB, bcol, kb * 64, full + st * 8, 3);
                        tma2d_mc(base + 16384 + rank * 16384 + 8192, tB, bcol + 64, kb * 64, full + st * 8, 3);
                        if (++st == G_STAGES) { st = 0; ph ^= 1; }
                    }
                }
            }
        } else if (warp < 3) {
            const int cw = warp - 1;
            const uint32_t epi = sb + G_EPI + cw * 16384;
            bar_arrive(3 + cw, 160);
            for (int j = 0, job; (job = glu_job(pair, j)) >= 0; j++) {
                const bool dn = job >= 224;
                const int mp = dn ? (job - 224) >> 2 : job / 28, nt = dn ? job & 3 : job % 28, rb = mp * 2 + rank;
                for (int hp = 0; hp <= (int)dn; hp++) {
                    bar_sync(1 + cw, 160);
                    if (lane == 0) {
                        const int col = dn ? nt * 256 + hp * 128 : nt * 128;
                        tma2d_store(dn ? &tYst : &tHst, col, rb * 128 + cw * 64, epi);
                        tma2d_store(dn ? &tYst : &tHst, col + 64, rb * 128 + cw * 64, epi + 8192);
                        asm volatile("cp.async.bulk.commit_group;\ncp.async.bulk.wait_group.read 0;" ::: "memory");
                    }
                    __syncwarp();
                    bar_arrive(3 + cw, 160);
                    if (lane == 0) {
                        asm volatile("cp.async.bulk.wait_group 0;\nfence.proxy.async.global;" ::: "memory");
                        count_up(dn ? CNT_Y + rb * 8 + nt * 2 + hp : CNT_H + rb);
                    }
                    __syncwarp();
                }
            }
        }
        cluster_sync();
    } else {
        asm volatile("setmaxnreg.inc.sync.aligned.u32 232;");
        const int cw = wg - 1, w4 = warp & 3;
        const uint32_t empty_dst = mapa(empty, lane & 1);
        const int er = w4 * 16 + (lane & 15), ec = lane >> 4;
        const uint32_t epi = sb + G_EPI + cw * 16384 + er * 128;
        uint32_t st = 0, ph = 0;
        float acc[128];
        auto put = [&](const uint32_t* o) {
            bar_sync(3 + cw, 160);
#pragma unroll
            for (int q = 0; q < 8; q++) stsm4(epi + (q >> 2) * 8192 + (((2 * (q & 3) + ec) ^ (er & 7)) << 4), o[q * 4], o[q * 4 + 1], o[q * 4 + 2], o[q * 4 + 3]);
            fence_async();
            bar_arrive(1 + cw, 160);
        };
        for (int j = 0, job; (job = glu_job(pair, j)) >= 0; j++) {
            const bool dn = job >= 224;
            const int nkb = dn ? FF / 64 : DM / 64;
            uint32_t prev = 0;
#pragma unroll 1
            for (int kb = 0; kb < nkb; kb++) {
                mbar_wait(full + st * 8, ph);
                const uint32_t base = sb + st * G_STAGE;
                const uint32_t da = (((base + cw * 8192) & 0x3FFFF) >> 4) | (1u << 16);
                const uint32_t db = (((base + 16384) & 0x3FFFF) >> 4) | (512u << 16);
                wg_fence();
#pragma unroll
                for (int k = 0; k < 4; k++) wg256(acc, da + k * 2, db + k * 128, (kb | k) != 0);
                wg_commit();
                if (kb > 0) {
                    wg_wait<1>();
                    if (lane < 2) mbar_arrive_cluster(empty_dst + prev * 8);
                }
                prev = st;
                if (++st == G_STAGES) { st = 0; ph ^= 1; }
            }
            wg_wait<0>();
            reg_fence<128>(acc);
            if (lane < 2) mbar_arrive_cluster(empty_dst + prev * 8);
            uint32_t o[32];
            if (!dn) {
#pragma unroll
                for (int i = 0; i < 32; i++) o[i] = pack2(sigmoidf_(acc[2 * i]) * acc[64 + 2 * i], sigmoidf_(acc[2 * i + 1]) * acc[65 + 2 * i]);
                put(o);
            } else {
#pragma unroll
                for (int hp = 0; hp < 2; hp++) {
#pragma unroll
                    for (int i = 0; i < 32; i++) {
                        const float a = acc[hp * 64 + 2 * i], b = acc[hp * 64 + 2 * i + 1];
                        o[i] = pack2(sigmoidf_(a) * a, sigmoidf_(b) * b);
                    }
                    put(o);
                }
            }
        }
        bar_sync(3 + cw, 160);
        if (tid == 128) TL(2, 1);
        cluster_sync();
    }
}

constexpr int O_STAGES = 7;
constexpr uint32_t O_STAGE = 32768, O_BAR = O_STAGES * O_STAGE, O_SMEM = O_BAR + 256;

__global__ void __cluster_dims__(2, 1, 1) __launch_bounds__(384, 1)
out_kernel(const __grid_constant__ CUtensorMap tOx, const __grid_constant__ CUtensorMap tWo, const __grid_constant__ CUtensorMap tX,
           const __grid_constant__ CUtensorMap tY, const __grid_constant__ CUtensorMap tOut) {
    extern __shared__ __align__(1024) uint8_t smem[];
    const uint32_t sb = smem_u32(smem);
    const uint32_t full = sb + O_BAR, empty = full + 64;
    const int tid = threadIdx.x, lane = tid & 31;
    const int warp = uni(tid >> 5), wg = warp >> 2;
    const int rank = blockIdx.x & 1, nt = (blockIdx.x >> 1) & 7, rb = (blockIdx.x >> 4) * 2 + rank;
    constexpr int NKB = HD / 64;
    if (tid == 0) {
        TL(3, 0); TLSM(3);
        for (int i = 0; i < O_STAGES; i++) { mbar_init(full + i * 8, 1); mbar_init(empty + i * 8, 16); }
        asm volatile("fence.mbarrier_init.release.cluster;" ::: "memory");
        fence_async();
    }
    __syncthreads();
    cluster_sync();
    if (wg == 0) {
        if (tid == 0) {
            uint32_t st = 0, ph = 1;
            for (int kb = 0; kb < O_STAGES; kb++) {
                mbar_expect(full + kb * 8, O_STAGE);
                tma2d_mc(sb + kb * O_STAGE + 16384 + rank * 8192, &tWo, nt * 128 + rank * 64, kb * 64, full + kb * 8, 3);
            }
            wait_count(CNT_OX + rb, 32);
            TL(3, 2);
            for (int kb = 0; kb < NKB + 2; kb++) {
                const uint32_t base = sb + st * O_STAGE;
                if (kb >= O_STAGES) {
                    mbar_wait(empty + st * 8, ph);
                    mbar_expect(full + st * 8, O_STAGE);
                }
                if (kb < NKB) {
                    tma2d(base, &tOx, kb * 64, rb * 128, full + st * 8);
                    if (kb >= O_STAGES) tma2d_mc(base + 16384 + rank * 8192, &tWo, nt * 128 + rank * 64, kb * 64, full + st * 8, 3);
                } else {
                    if (kb == NKB) wait_count(CNT_Y + rb * 8 + nt, 2);
                    tma2d(base, &tX, nt * 128 + (kb - NKB) * 64, rb * 128, full + st * 8);
                    tma2d(base + 16384, &tY, nt * 128 + (kb - NKB) * 64, rb * 128, full + st * 8);
                }
                if (++st == O_STAGES) { st = 0; ph ^= 1; }
            }
        }
        __syncwarp();
    } else {
        const int cw = wg - 1, w4 = warp & 3;
        const uint32_t empty_dst = mapa(empty, lane & 1);
        const int er = cw * 64 + w4 * 16 + (lane & 15), ec = lane >> 4;
        uint32_t st = 0, ph = 0, prev = 0;
        float acc[64];
#pragma unroll 1
        for (int kb = 0; kb < NKB; kb++) {
            mbar_wait(full + st * 8, ph);
            const uint32_t base = sb + st * O_STAGE;
            const uint32_t da = (((base + cw * 8192) & 0x3FFFF) >> 4) | (1u << 16);
            const uint32_t db = (((base + 16384) & 0x3FFFF) >> 4) | (512u << 16);
            wg_fence();
#pragma unroll
            for (int k = 0; k < 4; k++) wg128(acc, da + k * 2, db + k * 128, (kb | k) != 0);
            wg_commit();
            if (kb > 0) {
                wg_wait<1>();
                if (lane < 2) mbar_arrive_cluster(empty_dst + prev * 8);
            }
            prev = st;
            if (++st == O_STAGES) { st = 0; ph ^= 1; }
        }
        wg_wait<0>();
        reg_fence<64>(acc);
#pragma unroll
        for (int bx = 0; bx < 2; bx++) {
            mbar_wait(full + st * 8, ph);
            const uint32_t base = sb + st * O_STAGE;
#pragma unroll
            for (int j = 0; j < 4; j++) {
                uint32_t xv[4], yv[4];
                const uint32_t ad = base + er * 128 + (((2 * j + ec) ^ (er & 7)) << 4);
                ldsm4(xv, ad); ldsm4(yv, ad + 16384);
                const float* a = acc + bx * 32 + j * 8;
#pragma unroll
                for (int i = 0; i < 4; i++)
                    xv[i] = pack2(fmaf(a[2 * i], bf_lo(yv[i]), bf_lo(xv[i])), fmaf(a[2 * i + 1], bf_hi(yv[i]), bf_hi(xv[i])));
                stsm4(ad, xv[0], xv[1], xv[2], xv[3]);
            }
            fence_async();
            bar_sync(1 + cw, 128);
            if ((tid & 127) == 0) {
                tma2d_store(&tOut, nt * 128 + bx * 64, rb * 128 + cw * 64, base + cw * 8192);
                asm volatile("cp.async.bulk.commit_group;" ::: "memory");
            }
            if (++st == O_STAGES) { st = 0; ph ^= 1; }
        }
        if ((tid & 127) == 0) asm volatile("cp.async.bulk.wait_group 0;" ::: "memory");
        if (tid == 128) TL(3, 1);
        __syncwarp();
    }
    cluster_sync();
}

typedef CUresult (*EncodeFn)(CUtensorMap*, CUtensorMapDataType, cuuint32_t, void*, const cuuint64_t*, const cuuint64_t*, const cuuint32_t*,
                             const cuuint32_t*, CUtensorMapInterleave, CUtensorMapSwizzle, CUtensorMapL2promotion, CUtensorMapFloatOOBfill);

CUtensorMap make_map(EncodeFn enc, const void* p, int rows, int cols, int box_rows) {
    CUtensorMap m;
    cuuint64_t dims[2] = {(cuuint64_t)cols, (cuuint64_t)rows}, strides[1] = {(cuuint64_t)cols * 2};
    cuuint32_t box[2] = {64, (cuuint32_t)box_rows}, es[2] = {1, 1};
    enc(&m, CU_TENSOR_MAP_DATA_TYPE_BFLOAT16, 2, const_cast<void*>(p), dims, strides, box, es, CU_TENSOR_MAP_INTERLEAVE_NONE,
        CU_TENSOR_MAP_SWIZZLE_128B, CU_TENSOR_MAP_L2_PROMOTION_L2_128B, CU_TENSOR_MAP_FLOAT_OOB_FILL_NONE);
    return m;
}

}

#define PDL 7
extern "C" void kernel_launch(void* const* d_in, const int* in_sizes, int n_in, void* d_out, int out_size) {
    const __nv_bfloat16* x = (const __nv_bfloat16*)d_in[0];
    const __nv_bfloat16* mem0 = (const __nv_bfloat16*)d_in[1];
    void* fn = nullptr;
    cudaDriverEntryPointQueryResult qr;
    cudaGetDriverEntryPoint("cuTensorMapEncodeTiled", &fn, cudaEnableDefault, &qr);
    EncodeFn enc = (EncodeFn)fn;
    void *xn, *ox, *h, *y;
    cudaGetSymbolAddress(&xn, g_xn); cudaGetSymbolAddress(&ox, g_ox); cudaGetSymbolAddress(&h, g_h); cudaGetSymbolAddress(&y, g_y);

    const CUtensorMap tq = make_map(enc, d_in[2], DM, HD, 128), tk = make_map(enc, d_in[3], DM, HD, 128), tv = make_map(enc, d_in[4], DM, HD, 128);
    const CUtensorMap two16 = make_map(enc, d_in[5], HD, DM, 16);
    const CUtensorMap txn128 = make_map(enc, xn, SEQ, DM, 128), tg = make_map(enc, d_in[8], DM, FF, 64), tu = make_map(enc, d_in[9], DM, FF, 64);
    const CUtensorMap th64 = make_map(enc, h, SEQ, FF, 64), th128 = make_map(enc, h, SEQ, FF, 128), td = make_map(enc, d_in[10], FF, DM, 64);
    const CUtensorMap ty64 = make_map(enc, y, SEQ, DM, 64), ty128 = make_map(enc, y, SEQ, DM, 128), tx128 = make_map(enc, x, SEQ, DM, 128);
    const CUtensorMap tox = make_map(enc, ox, SEQ, HD, 128), two64 = make_map(enc, d_in[5], HD, DM, 64), tout = make_map(enc, d_out, SEQ, DM, 64);

    cudaFuncSetAttribute(chain_kernel, cudaFuncAttributeMaxDynamicSharedMemorySize, C_SMEM);
    cudaFuncSetAttribute(glu_kernel, cudaFuncAttributeMaxDynamicSharedMemorySize, G_SMEM);
    cudaFuncSetAttribute(out_kernel, cudaFuncAttributeMaxDynamicSharedMemorySize, O_SMEM);

    Descs D;
    for (int i = 0; i < 4; i++) D.sw[i] = DSW;
    D.ns = DNS;
    cudaStream_t st = cudaStreamPerThread;
    cudaLaunchAttribute at;
    at.id = cudaLaunchAttributeProgrammaticStreamSerialization;
    at.val.programmaticStreamSerializationAllowed = 1;
    cudaLaunchConfig_t cfg = {};
    cfg.stream = st; cfg.attrs = &at; cfg.numAttrs = 0;
    cfg.gridDim = dim3(96); cfg.blockDim = dim3(256); cfg.dynamicSmemBytes = C_SMEM;
    cudaLaunchKernelEx(&cfg, chain_kernel, tq, tk, tv, two16, D, D, x, mem0);
    cfg.gridDim = dim3(2 * G_PAIRS); cfg.blockDim = dim3(384); cfg.dynamicSmemBytes = G_SMEM; cfg.numAttrs = (PDL >> 1) & 1;
    cudaLaunchKernelEx(&cfg, glu_kernel, txn128, tg, tu, th64, th128, td, ty64);
    cfg.gridDim = dim3(128); cfg.dynamicSmemBytes = O_SMEM; cfg.numAttrs = (PDL >> 2) & 1;
    cudaLaunchKernelEx(&cfg, out_kernel, tox, two64, tx128, ty128, tout);
}
```

```cpp
#include <cuda_runtime.h>
#include <cuda_bf16.h>
#include <cuda.h>
#include <stdint.h>
#include <type_traits>

namespace {

constexpr int SEQ = 2048, DM = 1024, HD = 4096, FF = 3584, NSEG = 64;

__device__ __align__(1024) __nv_bfloat16 g_xn[SEQ * DM];
__device__ __align__(1024) uint4 g_xc[SEQ * DM / 8];
__device__ __align__(1024) __nv_bfloat16 g_ox[SEQ * HD];
__device__ __align__(1024) __nv_bfloat16 g_h[SEQ * FF];
__device__ __align__(1024) __nv_bfloat16 g_y[SEQ * DM];
__device__ __align__(1024) uint4 g_xmem[4][1024];
__device__ __align__(1024) uint4 g_xo[4][4096];
#define FSTR 8
__device__ __align__(1024) uint32_t g_flag[1][96 * FSTR];
enum { CNT_H = 0, CNT_OX = 16, CNT_Y = 32, CNT_NUM = 160 };
__device__ __align__(1024) uint32_t g_cnt[CNT_NUM * 8];
__device__ __align__(128) uint32_t g_epoch;
#define TL(k, i)
#define TLSM(k)

__device__ __forceinline__ uint32_t smem_u32(const void* p) { return (uint32_t)__cvta_generic_to_shared(p); }
__device__ __forceinline__ uint32_t mapa(uint32_t a, uint32_t r) {
    uint32_t o; asm("mapa.shared::cluster.u32 %0, %1, %2;" : "=r"(o) : "r"(a), "r"(r)); return o;
}
__device__ __forceinline__ void mbar_init(uint32_t a, uint32_t cnt) {
    asm volatile("mbarrier.init.shared.b64 [%0], %1;" :: "r"(a), "r"(cnt) : "memory");
}
__device__ __forceinline__ void mbar_expect(uint32_t a, uint32_t bytes) {
    asm volatile("mbarrier.arrive.expect_tx.shared.b64 _, [%0], %1;" :: "r"(a), "r"(bytes) : "memory");
}
__device__ __forceinline__ void mbar_arrive_cluster(uint32_t a) {
    asm volatile("mbarrier.arrive.shared::cluster.b64 _, [%0];" :: "r"(a) : "memory");
}
__device__ __forceinline__ void spin_guard(uint32_t& it) {
    asm volatile("{\n.reg .pred p;\nadd.u32 %0, %0, 1;\nsetp.gt.u32 p, %0, 0x400000;\n@p st.shared.u32 [%0], %0;\n}" : "+r"(it));
}
__device__ __forceinline__ void mbar_wait(uint32_t a, uint32_t par) {
    asm volatile("{\n.reg .pred p;\nWL:\nmbarrier.try_wait.parity.shared::cta.b64 p, [%0], %1;\n@!p bra WL;\n}" :: "r"(a), "r"(par) : "memory");
}
__device__ __forceinline__ void mbar_arrive(uint32_t a) { asm volatile("mbarrier.arrive.shared.b64 _, [%0];" :: "r"(a) : "memory"); }
__device__ __forceinline__ void tma2d(uint32_t dst, const CUtensorMap* m, int c0, int c1, uint32_t bar) {
    asm volatile("cp.async.bulk.tensor.2d.shared::cluster.global.mbarrier::complete_tx::bytes [%0], [%1, {%3, %4}], [%2];"
                 :: "r"(dst), "l"(m), "r"(bar), "r"(c0), "r"(c1) : "memory");
}
__device__ __forceinline__ void tma2d_mc(uint32_t dst, const CUtensorMap* m, int c0, int c1, uint32_t bar, uint16_t mask) {
    asm volatile("cp.async.bulk.tensor.2d.shared::cluster.global.mbarrier::complete_tx::bytes.multicast::cluster [%0], [%1, {%3, %4}], [%2], %5;"
                 :: "r"(dst), "l"(m), "r"(bar), "r"(c0), "r"(c1), "h"(mask) : "memory");
}
__device__ __forceinline__ void bulk_mc(uint32_t dst, const void* src, uint32_t bytes, uint32_t bar, uint16_t mask) {
    asm volatile("cp.async.bulk.shared::cluster.global.mbarrier::complete_tx::bytes.multicast::cluster [%0], [%1], %2, [%3], %4;"
                 :: "r"(dst), "l"(src), "r"(bytes), "r"(bar), "h"(mask) : "memory");
}
__device__ __forceinline__ void bulk_ld(uint32_t dst, const void* src, uint32_t bytes, uint32_t bar) {
    asm volatile("cp.async.bulk.shared::cluster.global.mbarrier::complete_tx::bytes [%0], [%1], %2, [%3];"
                 :: "r"(dst), "l"(src), "r"(bytes), "r"(bar) : "memory");
}
__device__ __forceinline__ uint32_t gtick() { uint64_t c; asm volatile("mov.u64 %0, %%globaltimer;" : "=l"(c)); return (uint32_t)c >> 5; }
__device__ __forceinline__ uint32_t gtick_dep(uint32_t zero) {
    uint32_t c;
    asm volatile("{\n.reg .pred p;\nsetp.eq.u32 p, %1, 0;\nmov.u32 %0, 0;\n@p mov.u32 %0, %%globaltimer_lo;\n}" : "=r"(c) : "r"(zero));
    return c >> 5;
}
__device__ __forceinline__ uint32_t ld_relaxed1(const void* p) {
    uint32_t v; asm volatile("ld.relaxed.gpu.global.u32 %0, [%1];" : "=r"(v) : "l"(p) : "memory"); return v;
}
__device__ __forceinline__ bool any_nan(float a, float b) {
    uint32_t r;
    asm volatile("{\n.reg .pred p;\nsetp.nan.f32 p, %1, %2;\nvote.sync.any.pred p, p, 0xffffffff;\nselp.u32 %0, 1, 0, p;\n}" : "=r"(r) : "f"(a), "f"(b));
    return r;
}
__device__ __forceinline__ bool bar_sync_any_nan(float a, float b) {
    uint32_t r;
    asm volatile("{\n.reg .pred p;\nsetp.nan.f32 p, %1, %2;\nbarrier.cta.red.or.aligned.pred p, 6, 256, p;\nselp.u32 %0, 1, 0, p;\n}"
                 : "=r"(r) : "f"(a), "f"(b) : "memory");
    return r;
}
__device__ __forceinline__ void bar_arrive(int id, int n) { asm volatile("bar.arrive %0, %1;" :: "r"(id), "r"(n) : "memory"); }
__device__ __forceinline__ uint32_t clk() { uint64_t c; asm volatile("mov.u64 %0, %%clock64;" : "=l"(c)); return (uint32_t)c; }
__device__ __forceinline__ void tma2d_store(const CUtensorMap* m, int c0, int c1, uint32_t src) {
    asm volatile("cp.async.bulk.tensor.2d.global.shared::cta.bulk_group [%0, {%1, %2}], [%3];"
                 :: "l"(m), "r"(c0), "r"(c1), "r"(src) : "memory");
}
__device__ __forceinline__ void bar_sync(int id, int n) { asm volatile("bar.sync %0, %1;" :: "r"(id), "r"(n) : "memory"); }
__device__ __forceinline__ void fence_async() { asm volatile("fence.proxy.async.shared::cta;" ::: "memory"); }
__device__ __forceinline__ void cluster_sync() {
    asm volatile("barrier.cluster.arrive.release.aligned;\nbarrier.cluster.wait.acquire.aligned;" ::: "memory");
}
__device__ __forceinline__ void ldsm4(uint32_t* r, uint32_t a) {
    asm volatile("ldmatrix.sync.aligned.m8n8.x4.shared.b16 {%0,%1,%2,%3}, [%4];"
                 : "=r"(r[0]), "=r"(r[1]), "=r"(r[2]), "=r"(r[3]) : "r"(a) : "memory");
}
__device__ __forceinline__ void ldsm4t(uint32_t* r, uint32_t a) {
    asm volatile("ldmatrix.sync.aligned.m8n8.x4.trans.shared.b16 {%0,%1,%2,%3}, [%4];"
                 : "=r"(r[0]), "=r"(r[1]), "=r"(r[2]), "=r"(r[3]) : "r"(a) : "memory");
}
__device__ __forceinline__ void stsm4(uint32_t a, uint32_t r0, uint32_t r1, uint32_t r2, uint32_t r3) {
    asm volatile("stmatrix.sync.aligned.m8n8.x4.shared.b16 [%0], {%1,%2,%3,%4};" :: "r"(a), "r"(r0), "r"(r1), "r"(r2), "r"(r3) : "memory");
}
__device__ __forceinline__ void stsm4f(uint32_t a, const float* v) {
    asm volatile("{\n.reg .b32 a, b, c, d;\nmov.b32 a, %1;\nmov.b32 b, %2;\nmov.b32 c, %3;\nmov.b32 d, %4;\n"
                 "stmatrix.sync.aligned.m8n8.x4.shared.b16 [%0], {a, b, c, d};\n}" :: "r"(a), "f"(v[0]), "f"(v[1]), "f"(v[2]), "f"(v[3]) : "memory");
}
__device__ __forceinline__ void ldsm4f(float* v, uint32_t a) {
    uint32_t r[4];
    ldsm4(r, a);
#pragma unroll
    for (int i = 0; i < 4; i++) v[i] = __uint_as_float(r[i]);
}
__device__ __forceinline__ void stsm4t(uint32_t a, uint32_t r0, uint32_t r1, uint32_t r2, uint32_t r3) {
    asm volatile("stmatrix.sync.aligned.m8n8.x4.trans.shared.b16 [%0], {%1,%2,%3,%4};" :: "r"(a), "r"(r0), "r"(r1), "r"(r2), "r"(r3) : "memory");
}
__device__ __forceinline__ void stsm2(uint32_t a, uint32_t r0, uint32_t r1) {
    asm volatile("stmatrix.sync.aligned.m8n8.x2.shared.b16 [%0], {%1,%2};" :: "r"(a), "r"(r0), "r"(r1) : "memory");
}
__device__ __forceinline__ void stsm2t(uint32_t a, uint32_t r0, uint32_t r1) {
    asm volatile("stmatrix.sync.aligned.m8n8.x2.trans.shared.b16 [%0], {%1,%2};" :: "r"(a), "r"(r0), "r"(r1) : "memory");
}
__device__ __forceinline__ uint32_t movm(uint32_t a) {
    uint32_t d; asm volatile("movmatrix.sync.aligned.m8n8.trans.b16 %0, %1;" : "=r"(d) : "r"(a)); return d;
}
__device__ __forceinline__ void mma16(float* d, uint32_t a0, uint32_t a1, uint32_t a2, uint32_t a3, uint32_t b0, uint32_t b1) {
    asm volatile("mma.sync.aligned.m16n8k16.row.col.f32.bf16.bf16.f32 {%0,%1,%2,%3}, {%4,%5,%6,%7}, {%8,%9}, {%0,%1,%2,%3};"
                 : "+f"(d[0]), "+f"(d[1]), "+f"(d[2]), "+f"(d[3]) : "r"(a0), "r"(a1), "r"(a2), "r"(a3), "r"(b0), "r"(b1));
}
__device__ __forceinline__ void mma8(float* d, uint32_t a0, uint32_t a1, uint32_t b0) {
    asm volatile("mma.sync.aligned.m16n8k8.row.col.f32.bf16.bf16.f32 {%0,%1,%2,%3}, {%4,%5}, {%6}, {%0,%1,%2,%3};"
                 : "+f"(d[0]), "+f"(d[1]), "+f"(d[2]), "+f"(d[3]) : "r"(a0), "r"(a1), "r"(b0));
}
__device__ __forceinline__ uint32_t pack2(float lo, float hi) {
    uint32_t r; asm("cvt.rn.bf16x2.f32 %0, %1, %2;" : "=r"(r) : "f"(hi), "f"(lo)); return r;
}
__device__ __forceinline__ float bf_lo(uint32_t v) { return __uint_as_float(v << 16); }
__device__ __forceinline__ float bf_hi(uint32_t v) { return __uint_as_float(v & 0xFFFF0000u); }
__device__ __forceinline__ float ex2(float x) { float y; asm("ex2.approx.ftz.f32 %0, %1;" : "=f"(y) : "f"(x)); return y; }
__device__ __forceinline__ float rcp(float x) { float y; asm("rcp.approx.ftz.f32 %0, %1;" : "=f"(y) : "f"(x)); return y; }
__device__ __forceinline__ void sts4f(uint32_t a, float x, float y, float z, float w) {
    asm volatile("st.shared.v4.f32 [%0], {%1,%2,%3,%4};" :: "r"(a), "f"(x), "f"(y), "f"(z), "f"(w) : "memory");
}
__device__ __forceinline__ void sts1u(uint32_t a, uint32_t v) { asm volatile("st.shared.u32 [%0], %1;" :: "r"(a), "r"(v) : "memory"); }
__device__ __forceinline__ void sts4u(uint32_t a, uint4 v) {
    asm volatile("st.shared.v4.u32 [%0], {%1,%2,%3,%4};" :: "r"(a), "r"(v.x), "r"(v.y), "r"(v.z), "r"(v.w) : "memory");
}
__device__ __forceinline__ float4 lds4f(uint32_t a) {
    float4 v; asm volatile("ld.shared.v4.f32 {%0,%1,%2,%3}, [%4];" : "=f"(v.x), "=f"(v.y), "=f"(v.z), "=f"(v.w) : "r"(a) : "memory"); return v;
}
__device__ __forceinline__ float2 lds2f(uint32_t a) {
    float2 v; asm volatile("ld.shared.v2.f32 {%0,%1}, [%2];" : "=f"(v.x), "=f"(v.y) : "r"(a) : "memory"); return v;
}
__device__ __forceinline__ uint4 lds4u(uint32_t a) {
    uint4 v; asm volatile("ld.shared.v4.u32 {%0,%1,%2,%3}, [%4];" : "=r"(v.x), "=r"(v.y), "=r"(v.z), "=r"(v.w) : "r"(a) : "memory"); return v;
}
__device__ __forceinline__ uint32_t lds1u(uint32_t a) {
    uint32_t v; asm volatile("ld.shared.u32 %0, [%1];" : "=r"(v) : "r"(a) : "memory"); return v;
}
__device__ __forceinline__ uint2 lds2u(uint32_t a) {
    uint2 v; asm volatile("ld.shared.v2.u32 {%0,%1}, [%2];" : "=r"(v.x), "=r"(v.y) : "r"(a) : "memory"); return v;
}
__device__ __forceinline__ void st_async4(uint32_t a, uint32_t bar, float x, float y, float z, float w) {
    asm volatile("st.async.shared::cluster.mbarrier::complete_tx::bytes.v4.f32 [%0], {%1,%2,%3,%4}, [%5];"
                 :: "r"(a), "f"(x), "f"(y), "f"(z), "f"(w), "r"(bar) : "memory");
}
__device__ __forceinline__ void st_async2(uint32_t a, uint32_t bar, float x, float y) {
    asm volatile("st.async.shared::cluster.mbarrier::complete_tx::bytes.v2.f32 [%0], {%1,%2}, [%3];"
                 :: "r"(a), "f"(x), "f"(y), "r"(bar) : "memory");
}
__device__ __forceinline__ void st_async1f(uint32_t a, uint32_t bar, float x) {
    asm volatile("st.async.shared::cluster.mbarrier::complete_tx::bytes.f32 [%0], %1, [%2];" :: "r"(a), "f"(x), "r"(bar) : "memory");
}
__device__ __forceinline__ void st_async1(uint32_t a, uint32_t bar, uint32_t x) {
    asm volatile("st.async.shared::cluster.mbarrier::complete_tx::bytes.b32 [%0], %1, [%2];" :: "r"(a), "r"(x), "r"(bar) : "memory");
}
__device__ __forceinline__ uint4 ld_relaxed4(const uint4* p) {
    uint4 v;
    asm volatile("ld.relaxed.gpu.global.v4.u32 {%0,%1,%2,%3}, [%4];" : "=r"(v.x), "=r"(v.y), "=r"(v.z), "=r"(v.w) : "l"(p) : "memory");
    return v;
}
__device__ __forceinline__ void st_relaxed4(uint4* p, uint4 v) {
    asm volatile("st.relaxed.gpu.global.v4.u32 [%0], {%1,%2,%3,%4};" :: "l"(p), "r"(v.x), "r"(v.y), "r"(v.z), "r"(v.w) : "memory");
}
__device__ __forceinline__ void count_up(int idx) {
    asm volatile("red.release.gpu.global.add.u32 [%0], 1;" :: "l"(&g_cnt[idx * 8]) : "memory");
}
__device__ __forceinline__ void st_pred1(void* p, uint32_t v, bool on) {
    asm volatile("{\n.reg .pred p;\nsetp.ne.u32 p, %2, 0;\n@p st.relaxed.gpu.global.u32 [%0], %1;\n}" :: "l"(p), "r"(v), "r"((uint32_t)on) : "memory");
}
__device__ __forceinline__ void st_pred4(void* p, uint4 v, bool on) {
    asm volatile("{\n.reg .pred p;\nsetp.ne.u32 p, %5, 0;\n@p st.global.v4.u32 [%0], {%1,%2,%3,%4};\n}"
                 :: "l"(p), "r"(v.x), "r"(v.y), "r"(v.z), "r"(v.w), "r"((uint32_t)on) : "memory");
}
__device__ __forceinline__ void st_relaxed1(void* p, uint32_t v) {
    asm volatile("st.relaxed.gpu.global.u32 [%0], %1;" :: "l"(p), "r"(v) : "memory");
}
__device__ __forceinline__ uint32_t umax4(uint4 v) { return max(max(v.x, v.y), max(v.z, v.w)); }
__device__ __forceinline__ void wg_fence() { asm volatile("wgmma.fence.sync.aligned;" ::: "memory"); }
__device__ __forceinline__ void wg_commit() { asm volatile("wgmma.commit_group.sync.aligned;" ::: "memory"); }
template <int N> __device__ __forceinline__ void wg_wait() { asm volatile("wgmma.wait_group.sync.aligned %0;" :: "n"(N) : "memory"); }
template <int N> __device__ __forceinline__ void reg_fence(float* d) {
#pragma unroll
    for (int i = 0; i < N; i++) asm volatile("" : "+f"(d[i]) :: "memory");
}
#define ACC16(d) "+f"(d[0]), "+f"(d[1]), "+f"(d[2]), "+f"(d[3]), "+f"(d[4]), "+f"(d[5]), "+f"(d[6]), "+f"(d[7]), \
                 "+f"(d[8]), "+f"(d[9]), "+f"(d[10]), "+f"(d[11]), "+f"(d[12]), "+f"(d[13]), "+f"(d[14]), "+f"(d[15])
#define DESC_HI_SW128 "0x40000040"
#define OUT16(d) "=f"(d[0]), "=f"(d[1]), "=f"(d[2]), "=f"(d[3]), "=f"(d[4]), "=f"(d[5]), "=f"(d[6]), "=f"(d[7]), \
                 "=f"(d[8]), "=f"(d[9]), "=f"(d[10]), "=f"(d[11]), "=f"(d[12]), "=f"(d[13]), "=f"(d[14]), "=f"(d[15])
template <int ACCUM, int BOFF>
__device__ __forceinline__ void wg32_rs(float* d, const uint32_t* a, uint64_t dsw) {
    if (ACCUM)
        asm volatile("{\n.reg .b64 db;\nadd.s64 db, %20, %21;\n"
                     "wgmma.mma_async.sync.aligned.m64n32k16.f32.bf16.bf16 {%0,%1,%2,%3,%4,%5,%6,%7,%8,%9,%10,%11,%12,%13,%14,%15}, "
                     "{%16,%17,%18,%19}, db, 1, 1, 1, 0;\n}"
                     : ACC16(d) : "r"(a[0]), "r"(a[1]), "r"(a[2]), "r"(a[3]), "l"(dsw), "n"(BOFF));
    else
        asm volatile("{\n.reg .b64 db;\nadd.s64 db, %20, %21;\n"
                     "wgmma.mma_async.sync.aligned.m64n32k16.f32.bf16.bf16 {%0,%1,%2,%3,%4,%5,%6,%7,%8,%9,%10,%11,%12,%13,%14,%15}, "
                     "{%16,%17,%18,%19}, db, 0, 1, 1, 0;\n}"
                     : OUT16(d) : "r"(a[0]), "r"(a[1]), "r"(a[2]), "r"(a[3]), "l"(dsw), "n"(BOFF));
}
template <int ACCUM, int AOFF, int BOFF>
__device__ __forceinline__ void wg32_ss(float* d, uint64_t dsw) {
    if (ACCUM)
        asm volatile("{\n.reg .b64 da, db;\nadd.s64 da, %16, %17;\nadd.s64 db, %16, %18;\n"
                     "wgmma.mma_async.sync.aligned.m64n32k16.f32.bf16.bf16 {%0,%1,%2,%3,%4,%5,%6,%7,%8,%9,%10,%11,%12,%13,%14,%15}, "
                     "da, db, 1, 1, 1, 1, 0;\n}"
                     : ACC16(d) : "l"(dsw), "n"(AOFF), "n"(BOFF));
    else
        asm volatile("{\n.reg .b64 da, db;\nadd.s64 da, %16, %17;\nadd.s64 db, %16, %18;\n"
                     "wgmma.mma_async.sync.aligned.m64n32k16.f32.bf16.bf16 {%0,%1,%2,%3,%4,%5,%6,%7,%8,%9,%10,%11,%12,%13,%14,%15}, "
                     "da, db, 0, 1, 1, 1, 0;\n}"
                     : OUT16(d) : "l"(dsw), "n"(AOFF), "n"(BOFF));
}
template <int ACCUM, int AOFF, int BOFF>
__device__ __forceinline__ void wg8_ss(float* d, uint64_t dsw, uint64_t dns) {
    if (!ACCUM)
        asm volatile("{\n.reg .b64 da, db;\nadd.s64 da, %4, %6;\nadd.s64 db, %5, %7;\n"
                     "wgmma.mma_async.sync.aligned.m64n8k16.f32.bf16.bf16 {%0,%1,%2,%3}, da, db, 0, 1, 1, 1, 0;\n}"
                     : "=f"(d[0]), "=f"(d[1]), "=f"(d[2]), "=f"(d[3]) : "l"(dsw), "l"(dns), "n"(AOFF), "n"(BOFF));
    else
        asm volatile("{\n.reg .b64 da, db;\nadd.s64 da, %4, %6;\nadd.s64 db, %5, %7;\n"
                     "wgmma.mma_async.sync.aligned.m64n8k16.f32.bf16.bf16 {%0,%1,%2,%3}, da, db, 1, 1, 1, 1, 0;\n}"
                     : "+f"(d[0]), "+f"(d[1]), "+f"(d[2]), "+f"(d[3]) : "l"(dsw), "l"(dns), "n"(AOFF), "n"(BOFF));
}
template <int I0, int I1, class F>
__device__ __forceinline__ void static_for(F&& f) {
    if constexpr (I0 < I1) { f(std::integral_constant<int, I0>{}); static_for<I0 + 1, I1>(f); }
}
template <int I0, int I1, int AOFF, int BOFF>
__device__ __forceinline__ void wg8_chain(float* d, uint64_t dsw, uint64_t dns) {
    wg_fence();
    static_for<I0, I1>([&](auto i) { wg8_ss<i.value != 0, AOFF + i.value * 128, BOFF + i.value * 16>(d, dsw, dns); });
    wg_commit();
}

__device__ __forceinline__ void ln_row(const uint4* v, int row, int lane) {
    float f[32];
#pragma unroll
    for (int j = 0; j < 4; j++) {
        f[j * 8 + 0] = bf_lo(v[j].x); f[j * 8 + 1] = bf_hi(v[j].x); f[j * 8 + 2] = bf_lo(v[j].y); f[j * 8 + 3] = bf_hi(v[j].y);
        f[j * 8 + 4] = bf_lo(v[j].z); f[j * 8 + 5] = bf_hi(v[j].z); f[j * 8 + 6] = bf_lo(v[j].w); f[j * 8 + 7] = bf_hi(v[j].w);
    }
    float s = 0.f;
#pragma unroll
    for (int i = 0; i < 32; i++) s += f[i];
#pragma unroll
    for (int o = 16; o; o >>= 1) s += __shfl_xor_sync(~0u, s, o);
    const float mean = s * (1.f / DM);
    float q = 0.f;
#pragma unroll
    for (int i = 0; i < 32; i++) { f[i] -= mean; q += f[i] * f[i]; }
#pragma unroll
    for (int o = 16; o; o >>= 1) q += __shfl_xor_sync(~0u, q, o);
    const float r = 1.f / sqrtf(q * (1.f / DM) + 1e-5f);
    uint4* dst = reinterpret_cast<uint4*>(g_xn + (size_t)row * DM);
    uint4* dst2 = g_xc + (row >> 5) * 4096 + (lane >> 3) * 256 + (row & 31) * 8 + ((lane & 7) ^ (row & 7));
#pragma unroll
    for (int j = 0; j < 4; j++) {
        const uint4 o = make_uint4(pack2(f[j * 8] * r, f[j * 8 + 1] * r), pack2(f[j * 8 + 2] * r, f[j * 8 + 3] * r),
                                   pack2(f[j * 8 + 4] * r, f[j * 8 + 5] * r), pack2(f[j * 8 + 6] * r, f[j * 8 + 7] * r));
        dst[j * 32 + lane] = o;
        dst2[(j & 1) * 2048 + (j >> 1) * 1024] = o;
    }
}
__device__ __forceinline__ void reset_exchange(const __nv_bfloat16* __restrict__ mem0) {
    const int gi = blockIdx.x * 256 + threadIdx.x;
    const uint4 poison = make_uint4(~0u, ~0u, ~0u, ~0u);
    if (gi < 1024) {
        uint4 m = reinterpret_cast<const uint4*>(mem0)[(gi & 7) * 128 + (gi >> 3)];
        if (m.x == ~0u) m.x = 0x7FFF7FFFu;
        if (m.y == ~0u) m.y = 0x7FFF7FFFu;
        if (m.z == ~0u) m.z = 0x7FFF7FFFu;
        if (m.w == ~0u) m.w = 0x7FFF7FFFu;
        g_xmem[0][gi] = m;
    } else if (gi < 4096) {
        (&g_xmem[0][0])[gi] = poison;
    } else if (gi < 4096 + 16384) {
        (&g_xo[0][0])[gi - 4096] = poison;
    } else if (gi < 4096 + 16384 + 24 * FSTR) {
        reinterpret_cast<uint4*>(&g_flag[0][0])[gi - 4096 - 16384] = poison;
    } else if (gi >= 24576 - CNT_NUM) {
        g_cnt[(24575 - gi) * 8] = 0;
    }
}

#define ONKQ 45
constexpr int ONKV = 128 - 2 * ONKQ;
constexpr uint32_t SB0 = 1024;
constexpr uint32_t C_WS = 0, C_XN = 65536, C_MB = 98304, C_WO = 114688, C_SMEM = 232448;
constexpr uint32_t C_BAR = C_SMEM - 384, C_CAL = C_BAR + 192;
constexpr uint32_t C_SLOTQ = C_WO + ONKQ * 2048, C_QX = C_SLOTQ + 8192, C_KX = C_QX + 4096,
                   C_XSL = C_KX + 4096, C_OL = C_SLOTQ + 4096;
constexpr uint32_t C_SLOTV = C_WO + ONKV * 2048, C_V = C_SLOTV + 8192, C_PL = C_V + 20480, C_SL = C_PL + 4096;
constexpr uint32_t C_DUMP = C_BAR - 512;
static_assert(C_XSL + 5120 <= C_DUMP && C_SL + 2560 <= C_DUMP, "smem overflow");
enum { B_W0 = 0, B_W1, B_W2, B_WS, B_XF0, B_XF1, B_SC, B_P0, B_P1, B_XS, B_OL, B_MF0, B_MF1, B_OF, B_RT0, B_RT1, B_VF, B_MBF, B_GO, B_DUMP, B_NUM };
struct Descs { uint64_t sw[4], ns; };
constexpr uint64_t DSW = 0x4000004000010000ull, DNS = 0x0000001000080000ull;
template <int V> using ic = std::integral_constant<int, V>;
constexpr float SM_SCALE = 0.08838834764831845f * 1.4426950408889634f;

#define TSD(i) do {} while (0)
#define TS_FLUSH(w)
#define TSX(i, c)
#define TS(i)
#define NOFILL 0
#define DLY1 2250
#define DLY2 2530
#define SWAP16 0
#define SSFIRST 1
#define EARLYB 0
#define CANARY ~0u
#define L2POS 10
#define QK1 10
#define RFPOS 6
#define STPOS 12
#define OTAIL 3
#define DLYS 450
#define DLYB 1
#define VLEAD 4

#define VEARLY 8
#define QSPLIT 20
__device__ __forceinline__ bool elect() {
    uint32_t r;
    asm volatile("{\n.reg .pred p;\nelect.sync _|p, 0xffffffff;\nselp.u32 %0, 1, 0, p;\n}" : "=r"(r));
    return r;
}
__device__ __forceinline__ int uni(int v) { return __shfl_sync(~0u, v, 0); }
__device__ __forceinline__ void calibrate(uint32_t cal, float keep) {
    const uint32_t t0 = gtick();
    uint32_t t, it = 0;
    do { t = gtick(); spin_guard(it); } while (__any_sync(~0u, t == t0));
    const uint32_t c = clk();
    const uint4 p = lds4u(cal);
    const float cpt = 256.f * fminf(fmaxf(__fdividef((float)(c - p.y), (float)((t - p.x) & 0x7FFFFFF)), 16.f), 128.f);
    __syncwarp();
    sts4u(cal, make_uint4(t, c, (uint32_t)(keep > 0.f ? fmaf(keep, (float)p.z - cpt, cpt) : cpt), 0));
}
struct Stamps { uint32_t v[6]; };
__device__ __forceinline__ void load_stamps2(Stamps& t, const uint32_t* f, uint32_t l16, bool on = true) {
    const char* p = reinterpret_cast<const char*>(f) + (l16 >> 2) * FSTR;
    asm volatile("{\n.reg .pred p;\nsetp.ne.u32 p, %7, 0;\nmov.u32 %0, 63;\nmov.u32 %1, 63;\nmov.u32 %2, 63;\nmov.u32 %3, 63;\nmov.u32 %4, 63;\nmov.u32 %5, 63;\n"
                 "@p ld.relaxed.gpu.global.v2.u32 {%0, %1}, [%6];\n@p ld.relaxed.gpu.global.v2.u32 {%2, %3}, [%6 + %8];\n"
                 "@p ld.relaxed.gpu.global.v2.u32 {%4, %5}, [%6 + %9];\n}"
                 : "=&r"(t.v[0]), "=&r"(t.v[1]), "=&r"(t.v[2]), "=&r"(t.v[3]), "=&r"(t.v[4]), "=&r"(t.v[5])
                 : "l"(p), "r"((uint32_t)on), "n"(128 * FSTR), "n"(256 * FSTR) : "memory");
}
template <int N>
__device__ __forceinline__ uint32_t stamps_missing(const uint32_t* v, int s) {
    uint32_t x = 0;
#pragma unroll
    for (int i = 0; i < N; i++) x |= v[i] ^ s;
    return x & 63;
}
template <int N>
__device__ __forceinline__ uint32_t latest_stamp(const uint32_t* v, const uint4 cal) {
    int late = (int)(v[0] - (cal.x << 6));
#pragma unroll
    for (int i = 1; i < N; i++) late = max(late, (int)(v[i] - (cal.x << 6)));
    return cal.y + (((late >> 6) * (int)cal.z) >> 8);
}
__device__ __forceinline__ void wait_clock(uint32_t target, uint32_t range = 65536) {
    while (__any_sync(~0u, target - clk() < range)) {}
}

template <int BYTES>
__device__ __forceinline__ bool incomplete(uint32_t buf, uint32_t l16) {
    uint32_t m = 0;
#pragma unroll 1
    for (int o = 0; o < BYTES; o += 256) m = max(m, umax4(lds4u(buf + o + (l16 & 255))));
    return __any_sync(~0u, m == ~0u);
}
__device__ __forceinline__ void refetch(uint32_t buf, const uint4* src, uint32_t bytes, uint32_t b, int w4, int barid, uint32_t& tries) {
    spin_guard(tries);
    bar_sync(barid, 128);
    if (w4 == 0 && elect()) { mbar_expect(b, bytes); bulk_ld(buf, src, bytes, b); }
    __syncwarp();
    mbar_wait(b, 0);
    bar_sync(barid, 128);
    if (w4 == 0 && elect()) mbar_arrive(b);
    __syncwarp();
}

__device__ __forceinline__ void load_box(const CUtensorMap* tA, const CUtensorMap* tB, int cl, int rank, uint32_t dst, int j, int q, uint32_t b) {
    const bool isb = (q ^ (q >> 1)) & 1;
    tma2d(dst + q * 16384, isb ? tB : tA, cl * 256 + (rank >= 4 ? (rank - 4) * 128 + isb * 64 : rank * 64), (q >> 1) * 512 + j * 128, b);
}

template <bool ISV, int WG>
__device__ __forceinline__ void chain_main(const CUtensorMap* tA, const CUtensorMap* tB, const CUtensorMap* tWo,
                                           const uint32_t sb, const int cl, const int rank, const Descs& D, const uint32_t goal) {
    const int tid = threadIdx.x;
    uint32_t l16 = __shfl_sync(~0u, (tid & 31) * 16, tid & 31);
    int w4 = uni((tid >> 5) & 3);
    const int role = ISV ? 2 : (rank & 1), hh = ISV ? rank - 4 : rank >> 1, head = 2 * cl + hh;
    const uint32_t bar = sb + C_BAR;
    constexpr int ONK = ISV ? ONKV : ONKQ;
    const int ostart = (hh * 128 + role * ONKQ);

    uint32_t wk[24][4], wv[24][4];
    uint32_t a_adr;
    {
        if (WG == 1 && w4 == 0) calibrate(sb + C_CAL, 0.f);
        const int lane = tid & 31, kr = (lane & 7) + ((lane >> 4) << 3);
        a_adr = __shfl_sync(~0u, sb + WG * 32768 + kr * 128 + (((w4 * 2 + ((lane >> 3) & 1)) ^ (kr & 7)) << 4), lane);
#pragma unroll
        for (int j = 0; j < 3; j++) {
            mbar_wait(bar + (B_W0 + j) * 8, 0);
#pragma unroll
            for (int i = 0; i < 8; i++) {
                ldsm4t(wk[j * 8 + i], a_adr + j * 65536 + i * 2048);
                ldsm4t(wv[j * 8 + i], a_adr + j * 65536 + 16384 + i * 2048);
            }
            if (j != 1) {
                bar_sync(6, 256);
                if (j == 0 && tid == 0) TL(1, 6);
                if (WG == 0 && j == 0 && elect()) load_box(tA, tB, cl, rank, sb + C_WS, 3, w4, bar + B_WS * 8);
                if (WG == 0 && j == 2) {
                    if (elect())
                        for (int i = w4; i < ONK; i += 4) tma2d(sb + C_WO + i * 2048, tWo, cl * 64, (ostart + i) * 16, bar + B_OF * 8);
                }
                __syncwarp();
            }
        }
        if (NOFILL) { for (uint32_t o = C_WO + ONK * 2048 + tid * 16; o < C_BAR; o += 4096) sts4u(sb + o, make_uint4(0, 0, 0, 0)); bar_sync(6, 256); }
        if (WG == 1 && w4 == 1) {
            uint32_t v, it = 0;
            do {
                asm volatile("ld.acquire.gpu.global.u32 %0, [%1];" : "=r"(v) : "l"(&g_epoch) : "memory");
                spin_guard(it);
            } while (__any_sync(~0u, (int)(v - goal) < 0));
        }
        if (WG == 1 && w4 == 0) calibrate(sb + C_CAL, 0.f);
        __syncwarp();
        bar_sync(6, 256);
        asm volatile("fence.proxy.async.global;" ::: "memory");
    }

    constexpr uint32_t SLOT = ISV ? C_SLOTV : C_SLOTQ;
    constexpr int WS_A = (SB0 + C_WS + WG * 32768) >> 4, WO_A = (SB0 + C_WO) >> 4, MB_A = (SB0 + C_MB) >> 4;
#define XN_A(ks) (int)(((SB0 + C_XN + WG * 16384) >> 4) + ((ks) >> 2) * 256 + ((ks) & 3) * 2)
    const uint32_t slot = (sb + SLOT + w4 * 512), mbw = sb + C_MB + WG * 8192;
    const uint32_t sb_v = (mapa(sb, 4 + hh));
    const uint32_t sb_x = uni(mapa(sb, 2 * hh + (WG ? 1 : (~w4 & 1))));
    const uint32_t sb_o = (mapa(sb, w4));
    const uint32_t u_off = (ISV ? (head * 128 + w4 * 32) * 16 : (cl * 4 + rank) * 256 + (w4 & 1) * 128);
    const uint32_t v_row = (sb + C_V + (2 * WG + (w4 >> 1)) * 512), v_b = ((w4 & 1) * 64);
    const uint32_t u_flag = (blockIdx.x * FSTR);
    const uint32_t f_half = (w4 & 1) * role * (ONKV * 128), f_sb = uni(mapa(sb, rank + (w4 & 1) * (4 + hh - rank)));
    const uint32_t f_src = uni((ostart + (w4 & 1) * (2 - role) * ONKQ) * 256 + f_half), f_dst = uni(f_sb + C_MB + f_half);
    const uint32_t m_dst = (sb + C_MB + role * 8192), m_bar = (bar + (B_MF0 + role) * 8);
    uint32_t target, missing;
    int s = -1;
    uint32_t pf[4][4];
    float xk[16], xv[16];
    uint4 oxp[4];

    auto send_planes = [&](auto n, uint32_t a, int b, const float* v, bool hold) {
        const uint32_t dump = sb + C_DUMP + (l16 >> 2), to = a + (l16 >> 2), ad = hold ? dump : to;
        const uint32_t mb = hold ? (dump & 0xFF000000u) | (SB0 + C_BAR + B_DUMP * 8) : (to & 0xFF000000u) | (SB0 + C_BAR + b * 8);
#pragma unroll
        for (int i = 0; i < n.value; i++) st_async1f(ad + i * 128, mb, v[i]);
    };
    auto store_ox = [&](int ss) {
        char* orow = reinterpret_cast<char*>(g_ox) + (ss * (32 * HD * 2) + (u_off >> 3) + (l16 >> 6) * (HD * 2) + (l16 & 48));
#pragma unroll
        for (int i = 0; i < 4; i++) st_pred4(orow + i * (8 * HD * 2), oxp[i], ss >= 0);
    };
    auto load_tokens = [&](int seg, int wina, int g) {
        const int khalf = ISV ? 1 - wina : wina;
        if (!NOFILL && elect()) {
            mbar_expect(bar + (B_XF0 + g) * 8, 16384);
            bulk_ld(sb + C_XN + g * 16384, g_xc + (seg * 4 + khalf * 2 + g) * 1024, 16384, bar + (B_XF0 + g) * 8);
        }
        __syncwarp();
    };
    auto prefetch = [&]() {
#pragma unroll
        for (int i = 0; i < 4; i++) ldsm4t(pf[i], a_adr + C_WS + (i & 1) * 16384 + (i >> 1) * 2048);
    };
    constexpr int HA = ISV ? 0 : 1, NK1 = ISV ? 0 : QK1;
    auto products = [&](auto give, auto half, auto init, auto i0, auto i1, const uint64_t d) {
        static_for<i0.value, i1.value>([&](auto i) {
            constexpr int ks = half.value * 16 + i.value, acc = !(init.value && i.value == i0.value);
            if constexpr (ks >= 24) wg32_ss<acc, WS_A + give.value * 1024 + (ks - 24) * 128, XN_A(i.value)>(give.value ? xv : xk, d);
            else if constexpr (give.value) wg32_rs<acc, XN_A(i.value)>(xv, wv[ks], d);
            else wg32_rs<acc, XN_A(i.value)>(xk, wk[ks], d);
        });
    };
    auto stream_a = [&](const uint64_t dk, const uint64_t dv) {
        if (NOFILL) return;
        constexpr int F = (WG == 0 && SSFIRST) ? 8 : 0;
        wg_fence();
        products(ic<0>{}, ic<HA>{}, ic<1>{}, ic<F>{}, ic<F + 8>{}, dk);
        products(ic<1>{}, ic<HA>{}, ic<1>{}, ic<F>{}, ic<F + 8>{}, dv);
        products(ic<1>{}, ic<HA>{}, ic<0>{}, ic<8 - F>{}, ic<16 - F>{}, dv);
        products(ic<0>{}, ic<HA>{}, ic<0>{}, ic<8 - F>{}, ic<16 - F>{}, dk);
        wg_commit();
    };
    auto token_softmax = [&]() {
        const int hi = w4 - 2, lane = l16 >> 4;
        const uint32_t src = sb + C_XSL + hi * 256 + (l16 & 255) + (l16 >> 8) * 2560;
        const int d0 = 16 * role + 8 * hi + (lane >> 2) - 2 * (lane & 3);
        mbar_wait(bar + B_XS * 8, s & 1);
        float e[10];
        float m = -INFINITY;
#pragma unroll
        for (int i = 0; i < 5; i++) {
            __syncwarp();
            float a[4];
            ldsm4f(a, src + i * 512);
            e[2 * i] = (i == 0 || d0 >= 8 * (i - 1)) ? a[0] + a[2] : -INFINITY;
            e[2 * i + 1] = (i == 0 || d0 > 8 * (i - 1)) ? a[1] + a[3] : -INFINITY;
            m = fmaxf(m, fmaxf(e[2 * i], e[2 * i + 1]));
        }
        m = fmaxf(m, __shfl_xor_sync(~0u, m, 1));
        m = fmaxf(m, __shfl_xor_sync(~0u, m, 2));
        m *= -SM_SCALE;
        float l = 0.f;
#pragma unroll
        for (int i = 0; i < 10; i++) { e[i] = ex2(fmaf(e[i], SM_SCALE, m)); l += e[i]; }
        l += __shfl_xor_sync(~0u, l, 1);
        l += __shfl_xor_sync(~0u, l, 2);
        l = rcp(l);
        const uint32_t pd = sb_v + C_PL + (s & 1) * 2048 + role * 768 + hi * 128 + (l16 >> 2), pb = sb_v + C_BAR + (B_P0 + (s & 1)) * 8;
        st_async1(pd, pb, pack2(e[0] * l, e[1] * l));
        st_async1(pd + 256, pb, pack2(e[2] * l, e[3] * l));
        st_async1(pd + 512, pb, pack2(e[4] * l, e[5] * l));
        if (role) {
            st_async1(pd + 768, pb, pack2(e[6] * l, e[7] * l));
            st_async1(pd + 1024, pb, pack2(e[8] * l, e[9] * l));
        }
        if (hi == 0 && l16 == 0) mbar_expect(bar + B_XS * 8, 3072 + role * 2048);
        __syncwarp();
    };

    auto windows = [&]() {
        asm volatile("" : "+r"(l16), "+r"(w4));
        const uint64_t* const dd = D.sw;
        TS(5);
        if constexpr (WG == 1) {
            TS(6);
            if (ISV) bar_sync(3, 256);
            Stamps st2;
            if (!ISV) load_stamps2(st2, g_flag[0], l16, __any_sync(~0u, missing) && w4 < 2);
            stream_a(dd[0], dd[1]);
            if (!NOFILL) bar_arrive(7, 256);
            if (ISV) {
                if (!NOFILL) store_ox(s - 1);
                st_relaxed4(reinterpret_cast<uint4*>(reinterpret_cast<char*>(&g_xo[(s + 2) & 3][0]) + (u_off + l16)), make_uint4(~0u, ~0u, ~0u, ~0u));
            }
            auto fetch_o = [&]() {
            if (!ISV && w4 < 2 && s >= 0) {
                const char* src = reinterpret_cast<const char*>(&g_xo[s & 3][0]) + f_src;
                if (__builtin_expect(__any_sync(~0u, missing), 0)) {
                    uint32_t it = 0;
                    while (__any_sync(~0u, stamps_missing<6>(st2.v, s))) { load_stamps2(st2, g_flag[0], l16); spin_guard(it); }
                    target = latest_stamp<6>(st2.v, lds4u(sb + C_CAL)) + DLY1;
                }
                mbar_wait(bar + B_VF * 8, s & 1);
                TS(10);
                wait_clock(target);
                if (elect()) bulk_ld(f_dst, src, ONKQ * 256 - w4 * (ONKQ * 256 - ONKV * 128), f_sb + C_BAR + B_OF * 8);
                __syncwarp();
                TS(8);
            }
            };
            if (!EARLYB) fetch_o();
            if (!NOFILL) {
                wg_wait<0>();
                reg_fence<16>(xk); reg_fence<16>(xv);
                if (w4 == 3) { bar_sync(2, 128); load_tokens(s + 1, 0, 1); }
                else bar_arrive(2, 128);
            }
            if (EARLYB) fetch_o();
            TS(7);
        } else {
            if (!NOFILL) {
                mbar_wait(bar + B_XF0 * 8, 0);
                bar_sync(7, 256);
            }
            TS(6);
            stream_a(dd[0], dd[1]);
        }
        if constexpr (WG == 0) {
            if (s >= 0) {
                const uint32_t dst = sb_o + C_OL + rank * 512;
                const uint32_t can = sb + C_MB + l16 * 8 + (l16 >> 2), can2 = can + (l16 < (ONK * 2 - 64) * 16 ? 8192 : 0);
                float co[4];
                TS(7);
                uint32_t tries = 0;
                for (;; tries |= 1) {
                    asm volatile("" : "+r"(tries));
                    if (__builtin_expect(tries, 0)) {
                        wg_wait<0>();
                        refetch(sb + C_MB, &g_xo[s & 3][ostart * 16], ONK * 256, bar + B_RT0 * 8, w4, 1, tries);
                    }
                    mbar_wait(bar + B_OF * 8, s & 1);
                    TS(8);
                    wg8_chain<0, 8, WO_A, MB_A>(co, D.sw[0], D.ns);
                    if (__builtin_expect(!__any_sync(~0u, max(max(lds1u(can), lds1u(can + 4096)), lds1u(can2)) == CANARY), 1)) break;
                }
                wg_wait<1>();
                if (l16 == 0) mbar_arrive(bar + B_GO * 8);
                wg8_chain<8, ONK - OTAIL, WO_A, MB_A>(co, D.sw[0], D.ns);
                static_for<ONK - OTAIL, ONK>([&](auto i) { wg8_ss<1, WO_A + i.value * 128, MB_A + i.value * 16>(co, D.sw[0], D.ns); });
                wg_commit();
                wg_wait<1>();
                bar_arrive(5, 256);
                wg_wait<0>();
                reg_fence<4>(co);
                const bool nan = any_nan(co[0], co[1]);
                send_planes(ic<4>{}, dst, B_OL, co, nan);
                if (__builtin_expect(nan, 0)) {
                    while (incomplete<ONK * 256>(sb + C_MB, l16)) {
                        refetch(sb + C_MB, &g_xo[s & 3][ostart * 16], ONK * 256, bar + B_RT0 * 8, w4, 1, tries);
                        co[0] = co[1] = co[2] = co[3] = 0.f;
#pragma unroll 1
                        for (int i = 0; i < ONK; i++) {
                            wg_fence();
                            wg8_ss<1, WO_A, MB_A>(co, DSW + i * 128, DNS + i * 16);
                            wg_commit();
                            wg_wait<0>();
                        }
                        reg_fence<4>(co);
                    }
                    send_planes(ic<4>{}, dst, B_OL, co, false);
                }
                TS(9);
                if (l16 < 48 && w4 == 3) mbar_expect(bar + B_MF0 * 8 + (l16 >> 1), l16 == 32 ? ONK * 256 : 8192);
            } else {
                wg_wait<0>();
                if (l16 == 0) mbar_arrive(bar + B_GO * 8);
                bar_arrive(5, 256);
            }
            if (l16 < 32) mbar_arrive_cluster(mapa(bar + B_MBF * 8, 2 * hh + (l16 >> 4)));
            __syncwarp();
            if (!NOFILL) { reg_fence<16>(xk); reg_fence<16>(xv); }
        } else {
            if (w4 < 2) {
                if (w4 == 1) {
                    mbar_wait(bar + B_GO * 8, (s + 1) & 1);
                    load_tokens(s + 1, 0, 0);
                } else if (!ISV) {
                    calibrate(sb + C_CAL, 0.75f);
                }
                if (!ISV) st_relaxed1(reinterpret_cast<char*>(&g_xmem[(s + 3) & 3][0]) + (u_off + (l16 >> 2)), ~0u);
            } else if (!NOFILL && s >= 0) {
                if (ISV && w4 == 2 && (s & 3) == 1 && s > 1 && l16 == 0) count_up(CNT_OX + (s >> 2) - 1);
                __syncwarp();
                if (!ISV) token_softmax();
                TSX(9, w4 == 2);
            }
            if (!NOFILL) mbar_wait(bar + B_XF1 * 8, 1);
            bar_sync(5, 256);
        }
        asm volatile("" : "+r"(l16), "+r"(w4));
        TSX(11, w4 == 0 && (WG || ISV));
        constexpr int NR = SWAP16 ? 2 : 4;
        constexpr uint32_t OUT = SWAP16 ? WG * 4096 : 0, IN = SWAP16 ? (WG ^ 1) * 4096 : 0;
        auto give = [&]() {
#pragma unroll
            for (int j = 0; j < NR; j++) {
                if (SWAP16) stsm4(slot + OUT + l16 + j * 2048, pack2(xv[8 * j], xv[8 * j + 1]), pack2(xv[8 * j + 2], xv[8 * j + 3]),
                                  pack2(xv[8 * j + 4], xv[8 * j + 5]), pack2(xv[8 * j + 6], xv[8 * j + 7]));
                else stsm4f(slot + l16 + j * 2048, xv + 4 * j);
            }
        };
        auto take = [&](uint32_t (*r)[4]) {
#pragma unroll
            for (int j = 0; j < NR; j++) ldsm4(r[j], slot + IN + l16 + j * 2048);
        };
        auto store_tokens = [&](const uint32_t (*r)[4]) {
            uint32_t lo[4], hi[4];
#pragma unroll
            for (int j = 0; j < 4; j++) {
                if (SWAP16) {
                    const uint32_t a = r[j >> 1][(j & 1) * 2], b = r[j >> 1][(j & 1) * 2 + 1];
                    lo[j] = pack2(xk[4 * j] + bf_lo(a), xk[4 * j + 1] + bf_hi(a));
                    hi[j] = pack2(xk[4 * j + 2] + bf_lo(b), xk[4 * j + 3] + bf_hi(b));
                } else {
                    lo[j] = pack2(xk[4 * j] + __uint_as_float(r[j % NR][0]), xk[4 * j + 1] + __uint_as_float(r[j % NR][1]));
                    hi[j] = pack2(xk[4 * j + 2] + __uint_as_float(r[j % NR][2]), xk[4 * j + 3] + __uint_as_float(r[j % NR][3]));
                }
            }
            if (!ISV) {
                const uint32_t d = sb + C_QX + WG * 4096 + w4 * 1024 + l16;
                stsm4t(d, lo[0], lo[1], lo[2], lo[3]);
                stsm4t(d + 512, hi[0], hi[1], hi[2], hi[3]);
            } else {
                const uint32_t d = v_row + ((s + 1) & 1) * 10240 + ((l16 & 384) << 4) + ((l16 & 96) << 2) + ((l16 & 112) ^ v_b);
                stsm4(d, lo[0], lo[1], lo[2], lo[3]);
                stsm4(d ^ 32, hi[0], hi[1], hi[2], hi[3]);
            }
        };
        if constexpr (WG == 1) {
            if (!NOFILL) {
                wg_fence();
                products(ic<1>{}, ic<1 - HA>{}, ic<0>{}, ic<0>{}, ic<16>{}, dd[3]);
                products(ic<0>{}, ic<1 - HA>{}, ic<0>{}, ic<0>{}, ic<NK1>{}, dd[2]);
                wg_commit();
                if (ISV) {
                    bar_arrive(7, 256);
                } else {
                    mbar_wait(bar + B_MBF * 8, (s + 1) & 1);
                    bar_sync(7, 256);
                }
                wg_wait<0>();
                reg_fence<16>(xv); reg_fence<16>(xk);
                give();
                bar_arrive(8, 256);
            }
            TS(12);
            if (!ISV && w4 == 0) {
                const uint4* src = &g_xmem[(s + 1) & 3][role * 512];
                if (NOFILL) mbar_wait(bar + B_MBF * 8, (s + 1) & 1);
                TS(3);
                wait_clock(target + DLY2, s >= 0 ? 65536 : 0);
                if (hh) { if (elect()) bulk_mc(m_dst, src, 8192, m_bar, 0x2C); }
                else if (elect()) bulk_mc(m_dst, src, 8192, m_bar, 0x13);
                __syncwarp();
                TS(4);
            }
            prefetch();
            if (!NOFILL) {
                bar_sync(9, 256);
                uint32_t r[NR][4];
                take(r);
                bar_sync(14, 256);
                wg_fence();
                products(ic<0>{}, ic<1 - HA>{}, ic<0>{}, ic<NK1>{}, ic<16>{}, dd[2]);
                wg_commit();
                wg_wait<0>();
                reg_fence<16>(xk);
                TS(13);
                store_tokens(r);
                bar_arrive(10, 256);
                if (w4 != 3) bar_arrive(13, 128);
            }
        } else {
            uint32_t r[NR][4];
            if (!NOFILL) mbar_wait(bar + B_XF0 * 8, 1);
            if (!ISV && w4 < 2 && s >= 0) {
                char* gd = reinterpret_cast<char*>(&g_xmem[(s + 1) & 3][0]) + (u_off + (l16 >> 2));
                const uint32_t src = sb + C_OL + w4 * 256 + l16 + (l16 & 256);
                mbar_wait(bar + B_OL * 8, s & 1);
                TSD(3);
                float a[3][4];
#pragma unroll
                for (int i = 0; i < 3; i++) ldsm4f(a[i], src + i * 1024);
                st_relaxed1(gd, movm(pack2((a[0][0] + a[0][2]) + (a[1][0] + a[1][2]) + (a[2][0] + a[2][2]),
                                           (a[0][1] + a[0][3]) + (a[1][1] + a[1][3]) + (a[2][1] + a[2][3]))));
                TS(11);
                if (w4 == 0 && l16 == 0) mbar_expect(bar + B_OL * 8, 3072);
                __syncwarp();
            }
            if (!NOFILL) {
                bar_sync(7, 256);
                TS(12);
                wg_fence();
                products(ic<1>{}, ic<1 - HA>{}, ic<0>{}, ic<0>{}, ic<16>{}, dd[3]);
                wg_commit();
                products(ic<0>{}, ic<1 - HA>{}, ic<0>{}, ic<0>{}, ic<6>{}, dd[2]);
                wg_commit();
                bar_sync(8, 256);
                take(r);
                wg_wait<1>();
                reg_fence<16>(xv);
                give();
                bar_arrive(9, 256);
                products(ic<0>{}, ic<1 - HA>{}, ic<0>{}, ic<6>{}, ic<16>{}, dd[2]);
                wg_commit();
                bar_arrive(14, 256);
                wg_wait<0>();
                reg_fence<16>(xk);
            }
            TS(13);
            if (!NOFILL) store_tokens(r);
            prefetch();
        }
    };

    if (tid == 0) TL(1, 2);
    if (w4 == 0) load_tokens(0, 1, WG);
    mbar_wait(bar + B_WS * 8, 0);
    if (WG == 1 && !NOFILL) mbar_wait(bar + B_XF1 * 8, 0);
    if (ISV && WG == 0) bar_arrive(3, 256);
    target = missing = 0;
    oxp[0] = oxp[1] = oxp[2] = oxp[3] = make_uint4(0, 0, 0, 0);

#pragma unroll 1
    while (true) {
        windows();
        s++;

        asm volatile("" : "+r"(l16), "+r"(a_adr), "+r"(w4));
        TS_FLUSH(WG);
        TS(0);
        float ck[4], cv[4], dk[4], dv[4];
        uint32_t b[3][4], tries = 0;
        Stamps st1;
        const uint32_t kl = sb + C_KX + ((l16 & 384) << 2) + (l16 & 112);
        auto load_b = [&](auto kp) { ldsm4(b[kp.value % 3], mbw + l16 + ((kp.value & 3) ? (kp.value >> 2) * 3 + (kp.value & 3) - 1 : 12 + (kp.value >> 2)) * 512); };
        auto kpair = [&](auto kp_) {
            constexpr int kp = kp_.value, grp = kp >> 2, ph = kp & 3;
            if constexpr (kp > 0 && kp < 14) load_b(ic<kp + 2>{});
            const uint32_t* bb = b[kp % 3];
            if constexpr (ph != 0) {
                constexpr int q = (grp * 3 + ph - 1) * 2;
                static_for<(ph == 1 ? 0 : ph), ph + 1>([&](auto i) {
                    if constexpr (grp < 3) ldsm4t(pf[i.value], a_adr + C_WS + (i.value & 1) * 16384 + (grp * 2 + 2 + (i.value >> 1)) * 2048);
                });
                __syncwarp();
                mma16(cv, wv[q][0], wv[q][1], wv[q][2], wv[q][3], bb[0], bb[1]);
                mma16(ck, wk[q][0], wk[q][1], wk[q][2], wk[q][3], bb[0], bb[1]);
                mma16(dv, wv[q + 1][0], wv[q + 1][1], wv[q + 1][2], wv[q + 1][3], bb[2], bb[3]);
                mma16(dk, wk[q + 1][0], wk[q + 1][1], wk[q + 1][2], wk[q + 1][3], bb[2], bb[3]);
            } else {
                if constexpr (kp == 0) {
#pragma unroll
                    for (int i = 0; i < 4; i++) ck[i] = cv[i] = dk[i] = dv[i] = 0.f;
                }
                mma16(ck, pf[0][0], pf[0][1], pf[0][2], pf[0][3], bb[0], bb[1]);
                mma16(cv, pf[1][0], pf[1][1], pf[1][2], pf[1][3], bb[0], bb[1]);
                mma16(dk, pf[2][0], pf[2][1], pf[2][2], pf[2][3], bb[2], bb[3]);
                mma16(dv, pf[3][0], pf[3][1], pf[3][2], pf[3][3], bb[2], bb[3]);
            }
        };
        auto hand_over = [&]() {
#pragma unroll
            for (int i = 0; i < 4; i++) { cv[i] += dv[i]; ck[i] += dk[i]; }
            if (ISV) {
                stsm4f(slot + WG * 2048 + l16, cv);
            } else {
                const float *q = WG ? cv : ck, *k = WG ? ck : cv;
                stsm4t(slot + WG * 2048 + l16, pack2(q[0], q[1]), pack2(q[2], q[3]), pack2(k[0], k[1]), pack2(k[2], k[3]));
            }
        };
        auto repair = [&]() {
            bar_sync(6, 256);
            while (incomplete<8192>(mbw, l16)) {
                refetch(mbw, &g_xmem[s & 3][WG * 512], 8192, bar + (B_RT0 + WG) * 8, w4, 1 + WG, tries);
                prefetch();
                static_for<0, 3>(load_b);
                static_for<0, 16>(kpair);
                hand_over();
            }
            bar_sync(6, 256);
        };
        {
            const uint32_t can = mbw + l16 * 8 + (l16 >> 2);
            uint32_t* const flag = &g_flag[0][u_flag + WG + l16];
            for (;; tries |= 1) {
                asm volatile("" : "+r"(tries));
                if (__builtin_expect(tries, 0)) {
                    refetch(mbw, &g_xmem[s & 3][WG * 512], 8192, bar + (B_RT0 + WG) * 8, w4, 1 + WG, tries);
                }
                mbar_wait(bar + (B_MF0 + WG) * 8, s & 1);
                TS(1);
                static_for<0, 3>(load_b);
                const uint32_t c0 = lds1u(can), c1 = lds1u(can + 4096);
                const uint32_t v = ((gtick() - (ISV ? VLEAD : 0)) << 6) | s;
                kpair(ic<0>{});
                const bool early = __any_sync(~0u, max(c0, c1) == CANARY);
                st_pred1(flag, v, w4 * 512 + l16 == 1536 && !early);
                if (__builtin_expect(!early, 1)) break;
            }
            static_for<1, RFPOS>(kpair);
            if (WG == 0 && !NOFILL) bar_sync(10, 256);
            if (WG == 1 && !NOFILL && w4 == 3) {
                bar_sync(13, 128);
                if (s < NSEG - 1) load_tokens(s + 1, 1, 1);
            }
            static_for<RFPOS, STPOS>(kpair);
            if (!ISV && WG == 1) load_stamps2(st1, g_flag[0], l16, w4 < 2);
            static_for<STPOS, 13>(kpair);
        }
        auto finish_projections = [&]() {
            static_for<13, 16>(kpair);
            hand_over();
            TS(2);
            return bar_sync_any_nan(cv[0], cv[1]);
        };
        if constexpr (!ISV) {
            const uint32_t qa = sb + C_SLOTQ + ((l16 >> 1) & 128) + ((l16 & 128) << 3) + (l16 & 112);
            const uint32_t ma = sb + C_SLOTQ + 256 + l16 + (l16 & 256);
            const uint32_t qx = sb + C_QX + l16 + (l16 & 256);
            auto ldsm_sum = [&](uint32_t* r, uint32_t a) {
                uint32_t t[4];
                ldsm4(r, a); ldsm4(t, a + 2048);
#pragma unroll
                for (int i = 0; i < 4; i++) asm("add.rn.bf16x2 %0, %0, %1;" : "+r"(r[i]) : "r"(t[i]));
            };
            auto tile = [&](float* d, const uint32_t (*q)[4], const uint32_t (*k)[4]) {
                d[0] = d[1] = d[2] = d[3] = 0.f;
#pragma unroll
                for (int i = 0; i < 4; i++) mma16(d, q[i][0], q[i][1], q[i][2], q[i][3], k[i >> 1][(i & 1) * 2], k[i >> 1][(i & 1) * 2 + 1]);
            };
            auto send = [&](int ti, const float* d, bool hold) {
                send_planes(ic<4>{}, sb_x + C_XSL + role * 2560 + ti * 512, B_XS, d, hold);
            };
            if constexpr (WG == 0) {
                auto scores = [&](auto again) {
                    bool nan = false;
                    if (w4 < 2) {
                        uint32_t k0[2][4], k1[2][4], q0[4], q1[4];
                        const uint32_t ka = kl + w4 * 256, dst = sb_v + C_SL + role * 1024 + w4 * 512;
                        ldsm4(k0[0], ka); ldsm4(k0[1], ka + 2048);
                        ldsm4(k1[0], ka + 128); ldsm4(k1[1], ka + 128 + 2048);
                        __syncwarp();
                        if (!again.value) nan = finish_projections();
                        TS(3);
                        ldsm_sum(q0, qa); ldsm_sum(q1, qa + 512);
                        float s0[4] = {0.f, 0.f, 0.f, 0.f}, s1[4] = {0.f, 0.f, 0.f, 0.f}, s2[4] = {0.f, 0.f, 0.f, 0.f}, s3[4] = {0.f, 0.f, 0.f, 0.f};
                        mma16(s0, q0[0], q0[1], q0[2], q0[3], k0[0][0], k0[0][1]);
                        mma16(s1, q0[0], q0[1], q0[2], q0[3], k0[1][0], k0[1][1]);
                        mma16(s2, q0[0], q0[1], q0[2], q0[3], k1[0][0], k1[0][1]);
                        mma16(s3, q0[0], q0[1], q0[2], q0[3], k1[1][0], k1[1][1]);
                        mma16(s0, q1[0], q1[1], q1[2], q1[3], k0[0][2], k0[0][3]);
                        mma16(s1, q1[0], q1[1], q1[2], q1[3], k0[1][2], k0[1][3]);
                        mma16(s2, q1[0], q1[1], q1[2], q1[3], k1[0][2], k1[0][3]);
                        mma16(s3, q1[0], q1[1], q1[2], q1[3], k1[1][2], k1[1][3]);
                        const float out[4] = {s0[0] + s1[2], s0[1] + s1[3], s2[0] + s3[2], s2[1] + s3[3]};
                        send_planes(ic<4>{}, dst, B_SC, out, nan);
                        if (!again.value) bar_arrive(12, 256);
                        TS(4);
                    } else if (w4 == 2) {
                        uint32_t q0[4], q1[4], km[2][4], q[4][4];
                        const uint32_t dst = sb_v + C_SL + 2048 + role * 256;
                        if (!again.value) nan = finish_projections();
                        ldsm_sum(q0, qa); ldsm_sum(km[0], ma); ldsm_sum(km[1], ma + 1024); ldsm_sum(q1, qa + 512);
                        __syncwarp();
#pragma unroll
                        for (int i = 0; i < 4; i++) ldsm4(q[i], qx + 256 + i * 1024);
                        float s0[4] = {0.f, 0.f, 0.f, 0.f}, s1[4] = {0.f, 0.f, 0.f, 0.f}, d0[4];
                        mma16(s0, q0[0], q0[1], q0[2], q0[3], km[0][0], km[0][1]);
                        mma16(s1, q0[0], q0[1], q0[2], q0[3], km[1][0], km[1][1]);
                        mma16(s0, q1[0], q1[1], q1[2], q1[3], km[0][2], km[0][3]);
                        mma16(s1, q1[0], q1[1], q1[2], q1[3], km[1][2], km[1][3]);
                        const float out[2] = {s0[0] + s1[2], s0[1] + s1[3]};
                        send_planes(ic<2>{}, dst, B_SC, out, nan);
                        if (!NOFILL) tile(d0, q, km);
                        if (!again.value) bar_sync(12, 256);
                        if (!NOFILL) send(0, d0, nan);
                    } else {
                        if (!again.value) {
                            nan = finish_projections();
                            if (s < NSEG - 1) load_tokens(s + 1, 1, 0);
                        }
                        uint32_t q[4][4], k0[2][4], k1[2][4], km[2][4];
                        float d0[4], d1[4], d2[4];
                        if (!NOFILL) {
#pragma unroll
                            for (int i = 0; i < 4; i++) ldsm4(q[i], qx + i * 1024);
                            ldsm4(k0[0], kl); ldsm4(k0[1], kl + 2048);
                            ldsm4(k1[0], kl + 128); ldsm4(k1[1], kl + 128 + 2048);
                            tile(d1, q, k0); tile(d2, q, k1);
                            ldsm_sum(km[0], ma); ldsm_sum(km[1], ma + 1024);
                            tile(d0, q, km);
                        }
                        if (!again.value) bar_sync(12, 256);
                        if (!NOFILL) { send(0, d0, nan); send(1, d1, nan); send(2, d2, nan); }
                    }
                    return nan;
                };
                if (__builtin_expect(__any_sync(~0u, scores(ic<0>{})), 0)) { repair(); scores(ic<1>{}); }
                if (__builtin_expect(s == NSEG - 1, 0)) break;
            } else {
                const bool nan = finish_projections();
                mbar_wait(bar + B_WS * 8, 0);
                missing = stamps_missing<6>(st1.v, s);
                target = latest_stamp<6>(st1.v, lds4u(sb + C_CAL)) + DLY1;
                asm volatile("" : "+r"(target), "+r"(missing));
                if (!NOFILL) {
                    uint32_t q[4][4], k0[2][4];
                    float d1[4];
#pragma unroll
                    for (int i = 0; i < 4; i++) ldsm4(q[i], qx + 256 + i * 1024);
                    ldsm4(k0[0], kl + w4 * 128); ldsm4(k0[1], kl + w4 * 128 + 2048);
                    tile(d1, q, k0);
                    mbar_wait(bar + B_XF1 * 8, s == NSEG - 1);
                    bar_sync(12, 256);
                    send(1 + w4, d1, false);
                } else {
                    bar_sync(12, 256);
                }
                if (__builtin_expect(__any_sync(~0u, nan), 0)) repair();
                if (__builtin_expect(s == NSEG - 1, 0)) {
                    asm volatile("" : "+r"(l16));
                    if (w4 >= 2 && !NOFILL) token_softmax();
                    break;
                }
            }
        } else {
            const uint32_t lane_b = sb + C_V + w4 * 512 + ((l16 & 384) << 4) + (l16 & 112);
            auto load_vx = [&](uint32_t (*vx)[4], int ss) {
#pragma unroll
                for (int j = 0; j < 4; j++) ldsm4(vx[j], ((lane_b + (ss & 1) * 10240) ^ (j * 32)) + j * 128);
            };
            auto load_vm = [&](uint32_t* vm, int ss) { ldsm4(vm, sb + C_V + (ss & 1) * 10240 + w4 * 512 + 8192 + (l16 ^ ((l16 >> 2) & 96))); };
            auto token_output = [&](int ss) {
                uint32_t vx[4][4], vm[4];
                const uint32_t pl = sb + C_PL + (ss & 1) * 2048 + l16;
                auto lds_frag = [&](uint32_t a) { uint32_t r[4]; ldsm4(r, a); return make_uint4(r[0], r[1], r[2], r[3]); };
                load_vm(vm, ss);
                load_vx(vx, ss);
                mbar_wait(bar + (B_P0 + (ss & 1)) * 8, (ss >> 1) & 1);
                uint32_t dep = 0;
#pragma unroll
                for (int mh = 1; mh >= 0; mh--) {
                    uint2 pm;
                    asm volatile("ldmatrix.sync.aligned.m8n8.x2.shared.b16 {%0,%1}, [%2];" : "=r"(pm.x), "=r"(pm.y) : "r"(pl + mh * 768 + dep) : "memory");
                    const uint4 p0 = lds_frag(pl + mh * 768 + 256);
                    float o[4][4];
#pragma unroll
                    for (int j = 0; j < 4; j++) { o[j][0] = o[j][1] = o[j][2] = o[j][3] = 0.f; mma8(o[j], pm.x, pm.y, vm[j]); }
#pragma unroll
                    for (int j = 0; j < 4; j++) mma16(o[j], p0.x, p0.y, p0.z, p0.w, vx[j][0], vx[j][1]);
                    if (mh) {
                        const uint4 p1 = lds_frag(pl + 1536);
#pragma unroll
                        for (int j = 0; j < 4; j++) mma16(o[j], p1.x, p1.y, p1.z, p1.w, vx[j][2], vx[j][3]);
                    }
                    oxp[2 * mh] = make_uint4(pack2(o[0][0], o[0][1]), pack2(o[1][0], o[1][1]), pack2(o[2][0], o[2][1]), pack2(o[3][0], o[3][1]));
                    oxp[2 * mh + 1] = make_uint4(pack2(o[0][2], o[0][3]), pack2(o[1][2], o[1][3]), pack2(o[2][2], o[2][3]), pack2(o[3][2], o[3][3]));
                    asm volatile("" : "+r"(oxp[2 * mh].x), "+r"(oxp[2 * mh].y), "+r"(oxp[2 * mh].z), "+r"(oxp[2 * mh].w),
                                 "+r"(oxp[2 * mh + 1].x), "+r"(oxp[2 * mh + 1].y), "+r"(oxp[2 * mh + 1].z), "+r"(oxp[2 * mh + 1].w));
                    dep = oxp[2].x == ~0u ? 16 : 0;
                }
            };
            const uint32_t vd = v_row + (s & 1) * 10240 + 8192 + ((l16 & 96) << 2) + ((l16 & 112) ^ v_b ^ ((l16 & 128) >> 2));
            uint32_t vx[4][4], vm[4];
            if (WG == 0) { load_vx(vx, s); __syncwarp(); }
            if (__builtin_expect(__any_sync(~0u, finish_projections()), 0)) { repair(); if (WG == 0) load_vx(vx, s); }
            float r[4];
            ldsm4f(r, slot + (WG ^ 1) * 2048 + l16);
            stsm2(vd, pack2(ck[0] + r[0], ck[1] + r[1]), pack2(ck[2] + r[2], ck[3] + r[3]));
            TSX(3, WG == 0 && w4 == 0);
            if (WG == 1) {
                bar_arrive(11, 256);
                if (w4 == 3 && l16 < 32) mbar_arrive_cluster(mapa(bar + B_VF * 8, 2 * hh + (l16 >> 4)));
                if (w4 == 2 && s < NSEG - 1) load_tokens(s + 1, 1, 0);
                if (!NOFILL) {
                    token_output(s - 1);
                    if (w4 == 1 && l16 == 0 && s > 0) mbar_expect(bar + (B_P0 + ((s - 1) & 1)) * 8, 2048);
                    mbar_wait(bar + B_XF1 * 8, s == NSEG - 1);
                }
            }
            if (WG == 0) bar_sync(11, 256);
            if (__builtin_expect(s == NSEG - 1, 0)) {
                bar_sync(6, 256);
                if (WG == 1) {
                    if (!NOFILL) {
                        store_ox(s - 1);
                        token_output(s);
                        store_ox(s);
                    }
                    bar_sync(2, 128);
                    if (w4 == 0 && l16 == 0) {
                        if (NOFILL) for (int i = 0; i < 15; i++) count_up(CNT_OX + i);
                        count_up(CNT_OX + 15);
                    }
                    __syncwarp();
                }
                mbar_wait(bar + B_SC * 8, s & 1);
                break;
            }
            if constexpr (WG == 0) {
                load_vm(vm, s);
                const uint32_t oo = u_off + ((l16 & 48) << 3) + ((l16 >> 2) & 112);
                char* dst = reinterpret_cast<char*>(&g_xo[s & 3][0]) + oo;
                mbar_wait(bar + B_SC * 8, s & 1);
                TS(4);
                float a0[4], b0[4], a1[4], b1[4], a2[4];
                ldsm4f(a0, sb + C_SL + l16); ldsm4f(b0, sb + C_SL + 1024 + l16);
                ldsm4f(a1, sb + C_SL + 512 + l16); ldsm4f(b1, sb + C_SL + 1536 + l16);
                ldsm4f(a2, sb + C_SL + 2048 + l16);
                const float e[10] = {a0[0] + b0[0], a0[1] + b0[1], a0[2] + b0[2], a0[3] + b0[3], a1[0] + b1[0], a1[1] + b1[1], a1[2] + b1[2], a1[3] + b1[3],
                                     a2[0] + a2[2], a2[1] + a2[3]};
                float m = fmaxf(fmaxf(fmaxf(e[0], e[1]), fmaxf(e[2], e[3])), fmaxf(fmaxf(e[4], e[5]), fmaxf(e[6], e[7])));
                m = fmaxf(m, fmaxf(e[8], e[9]));
                m = fmaxf(fmaxf(m, __shfl_xor_sync(~0u, m, 1)), fmaxf(__shfl_xor_sync(~0u, m, 2), __shfl_xor_sync(~0u, m, 3)));
                m *= -SM_SCALE;
                float x[10];
#pragma unroll
                for (int i = 0; i < 10; i++) x[i] = ex2(fmaf(e[i], SM_SCALE, m));
                float o[4][4];
                const uint32_t p0 = pack2(x[0], x[1]), p1 = pack2(x[2], x[3]), j0 = __float_as_uint(x[1]), j1 = __float_as_uint(x[3]);
#pragma unroll
                for (int j = 0; j < 4; j++) { o[j][0] = o[j][1] = o[j][2] = o[j][3] = 0.f; mma16(o[j], p0, j0, p1, j1, vx[j][0], vx[j][1]); }
                const uint32_t p2 = pack2(x[4], x[5]), p3 = pack2(x[6], x[7]), j2 = __float_as_uint(x[5]), j3 = __float_as_uint(x[7]);
#pragma unroll
                for (int j = 0; j < 4; j++) mma16(o[j], p2, j2, p3, j3, vx[j][2], vx[j][3]);
                const uint32_t p4 = pack2(x[8], x[9]), j4 = __float_as_uint(x[9]);
                float l = (((x[0] + x[1]) + (x[2] + x[3])) + ((x[4] + x[5]) + (x[6] + x[7]))) + (x[8] + x[9]);
                l = (l + __shfl_xor_sync(~0u, l, 1)) + (__shfl_xor_sync(~0u, l, 2) + __shfl_xor_sync(~0u, l, 3));
#pragma unroll
                for (int j = 0; j < 4; j++) mma8(o[j], p4, j4, vm[j]);
                l = rcp(l);
                st_relaxed4(reinterpret_cast<uint4*>(dst), make_uint4(pack2(o[0][0] * l, o[0][1] * l), pack2(o[1][0] * l, o[1][1] * l),
                                                                      pack2(o[2][0] * l, o[2][1] * l), pack2(o[3][0] * l, o[3][1] * l)));
                bar_arrive(3, 256);
                if (w4 == 0 && l16 == 0) mbar_expect(bar + B_SC * 8, 2560);
            }
        }
    }
}

__global__ void __cluster_dims__(6, 1, 1) __launch_bounds__(256, 1)
chain_kernel(const __grid_constant__ CUtensorMap tq, const __grid_constant__ CUtensorMap tk, const __grid_constant__ CUtensorMap tv,
             const __grid_constant__ CUtensorMap two, const __grid_constant__ Descs D, const __grid_constant__ Descs DV,
             const __nv_bfloat16* __restrict__ x, const __nv_bfloat16* __restrict__ mem0) {
    extern __shared__ __align__(1024) uint8_t smem[];
    const uint32_t sb = smem_u32(smem);
    const int rank = blockIdx.x % 6, cl = blockIdx.x / 6, role = rank >= 4 ? 2 : rank & 1;
    const int tid = threadIdx.x, lane = tid & 31, gw = blockIdx.x * 8 + uni(tid >> 5);
    const CUtensorMap *tA = role == 2 ? &tv : &tq, *tB = role == 2 ? &tv : &tk;
    uint4 cur[4], nxt[4];
#pragma unroll
    for (int j = 0; j < 4; j++) {
        cur[j] = reinterpret_cast<const uint4*>(x)[gw * 128 + j * 32 + lane];
        nxt[j] = reinterpret_cast<const uint4*>(x)[(gw + 768) * 128 + j * 32 + lane];
    }
    if (gw < 512 && lane < 16) asm volatile("prefetch.global.L2 [%0];" :: "l"(x + (gw + 1536) * DM + lane * 64));
    if ((gw & 7) == 0) {
        if (tid == 0) { TL(1, 0); TLSM(1); }
        if ((sb & 0xFFFFFF) != SB0 || mapa(sb, 5) != (SB0 | 0x5000000u)) sts1u(1, 0);
        const uint32_t b = sb + C_BAR + lane * 8;
        uint32_t tx = 0;
        if (lane <= B_WS) tx = 65536;
        if (lane == B_MF0 || lane == B_MF1) tx = 8192;
        if (lane == B_OF) tx = (role == 2 ? ONKV : ONKQ) * (256 + 2048);
        if (lane == B_SC) tx = 2560;
        if (lane == B_P0 || lane == B_P1) tx = 2048;
        if (lane == B_XS || lane == B_OL) tx = (lane == B_XS && role) ? 5120 : 3072;
        if (lane < B_NUM) mbar_init(b, lane == B_MBF ? 12 : (lane == B_GO ? 4 : 1));
        if (tx) mbar_expect(b, tx);
        asm volatile("fence.mbarrier_init.release.cluster;" ::: "memory");
        fence_async();
        __syncwarp();
#pragma unroll 1
        for (int i = 0; i < 12; i++)
            if (elect()) load_box(tA, tB, cl, rank, sb + (i >> 2) * 65536, i >> 2, i & 3, sb + C_BAR + (i >> 2) * 8);
    }
    __syncwarp();
    asm volatile("barrier.cluster.arrive.release.aligned;" ::: "memory");
    reset_exchange(mem0);
#pragma unroll 1
    for (int row = gw; row < SEQ; row += 768) {
        uint4 v[4];
#pragma unroll
        for (int j = 0; j < 4; j++) {
            v[j] = cur[j]; cur[j] = nxt[j];
            if (row + 1536 < SEQ) nxt[j] = reinterpret_cast<const uint4*>(x)[(row + 1536) * 128 + j * 32 + lane];
        }
        ln_row(v, row, lane);
    }
    if (tid == 0) TL(1, 5);
    __syncthreads();
    uint32_t goal = 0;
    if (tid == 160) {
        __threadfence();
        goal = (atomicAdd(&g_epoch, 1u) / 96 + 1) * 96;
        asm volatile("griddepcontrol.launch_dependents;" ::: "memory");
        TL(1, 4);
    }
    __syncwarp();
    asm volatile("barrier.cluster.wait.acquire.aligned;" ::: "memory");
    goal = uni(goal);
    const int wg = uni(threadIdx.x >> 7);
    if (role == 2) {
        if (wg == 0) chain_main<true, 0>(&tv, &tv, &two, sb, cl, rank, DV, goal);
        else chain_main<true, 1>(&tv, &tv, &two, sb, cl, rank, DV, goal);
    } else {
        if (wg == 0) chain_main<false, 0>(&tq, &tk, &two, sb, cl, rank, D, goal);
        else chain_main<false, 1>(&tq, &tk, &two, sb, cl, rank, D, goal);
    }
    __syncwarp();
    cluster_sync();
    if (threadIdx.x == 0) TL(1, 1);
}

__device__ __forceinline__ void wg256(float* d, uint32_t da, uint32_t db, uint32_t accum) {
    asm volatile("{\n.reg .b64 da, db;\n.reg .pred p;\nsetp.ne.u32 p, %130, 0;\nmov.b64 da, {%128, " DESC_HI_SW128 "};\nmov.b64 db, {%129, " DESC_HI_SW128 "};\n"
                 "wgmma.mma_async.sync.aligned.m64n256k16.f32.bf16.bf16 {"
                 "%0,%1,%2,%3,%4,%5,%6,%7,%8,%9,%10,%11,%12,%13,%14,%15,%16,%17,%18,%19,%20,%21,%22,%23,%24,%25,%26,%27,%28,%29,%30,%31,"
                 "%32,%33,%34,%35,%36,%37,%38,%39,%40,%41,%42,%43,%44,%45,%46,%47,%48,%49,%50,%51,%52,%53,%54,%55,%56,%57,%58,%59,%60,%61,%62,%63,"
                 "%64,%65,%66,%67,%68,%69,%70,%71,%72,%73,%74,%75,%76,%77,%78,%79,%80,%81,%82,%83,%84,%85,%86,%87,%88,%89,%90,%91,%92,%93,%94,%95,"
                 "%96,%97,%98,%99,%100,%101,%102,%103,%104,%105,%106,%107,%108,%109,%110,%111,%112,%113,%114,%115,%116,%117,%118,%119,%120,%121,%122,%123,%124,%125,%126,%127"
                 "}, da, db, p, 1, 1, 0, 1;\n}"
                 : ACC16(d), ACC16((d + 16)), ACC16((d + 32)), ACC16((d + 48)), ACC16((d + 64)), ACC16((d + 80)), ACC16((d + 96)), ACC16((d + 112))
                 : "r"(da), "r"(db), "r"(accum));
}
__device__ __forceinline__ void wg128(float* d, uint32_t da, uint32_t db, uint32_t accum) {
    asm volatile("{\n.reg .b64 da, db;\n.reg .pred p;\nsetp.ne.u32 p, %66, 0;\nmov.b64 da, {%64, " DESC_HI_SW128 "};\nmov.b64 db, {%65, " DESC_HI_SW128 "};\n"
                 "wgmma.mma_async.sync.aligned.m64n128k16.f32.bf16.bf16 {"
                 "%0,%1,%2,%3,%4,%5,%6,%7,%8,%9,%10,%11,%12,%13,%14,%15,%16,%17,%18,%19,%20,%21,%22,%23,%24,%25,%26,%27,%28,%29,%30,%31,"
                 "%32,%33,%34,%35,%36,%37,%38,%39,%40,%41,%42,%43,%44,%45,%46,%47,%48,%49,%50,%51,%52,%53,%54,%55,%56,%57,%58,%59,%60,%61,%62,%63"
                 "}, da, db, p, 1, 1, 0, 1;\n}"
                 : ACC16(d), ACC16((d + 16)), ACC16((d + 32)), ACC16((d + 48))
                 : "r"(da), "r"(db), "r"(accum));
}
__device__ __forceinline__ float sigmoidf_(float v) { return rcp(1.f + ex2(-1.4426950408889634f * v)); }
__device__ __forceinline__ void wait_count(int idx, uint32_t n) {
    uint32_t v, it = 0;
    while (true) {
        asm volatile("ld.acquire.gpu.global.u32 %0, [%1];" : "=r"(v) : "l"(&g_cnt[idx * 8]) : "memory");
        if (v >= n) break;
        __nanosleep(100);
        spin_guard(it);
    }
    asm volatile("fence.proxy.async.global;" ::: "memory");
}

constexpr int G_STAGES = 4, G_PAIRS = 18;
constexpr uint32_t G_STAGE = 49152, G_EPI = G_STAGES * G_STAGE, G_BAR = G_EPI + 32768, G_SMEM = G_BAR + 256;
__device__ __forceinline__ int glu_job(int p, int j) {
    if (j < 12) return j * G_PAIRS + p;
    if (p < 14) return j == 12 ? 224 + p : (j == 13 ? 242 + p : -1);
    return j < 14 ? 216 + (j - 12) * 4 + (p - 14) : (j == 14 ? 224 + p : -1);
}

__global__ void __cluster_dims__(2, 1, 1) __launch_bounds__(384, 1)
glu_kernel(const __grid_constant__ CUtensorMap tXn, const __grid_constant__ CUtensorMap tG, const __grid_constant__ CUtensorMap tU,
           const __grid_constant__ CUtensorMap tHst, const __grid_constant__ CUtensorMap tHld, const __grid_constant__ CUtensorMap tD,
           const __grid_constant__ CUtensorMap tYst) {
    extern __shared__ __align__(1024) uint8_t smem[];
    const uint32_t sb = smem_u32(smem);
    const uint32_t full = sb + G_BAR, empty = full + 64;
    const int tid = threadIdx.x, lane = tid & 31;
    const int warp = uni(tid >> 5), wg = warp >> 2;
    const int rank = blockIdx.x & 1, pair = blockIdx.x >> 1;
    asm volatile("griddepcontrol.launch_dependents;" ::: "memory");
    if (tid == 0) {
        TL(2, 0); TLSM(2);
        for (int i = 0; i < G_STAGES; i++) { mbar_init(full + i * 8, 1); mbar_init(empty + i * 8, 16); }
        asm volatile("fence.mbarrier_init.release.cluster;" ::: "memory");
        fence_async();
    }
    __syncthreads();
    cluster_sync();
    if (wg == 0) {
        asm volatile("setmaxnreg.dec.sync.aligned.u32 40;");
        if (warp == 0) {
            if (lane == 0) {
                uint32_t st = 0, ph = 1;
                asm volatile("fence.acq_rel.gpu;\nfence.proxy.async.global;" ::: "memory");
                for (int j = 0, job; (job = glu_job(pair, j)) >= 0; j++) {
                    const bool dn = job >= 224;
                    const int mp = dn ? (job - 224) >> 2 : job / 28, nt = dn ? job & 3 : job % 28, rb = mp * 2 + rank;
                    const CUtensorMap* tA = dn ? &tHld : &tXn;
                    const CUtensorMap* tB = dn ? &tD : (rank ? &tU : &tG);
                    const int bcol = dn ? nt * 256 + rank * 128 : nt * 128, nkb = dn ? FF / 64 : DM / 64;
                    if (j == 12) TL(2, 2);
                    if (dn) wait_count(CNT_H + rb, 56);
                    for (int kb = 0; kb < nkb; kb++) {
                        mbar_wait(empty + st * 8, ph);
                        const uint32_t base = sb + st * G_STAGE;
                        mbar_expect(full + st * 8, G_STAGE);
                        tma2d(base, tA, kb * 64, rb * 128, full + st * 8);
                        tma2d_mc(base + 16384 + rank * 16384, tB, bcol, kb * 64, full + st * 8, 3);
                        tma2d_mc(base + 16384 + rank * 16384 + 8192, tB, bcol + 64, kb * 64, full + st * 8, 3);
                        if (++st == G_STAGES) { st = 0; ph ^= 1; }
                    }
                }
            }
        } else if (warp < 3) {
            const int cw = warp - 1;
            const uint32_t epi = sb + G_EPI + cw * 16384;
            bar_arrive(3 + cw, 160);
            for (int j = 0, job; (job = glu_job(pair, j)) >= 0; j++) {
                const bool dn = job >= 224;
                const int mp = dn ? (job - 224) >> 2 : job / 28, nt = dn ? job & 3 : job % 28, rb = mp * 2 + rank;
                for (int hp = 0; hp <= (int)dn; hp++) {
                    bar_sync(1 + cw, 160);
                    if (lane == 0) {
                        const int col = dn ? nt * 256 + hp * 128 : nt * 128;
                        tma2d_store(dn ? &tYst : &tHst, col, rb * 128 + cw * 64, epi);
                        tma2d_store(dn ? &tYst : &tHst, col + 64, rb * 128 + cw * 64, epi + 8192);
                        asm volatile("cp.async.bulk.commit_group;\ncp.async.bulk.wait_group.read 0;" ::: "memory");
                    }
                    __syncwarp();
                    bar_arrive(3 + cw, 160);
                    if (lane == 0) {
                        asm volatile("cp.async.bulk.wait_group 0;\nfence.proxy.async.global;" ::: "memory");
                        count_up(dn ? CNT_Y + rb * 8 + nt * 2 + hp : CNT_H + rb);
                    }
                    __syncwarp();
                }
            }
        }
        cluster_sync();
    } else {
        asm volatile("setmaxnreg.inc.sync.aligned.u32 232;");
        const int cw = wg - 1, w4 = warp & 3;
        const uint32_t empty_dst = mapa(empty, lane & 1);
        const int er = w4 * 16 + (lane & 15), ec = lane >> 4;
        const uint32_t epi = sb + G_EPI + cw * 16384 + er * 128;
        uint32_t st = 0, ph = 0;
        float acc[128];
        auto put = [&](const uint32_t* o) {
            bar_sync(3 + cw, 160);
#pragma unroll
            for (int q = 0; q < 8; q++) stsm4(epi + (q >> 2) * 8192 + (((2 * (q & 3) + ec) ^ (er & 7)) << 4), o[q * 4], o[q * 4 + 1], o[q * 4 + 2], o[q * 4 + 3]);
            fence_async();
            bar_arrive(1 + cw, 160);
        };
        for (int j = 0, job; (job = glu_job(pair, j)) >= 0; j++) {
            const bool dn = job >= 224;
            const int nkb = dn ? FF / 64 : DM / 64;
            uint32_t prev = 0;
#pragma unroll 1
            for (int kb = 0; kb < nkb; kb++) {
                mbar_wait(full + st * 8, ph);
                const uint32_t base = sb + st * G_STAGE;
                const uint32_t da = (((base + cw * 8192) & 0x3FFFF) >> 4) | (1u << 16);
                const uint32_t db = (((base + 16384) & 0x3FFFF) >> 4) | (512u << 16);
                wg_fence();
#pragma unroll
                for (int k = 0; k < 4; k++) wg256(acc, da + k * 2, db + k * 128, (kb | k) != 0);
                wg_commit();
                if (kb > 0) {
                    wg_wait<1>();
                    if (lane < 2) mbar_arrive_cluster(empty_dst + prev * 8);
                }
                prev = st;
                if (++st == G_STAGES) { st = 0; ph ^= 1; }
            }
            wg_wait<0>();
            reg_fence<128>(acc);
            if (lane < 2) mbar_arrive_cluster(empty_dst + prev * 8);
            uint32_t o[32];
            if (!dn) {
#pragma unroll
                for (int i = 0; i < 32; i++) o[i] = pack2(sigmoidf_(acc[2 * i]) * acc[64 + 2 * i], sigmoidf_(acc[2 * i + 1]) * acc[65 + 2 * i]);
                put(o);
            } else {
#pragma unroll
                for (int hp = 0; hp < 2; hp++) {
#pragma unroll
                    for (int i = 0; i < 32; i++) {
                        const float a = acc[hp * 64 + 2 * i], b = acc[hp * 64 + 2 * i + 1];
                        o[i] = pack2(sigmoidf_(a) * a, sigmoidf_(b) * b);
                    }
                    put(o);
                }
            }
        }
        bar_sync(3 + cw, 160);
        if (tid == 128) TL(2, 1);
        cluster_sync();
    }
}

constexpr int O_STAGES = 7;
constexpr uint32_t O_STAGE = 32768, O_BAR = O_STAGES * O_STAGE, O_SMEM = O_BAR + 256;

__global__ void __cluster_dims__(2, 1, 1) __launch_bounds__(384, 1)
out_kernel(const __grid_constant__ CUtensorMap tOx, const __grid_constant__ CUtensorMap tWo, const __grid_constant__ CUtensorMap tX,
           const __grid_constant__ CUtensorMap tY, const __grid_constant__ CUtensorMap tOut) {
    extern __shared__ __align__(1024) uint8_t smem[];
    const uint32_t sb = smem_u32(smem);
    const uint32_t full = sb + O_BAR, empty = full + 64;
    const int tid = threadIdx.x, lane = tid & 31;
    const int warp = uni(tid >> 5), wg = warp >> 2;
    const int rank = blockIdx.x & 1, nt = (blockIdx.x >> 1) & 7, rb = (blockIdx.x >> 4) * 2 + rank;
    constexpr int NKB = HD / 64;
    if (tid == 0) {
        TL(3, 0); TLSM(3);
        for (int i = 0; i < O_STAGES; i++) { mbar_init(full + i * 8, 1); mbar_init(empty + i * 8, 16); }
        asm volatile("fence.mbarrier_init.release.cluster;" ::: "memory");
        fence_async();
    }
    __syncthreads();
    cluster_sync();
    if (wg == 0) {
        if (tid == 0) {
            uint32_t st = 0, ph = 1;
            for (int kb = 0; kb < O_STAGES; kb++) {
                mbar_expect(full + kb * 8, O_STAGE);
                tma2d_mc(sb + kb * O_STAGE + 16384 + rank * 8192, &tWo, nt * 128 + rank * 64, kb * 64, full + kb * 8, 3);
            }
            wait_count(CNT_OX + rb, 32);
            TL(3, 2);
            for (int kb = 0; kb < NKB + 2; kb++) {
                const uint32_t base = sb + st * O_STAGE;
                if (kb >= O_STAGES) {
                    mbar_wait(empty + st * 8, ph);
                    mbar_expect(full + st * 8, O_STAGE);
                }
                if (kb < NKB) {
                    tma2d(base, &tOx, kb * 64, rb * 128, full + st * 8);
                    if (kb >= O_STAGES) tma2d_mc(base + 16384 + rank * 8192, &tWo, nt * 128 + rank * 64, kb * 64, full + st * 8, 3);
                } else {
                    if (kb == NKB) wait_count(CNT_Y + rb * 8 + nt, 2);
                    tma2d(base, &tX, nt * 128 + (kb - NKB) * 64, rb * 128, full + st * 8);
                    tma2d(base + 16384, &tY, nt * 128 + (kb - NKB) * 64, rb * 128, full + st * 8);
                }
                if (++st == O_STAGES) { st = 0; ph ^= 1; }
            }
        }
        __syncwarp();
    } else {
        const int cw = wg - 1, w4 = warp & 3;
        const uint32_t empty_dst = mapa(empty, lane & 1);
        const int er = cw * 64 + w4 * 16 + (lane & 15), ec = lane >> 4;
        uint32_t st = 0, ph = 0, prev = 0;
        float acc[64];
#pragma unroll 1
        for (int kb = 0; kb < NKB; kb++) {
            mbar_wait(full + st * 8, ph);
            const uint32_t base = sb + st * O_STAGE;
            const uint32_t da = (((base + cw * 8192) & 0x3FFFF) >> 4) | (1u << 16);
            const uint32_t db = (((base + 16384) & 0x3FFFF) >> 4) | (512u << 16);
            wg_fence();
#pragma unroll
            for (int k = 0; k < 4; k++) wg128(acc, da + k * 2, db + k * 128, (kb | k) != 0);
            wg_commit();
            if (kb > 0) {
                wg_wait<1>();
                if (lane < 2) mbar_arrive_cluster(empty_dst + prev * 8);
            }
            prev = st;
            if (++st == O_STAGES) { st = 0; ph ^= 1; }
        }
        wg_wait<0>();
        reg_fence<64>(acc);
#pragma unroll
        for (int bx = 0; bx < 2; bx++) {
            mbar_wait(full + st * 8, ph);
            const uint32_t base = sb + st * O_STAGE;
#pragma unroll
            for (int j = 0; j < 4; j++) {
                uint32_t xv[4], yv[4];
                const uint32_t ad = base + er * 128 + (((2 * j + ec) ^ (er & 7)) << 4);
                ldsm4(xv, ad); ldsm4(yv, ad + 16384);
                const float* a = acc + bx * 32 + j * 8;
#pragma unroll
                for (int i = 0; i < 4; i++)
                    xv[i] = pack2(fmaf(a[2 * i], bf_lo(yv[i]), bf_lo(xv[i])), fmaf(a[2 * i + 1], bf_hi(yv[i]), bf_hi(xv[i])));
                stsm4(ad, xv[0], xv[1], xv[2], xv[3]);
            }
            fence_async();
            bar_sync(1 + cw, 128);
            if ((tid & 127) == 0) {
                tma2d_store(&tOut, nt * 128 + bx * 64, rb * 128 + cw * 64, base + cw * 8192);
                asm volatile("cp.async.bulk.commit_group;" ::: "memory");
            }
            if (++st == O_STAGES) { st = 0; ph ^= 1; }
        }
        if ((tid & 127) == 0) asm volatile("cp.async.bulk.wait_group 0;" ::: "memory");
        if (tid == 128) TL(3, 1);
        __syncwarp();
    }
    cluster_sync();
}

typedef CUresult (*EncodeFn)(CUtensorMap*, CUtensorMapDataType, cuuint32_t, void*, const cuuint64_t*, const cuuint64_t*, const cuuint32_t*,
                             const cuuint32_t*, CUtensorMapInterleave, CUtensorMapSwizzle, CUtensorMapL2promotion, CUtensorMapFloatOOBfill);

CUtensorMap make_map(EncodeFn enc, const void* p, int rows, int cols, int box_rows) {
    CUtensorMap m;
    cuuint64_t dims[2] = {(cuuint64_t)cols, (cuuint64_t)rows}, strides[1] = {(cuuint64_t)cols * 2};
    cuuint32_t box[2] = {64, (cuuint32_t)box_rows}, es[2] = {1, 1};
    enc(&m, CU_TENSOR_MAP_DATA_TYPE_BFLOAT16, 2, const_cast<void*>(p), dims, strides, box, es, CU_TENSOR_MAP_INTERLEAVE_NONE,
        CU_TENSOR_MAP_SWIZZLE_128B, CU_TENSOR_MAP_L2_PROMOTION_L2_128B, CU_TENSOR_MAP_FLOAT_OOB_FILL_NONE);
    return m;
}

}

#define PDL 7
extern "C" void kernel_launch(void* const* d_in, const int* in_sizes, int n_in, void* d_out, int out_size) {
    const __nv_bfloat16* x = (const __nv_bfloat16*)d_in[0];
    const __nv_bfloat16* mem0 = (const __nv_bfloat16*)d_in[1];
    void* fn = nullptr;
    cudaDriverEntryPointQueryResult qr;
    cudaGetDriverEntryPoint("cuTensorMapEncodeTiled", &fn, cudaEnableDefault, &qr);
    EncodeFn enc = (EncodeFn)fn;
    void *xn, *ox, *h, *y;
    cudaGetSymbolAddress(&xn, g_xn); cudaGetSymbolAddress(&ox, g_ox); cudaGetSymbolAddress(&h, g_h); cudaGetSymbolAddress(&y, g_y);

    const CUtensorMap tq = make_map(enc, d_in[2], DM, HD, 128), tk = make_map(enc, d_in[3], DM, HD, 128), tv = make_map(enc, d_in[4], DM, HD, 128);
    const CUtensorMap two16 = make_map(enc, d_in[5], HD, DM, 16);
    const CUtensorMap txn128 = make_map(enc, xn, SEQ, DM, 128), tg = make_map(enc, d_in[8], DM, FF, 64), tu = make_map(enc, d_in[9], DM, FF, 64);
    const CUtensorMap th64 = make_map(enc, h, SEQ, FF, 64), th128 = make_map(enc, h, SEQ, FF, 128), td = make_map(enc, d_in[10], FF, DM, 64);
    const CUtensorMap ty64 = make_map(enc, y, SEQ, DM, 64), ty128 = make_map(enc, y, SEQ, DM, 128), tx128 = make_map(enc, x, SEQ, DM, 128);
    const CUtensorMap tox = make_map(enc, ox, SEQ, HD, 128), two64 = make_map(enc, d_in[5], HD, DM, 64), tout = make_map(enc, d_out, SEQ, DM, 64);

    cudaFuncSetAttribute(chain_kernel, cudaFuncAttributeMaxDynamicSharedMemorySize, C_SMEM);
    cudaFuncSetAttribute(glu_kernel, cudaFuncAttributeMaxDynamicSharedMemorySize, G_SMEM);
    cudaFuncSetAttribute(out_kernel, cudaFuncAttributeMaxDynamicSharedMemorySize, O_SMEM);

    Descs D;
    for (int i = 0; i < 4; i++) D.sw[i] = DSW;
    D.ns = DNS;
    cudaStream_t st = cudaStreamPerThread;
    cudaLaunchAttribute at;
    at.id = cudaLaunchAttributeProgrammaticStreamSerialization;
    at.val.programmaticStreamSerializationAllowed = 1;
    cudaLaunchConfig_t cfg = {};
    cfg.stream = st; cfg.attrs = &at; cfg.numAttrs = 0;
    cfg.gridDim = dim3(96); cfg.blockDim = dim3(256); cfg.dynamicSmemBytes = C_SMEM;
    cudaLaunchKernelEx(&cfg, chain_kernel, tq, tk, tv, two16, D, D, x, mem0);
    cfg.gridDim = dim3(2 * G_PAIRS); cfg.blockDim = dim3(384); cfg.dynamicSmemBytes = G_SMEM; cfg.numAttrs = (PDL >> 1) & 1;
    cudaLaunchKernelEx(&cfg, glu_kernel, txn128, tg, tu, th64, th128, td, ty64);
    cfg.gridDim = dim3(128); cfg.dynamicSmemBytes = O_SMEM; cfg.numAttrs = (PDL >> 2) & 1;
    cudaLaunchKernelEx(&cfg, out_kernel, tox, two64, tx128, ty128, tout);
}
```

```cpp
#include <cuda_runtime.h>
#include <cuda_bf16.h>
#include <cuda.h>
#include <stdint.h>
#include <type_traits>

namespace {

constexpr int SEQ = 2048, DM = 1024, HD = 4096, FF = 3584, NSEG = 64;

__device__ __align__(1024) __nv_bfloat16 g_xn[SEQ * DM];
__device__ __align__(1024) uint4 g_xc[SEQ * DM / 8];
__device__ __align__(1024) __nv_bfloat16 g_ox[SEQ * HD];
__device__ __align__(1024) __nv_bfloat16 g_h[SEQ * FF];
__device__ __align__(1024) __nv_bfloat16 g_y[SEQ * DM];
__device__ __align__(1024) uint4 g_xmem[4][1024];
__device__ __align__(1024) uint4 g_xo[4][4096];
#define FSTR 8
__device__ __align__(1024) uint32_t g_flag[1][96 * FSTR];
enum { CNT_H = 0, CNT_OX = 16, CNT_Y = 32, CNT_NUM = 160 };
__device__ __align__(1024) uint32_t g_cnt[CNT_NUM * 8];
__device__ __align__(128) uint32_t g_epoch;
#define TL(k, i)
#define TLSM(k)

__device__ __forceinline__ uint32_t smem_u32(const void* p) { return (uint32_t)__cvta_generic_to_shared(p); }
__device__ __forceinline__ uint32_t mapa(uint32_t a, uint32_t r) {
    uint32_t o; asm("mapa.shared::cluster.u32 %0, %1, %2;" : "=r"(o) : "r"(a), "r"(r)); return o;
}
__device__ __forceinline__ void mbar_init(uint32_t a, uint32_t cnt) {
    asm volatile("mbarrier.init.shared.b64 [%0], %1;" :: "r"(a), "r"(cnt) : "memory");
}
__device__ __forceinline__ void mbar_expect(uint32_t a, uint32_t bytes) {
    asm volatile("mbarrier.arrive.expect_tx.shared.b64 _, [%0], %1;" :: "r"(a), "r"(bytes) : "memory");
}
__device__ __forceinline__ void mbar_arrive_cluster(uint32_t a) {
    asm volatile("mbarrier.arrive.shared::cluster.b64 _, [%0];" :: "r"(a) : "memory");
}
__device__ __forceinline__ void spin_guard(uint32_t& it) {
    asm volatile("{\n.reg .pred p;\nadd.u32 %0, %0, 1;\nsetp.gt.u32 p, %0, 0x400000;\n@p st.shared.u32 [%0], %0;\n}" : "+r"(it));
}
__device__ __forceinline__ void mbar_wait(uint32_t a, uint32_t par) {
    asm volatile("{\n.reg .pred p;\nWL:\nmbarrier.try_wait.parity.shared::cta.b64 p, [%0], %1;\n@!p bra WL;\n}" :: "r"(a), "r"(par) : "memory");
}
__device__ __forceinline__ void mbar_arrive(uint32_t a) { asm volatile("mbarrier.arrive.shared.b64 _, [%0];" :: "r"(a) : "memory"); }
__device__ __forceinline__ void tma2d(uint32_t dst, const CUtensorMap* m, int c0, int c1, uint32_t bar) {
    asm volatile("cp.async.bulk.tensor.2d.shared::cluster.global.mbarrier::complete_tx::bytes [%0], [%1, {%3, %4}], [%2];"
                 :: "r"(dst), "l"(m), "r"(bar), "r"(c0), "r"(c1) : "memory");
}
__device__ __forceinline__ void tma2d_mc(uint32_t dst, const CUtensorMap* m, int c0, int c1, uint32_t bar, uint16_t mask) {
    asm volatile("cp.async.bulk.tensor.2d.shared::cluster.global.mbarrier::complete_tx::bytes.multicast::cluster [%0], [%1, {%3, %4}], [%2], %5;"
                 :: "r"(dst), "l"(m), "r"(bar), "r"(c0), "r"(c1), "h"(mask) : "memory");
}
__device__ __forceinline__ void bulk_mc(uint32_t dst, const void* src, uint32_t bytes, uint32_t bar, uint16_t mask) {
    asm volatile("cp.async.bulk.shared::cluster.global.mbarrier::complete_tx::bytes.multicast::cluster [%0], [%1], %2, [%3], %4;"
                 :: "r"(dst), "l"(src), "r"(bytes), "r"(bar), "h"(mask) : "memory");
}
__device__ __forceinline__ void bulk_ld(uint32_t dst, const void* src, uint32_t bytes, uint32_t bar) {
    asm volatile("cp.async.bulk.shared::cluster.global.mbarrier::complete_tx::bytes [%0], [%1], %2, [%3];"
                 :: "r"(dst), "l"(src), "r"(bytes), "r"(bar) : "memory");
}
__device__ __forceinline__ uint32_t gtick() { uint64_t c; asm volatile("mov.u64 %0, %%globaltimer;" : "=l"(c)); return (uint32_t)c >> 5; }
__device__ __forceinline__ uint32_t gtick_dep(uint32_t zero) {
    uint32_t c;
    asm volatile("{\n.reg .pred p;\nsetp.eq.u32 p, %1, 0;\nmov.u32 %0, 0;\n@p mov.u32 %0, %%globaltimer_lo;\n}" : "=r"(c) : "r"(zero));
    return c >> 5;
}
__device__ __forceinline__ uint32_t ld_relaxed1(const void* p) {
    uint32_t v; asm volatile("ld.relaxed.gpu.global.u32 %0, [%1];" : "=r"(v) : "l"(p) : "memory"); return v;
}
__device__ __forceinline__ bool any_nan(float a, float b) {
    uint32_t r;
    asm volatile("{\n.reg .pred p;\nsetp.nan.f32 p, %1, %2;\nvote.sync.any.pred p, p, 0xffffffff;\nselp.u32 %0, 1, 0, p;\n}" : "=r"(r) : "f"(a), "f"(b));
    return r;
}
__device__ __forceinline__ bool bar_sync_any_nan(float a, float b) {
    uint32_t r;
    asm volatile("{\n.reg .pred p;\nsetp.nan.f32 p, %1, %2;\nbarrier.cta.red.or.aligned.pred p, 6, 256, p;\nselp.u32 %0, 1, 0, p;\n}"
                 : "=r"(r) : "f"(a), "f"(b) : "memory");
    return r;
}
__device__ __forceinline__ void bar_arrive(int id, int n) { asm volatile("bar.arrive %0, %1;" :: "r"(id), "r"(n) : "memory"); }
__device__ __forceinline__ uint32_t clk() { uint64_t c; asm volatile("mov.u64 %0, %%clock64;" : "=l"(c)); return (uint32_t)c; }
__device__ __forceinline__ void tma2d_store(const CUtensorMap* m, int c0, int c1, uint32_t src) {
    asm volatile("cp.async.bulk.tensor.2d.global.shared::cta.bulk_group [%0, {%1, %2}], [%3];"
                 :: "l"(m), "r"(c0), "r"(c1), "r"(src) : "memory");
}
__device__ __forceinline__ void bar_sync(int id, int n) { asm volatile("bar.sync %0, %1;" :: "r"(id), "r"(n) : "memory"); }
__device__ __forceinline__ void fence_async() { asm volatile("fence.proxy.async.shared::cta;" ::: "memory"); }
__device__ __forceinline__ void cluster_sync() {
    asm volatile("barrier.cluster.arrive.release.aligned;\nbarrier.cluster.wait.acquire.aligned;" ::: "memory");
}
__device__ __forceinline__ void ldsm4(uint32_t* r, uint32_t a) {
    asm volatile("ldmatrix.sync.aligned.m8n8.x4.shared.b16 {%0,%1,%2,%3}, [%4];"
                 : "=r"(r[0]), "=r"(r[1]), "=r"(r[2]), "=r"(r[3]) : "r"(a) : "memory");
}
__device__ __forceinline__ void ldsm4t(uint32_t* r, uint32_t a) {
    asm volatile("ldmatrix.sync.aligned.m8n8.x4.trans.shared.b16 {%0,%1,%2,%3}, [%4];"
                 : "=r"(r[0]), "=r"(r[1]), "=r"(r[2]), "=r"(r[3]) : "r"(a) : "memory");
}
__device__ __forceinline__ void stsm4(uint32_t a, uint32_t r0, uint32_t r1, uint32_t r2, uint32_t r3) {
    asm volatile("stmatrix.sync.aligned.m8n8.x4.shared.b16 [%0], {%1,%2,%3,%4};" :: "r"(a), "r"(r0), "r"(r1), "r"(r2), "r"(r3) : "memory");
}
__device__ __forceinline__ void stsm4f(uint32_t a, const float* v) {
    asm volatile("{\n.reg .b32 a, b, c, d;\nmov.b32 a, %1;\nmov.b32 b, %2;\nmov.b32 c, %3;\nmov.b32 d, %4;\n"
                 "stmatrix.sync.aligned.m8n8.x4.shared.b16 [%0], {a, b, c, d};\n}" :: "r"(a), "f"(v[0]), "f"(v[1]), "f"(v[2]), "f"(v[3]) : "memory");
}
__device__ __forceinline__ void ldsm4f(float* v, uint32_t a) {
    uint32_t r[4];
    ldsm4(r, a);
#pragma unroll
    for (int i = 0; i < 4; i++) v[i] = __uint_as_float(r[i]);
}
__device__ __forceinline__ void stsm4t(uint32_t a, uint32_t r0, uint32_t r1, uint32_t r2, uint32_t r3) {
    asm volatile("stmatrix.sync.aligned.m8n8.x4.trans.shared.b16 [%0], {%1,%2,%3,%4};" :: "r"(a), "r"(r0), "r"(r1), "r"(r2), "r"(r3) : "memory");
}
__device__ __forceinline__ void stsm2(uint32_t a, uint32_t r0, uint32_t r1) {
    asm volatile("stmatrix.sync.aligned.m8n8.x2.shared.b16 [%0], {%1,%2};" :: "r"(a), "r"(r0), "r"(r1) : "memory");
}
__device__ __forceinline__ void stsm2t(uint32_t a, uint32_t r0, uint32_t r1) {
    asm volatile("stmatrix.sync.aligned.m8n8.x2.trans.shared.b16 [%0], {%1,%2};" :: "r"(a), "r"(r0), "r"(r1) : "memory");
}
__device__ __forceinline__ uint32_t movm(uint32_t a) {
    uint32_t d; asm volatile("movmatrix.sync.aligned.m8n8.trans.b16 %0, %1;" : "=r"(d) : "r"(a)); return d;
}
__device__ __forceinline__ void mma16(float* d, uint32_t a0, uint32_t a1, uint32_t a2, uint32_t a3, uint32_t b0, uint32_t b1) {
    asm volatile("mma.sync.aligned.m16n8k16.row.col.f32.bf16.bf16.f32 {%0,%1,%2,%3}, {%4,%5,%6,%7}, {%8,%9}, {%0,%1,%2,%3};"
                 : "+f"(d[0]), "+f"(d[1]), "+f"(d[2]), "+f"(d[3]) : "r"(a0), "r"(a1), "r"(a2), "r"(a3), "r"(b0), "r"(b1));
}
__device__ __forceinline__ void mma8(float* d, uint32_t a0, uint32_t a1, uint32_t b0) {
    asm volatile("mma.sync.aligned.m16n8k8.row.col.f32.bf16.bf16.f32 {%0,%1,%2,%3}, {%4,%5}, {%6}, {%0,%1,%2,%3};"
                 : "+f"(d[0]), "+f"(d[1]), "+f"(d[2]), "+f"(d[3]) : "r"(a0), "r"(a1), "r"(b0));
}
__device__ __forceinline__ uint32_t pack2(float lo, float hi) {
    uint32_t r; asm("cvt.rn.bf16x2.f32 %0, %1, %2;" : "=r"(r) : "f"(hi), "f"(lo)); return r;
}
__device__ __forceinline__ float bf_lo(uint32_t v) { return __uint_as_float(v << 16); }
__device__ __forceinline__ float bf_hi(uint32_t v) { return __uint_as_float(v & 0xFFFF0000u); }
__device__ __forceinline__ float ex2(float x) { float y; asm("ex2.approx.ftz.f32 %0, %1;" : "=f"(y) : "f"(x)); return y; }
__device__ __forceinline__ float rcp(float x) { float y; asm("rcp.approx.ftz.f32 %0, %1;" : "=f"(y) : "f"(x)); return y; }
__device__ __forceinline__ void sts4f(uint32_t a, float x, float y, float z, float w) {
    asm volatile("st.shared.v4.f32 [%0], {%1,%2,%3,%4};" :: "r"(a), "f"(x), "f"(y), "f"(z), "f"(w) : "memory");
}
__device__ __forceinline__ void sts1u(uint32_t a, uint32_t v) { asm volatile("st.shared.u32 [%0], %1;" :: "r"(a), "r"(v) : "memory"); }
__device__ __forceinline__ void sts4u(uint32_t a, uint4 v) {
    asm volatile("st.shared.v4.u32 [%0], {%1,%2,%3,%4};" :: "r"(a), "r"(v.x), "r"(v.y), "r"(v.z), "r"(v.w) : "memory");
}
__device__ __forceinline__ float4 lds4f(uint32_t a) {
    float4 v; asm volatile("ld.shared.v4.f32 {%0,%1,%2,%3}, [%4];" : "=f"(v.x), "=f"(v.y), "=f"(v.z), "=f"(v.w) : "r"(a) : "memory"); return v;
}
__device__ __forceinline__ float2 lds2f(uint32_t a) {
    float2 v; asm volatile("ld.shared.v2.f32 {%0,%1}, [%2];" : "=f"(v.x), "=f"(v.y) : "r"(a) : "memory"); return v;
}
__device__ __forceinline__ uint4 lds4u(uint32_t a) {
    uint4 v; asm volatile("ld.shared.v4.u32 {%0,%1,%2,%3}, [%4];" : "=r"(v.x), "=r"(v.y), "=r"(v.z), "=r"(v.w) : "r"(a) : "memory"); return v;
}
__device__ __forceinline__ uint32_t lds1u(uint32_t a) {
    uint32_t v; asm volatile("ld.shared.u32 %0, [%1];" : "=r"(v) : "r"(a) : "memory"); return v;
}
__device__ __forceinline__ uint2 lds2u(uint32_t a) {
    uint2 v; asm volatile("ld.shared.v2.u32 {%0,%1}, [%2];" : "=r"(v.x), "=r"(v.y) : "r"(a) : "memory"); return v;
}
__device__ __forceinline__ void st_async4(uint32_t a, uint32_t bar, float x, float y, float z, float w) {
    asm volatile("st.async.shared::cluster.mbarrier::complete_tx::bytes.v4.f32 [%0], {%1,%2,%3,%4}, [%5];"
                 :: "r"(a), "f"(x), "f"(y), "f"(z), "f"(w), "r"(bar) : "memory");
}
__device__ __forceinline__ void st_async2(uint32_t a, uint32_t bar, float x, float y) {
    asm volatile("st.async.shared::cluster.mbarrier::complete_tx::bytes.v2.f32 [%0], {%1,%2}, [%3];"
                 :: "r"(a), "f"(x), "f"(y), "r"(bar) : "memory");
}
__device__ __forceinline__ void st_async1f(uint32_t a, uint32_t bar, float x) {
    asm volatile("st.async.shared::cluster.mbarrier::complete_tx::bytes.f32 [%0], %1, [%2];" :: "r"(a), "f"(x), "r"(bar) : "memory");
}
__device__ __forceinline__ void st_async1(uint32_t a, uint32_t bar, uint32_t x) {
    asm volatile("st.async.shared::cluster.mbarrier::complete_tx::bytes.b32 [%0], %1, [%2];" :: "r"(a), "r"(x), "r"(bar) : "memory");
}
__device__ __forceinline__ uint4 ld_relaxed4(const uint4* p) {
    uint4 v;
    asm volatile("ld.relaxed.gpu.global.v4.u32 {%0,%1,%2,%3}, [%4];" : "=r"(v.x), "=r"(v.y), "=r"(v.z), "=r"(v.w) : "l"(p) : "memory");
    return v;
}
__device__ __forceinline__ void st_relaxed4(uint4* p, uint4 v) {
    asm volatile("st.relaxed.gpu.global.v4.u32 [%0], {%1,%2,%3,%4};" :: "l"(p), "r"(v.x), "r"(v.y), "r"(v.z), "r"(v.w) : "memory");
}
__device__ __forceinline__ void count_up(int idx) {
    asm volatile("red.release.gpu.global.add.u32 [%0], 1;" :: "l"(&g_cnt[idx * 8]) : "memory");
}
__device__ __forceinline__ void st_pred1(void* p, uint32_t v, bool on) {
    asm volatile("{\n.reg .pred p;\nsetp.ne.u32 p, %2, 0;\n@p st.relaxed.gpu.global.u32 [%0], %1;\n}" :: "l"(p), "r"(v), "r"((uint32_t)on) : "memory");
}
__device__ __forceinline__ void st_pred4(void* p, uint4 v, bool on) {
    asm volatile("{\n.reg .pred p;\nsetp.ne.u32 p, %5, 0;\n@p st.global.v4.u32 [%0], {%1,%2,%3,%4};\n}"
                 :: "l"(p), "r"(v.x), "r"(v.y), "r"(v.z), "r"(v.w), "r"((uint32_t)on) : "memory");
}
__device__ __forceinline__ void st_relaxed1(void* p, uint32_t v) {
    asm volatile("st.relaxed.gpu.global.u32 [%0], %1;" :: "l"(p), "r"(v) : "memory");
}
__device__ __forceinline__ uint32_t umax4(uint4 v) { return max(max(v.x, v.y), max(v.z, v.w)); }
__device__ __forceinline__ void wg_fence() { asm volatile("wgmma.fence.sync.aligned;" ::: "memory"); }
__device__ __forceinline__ void wg_commit() { asm volatile("wgmma.commit_group.sync.aligned;" ::: "memory"); }
template <int N> __device__ __forceinline__ void wg_wait() { asm volatile("wgmma.wait_group.sync.aligned %0;" :: "n"(N) : "memory"); }
template <int N> __device__ __forceinline__ void reg_fence(float* d) {
#pragma unroll
    for (int i = 0; i < N; i++) asm volatile("" : "+f"(d[i]) :: "memory");
}
#define ACC16(d) "+f"(d[0]), "+f"(d[1]), "+f"(d[2]), "+f"(d[3]), "+f"(d[4]), "+f"(d[5]), "+f"(d[6]), "+f"(d[7]), \
                 "+f"(d[8]), "+f"(d[9]), "+f"(d[10]), "+f"(d[11]), "+f"(d[12]), "+f"(d[13]), "+f"(d[14]), "+f"(d[15])
#define DESC_HI_SW128 "0x40000040"
#define OUT16(d) "=f"(d[0]), "=f"(d[1]), "=f"(d[2]), "=f"(d[3]), "=f"(d[4]), "=f"(d[5]), "=f"(d[6]), "=f"(d[7]), \
                 "=f"(d[8]), "=f"(d[9]), "=f"(d[10]), "=f"(d[11]), "=f"(d[12]), "=f"(d[13]), "=f"(d[14]), "=f"(d[15])
template <int ACCUM, int BOFF>
__device__ __forceinline__ void wg32_rs(float* d, const uint32_t* a, uint64_t dsw) {
    if (ACCUM)
        asm volatile("{\n.reg .b64 db;\nadd.s64 db, %20, %21;\n"
                     "wgmma.mma_async.sync.aligned.m64n32k16.f32.bf16.bf16 {%0,%1,%2,%3,%4,%5,%6,%7,%8,%9,%10,%11,%12,%13,%14,%15}, "
                     "{%16,%17,%18,%19}, db, 1, 1, 1, 0;\n}"
                     : ACC16(d) : "r"(a[0]), "r"(a[1]), "r"(a[2]), "r"(a[3]), "l"(dsw), "n"(BOFF));
    else
        asm volatile("{\n.reg .b64 db;\nadd.s64 db, %20, %21;\n"
                     "wgmma.mma_async.sync.aligned.m64n32k16.f32.bf16.bf16 {%0,%1,%2,%3,%4,%5,%6,%7,%8,%9,%10,%11,%12,%13,%14,%15}, "
                     "{%16,%17,%18,%19}, db, 0, 1, 1, 0;\n}"
                     : OUT16(d) : "r"(a[0]), "r"(a[1]), "r"(a[2]), "r"(a[3]), "l"(dsw), "n"(BOFF));
}
template <int ACCUM, int AOFF, int BOFF>
__device__ __forceinline__ void wg32_ss(float* d, uint64_t dsw) {
    if (ACCUM)
        asm volatile("{\n.reg .b64 da, db;\nadd.s64 da, %16, %17;\nadd.s64 db, %16, %18;\n"
                     "wgmma.mma_async.sync.aligned.m64n32k16.f32.bf16.bf16 {%0,%1,%2,%3,%4,%5,%6,%7,%8,%9,%10,%11,%12,%13,%14,%15}, "
                     "da, db, 1, 1, 1, 1, 0;\n}"
                     : ACC16(d) : "l"(dsw), "n"(AOFF), "n"(BOFF));
    else
        asm volatile("{\n.reg .b64 da, db;\nadd.s64 da, %16, %17;\nadd.s64 db, %16, %18;\n"
                     "wgmma.mma_async.sync.aligned.m64n32k16.f32.bf16.bf16 {%0,%1,%2,%3,%4,%5,%6,%7,%8,%9,%10,%11,%12,%13,%14,%15}, "
                     "da, db, 0, 1, 1, 1, 0;\n}"
                     : OUT16(d) : "l"(dsw), "n"(AOFF), "n"(BOFF));
}
template <int ACCUM, int AOFF, int BOFF>
__device__ __forceinline__ void wg8_ss(float* d, uint64_t dsw, uint64_t dns) {
    if (!ACCUM)
        asm volatile("{\n.reg .b64 da, db;\nadd.s64 da, %4, %6;\nadd.s64 db, %5, %7;\n"
                     "wgmma.mma_async.sync.aligned.m64n8k16.f32.bf16.bf16 {%0,%1,%2,%3}, da, db, 0, 1, 1, 1, 0;\n}"
                     : "=f"(d[0]), "=f"(d[1]), "=f"(d[2]), "=f"(d[3]) : "l"(dsw), "l"(dns), "n"(AOFF), "n"(BOFF));
    else
        asm volatile("{\n.reg .b64 da, db;\nadd.s64 da, %4, %6;\nadd.s64 db, %5, %7;\n"
                     "wgmma.mma_async.sync.aligned.m64n8k16.f32.bf16.bf16 {%0,%1,%2,%3}, da, db, 1, 1, 1, 1, 0;\n}"
                     : "+f"(d[0]), "+f"(d[1]), "+f"(d[2]), "+f"(d[3]) : "l"(dsw), "l"(dns), "n"(AOFF), "n"(BOFF));
}
template <int I0, int I1, class F>
__device__ __forceinline__ void static_for(F&& f) {
    if constexpr (I0 < I1) { f(std::integral_constant<int, I0>{}); static_for<I0 + 1, I1>(f); }
}
template <int I0, int I1, int AOFF, int BOFF>
__device__ __forceinline__ void wg8_chain(float* d, uint64_t dsw, uint64_t dns) {
    wg_fence();
    static_for<I0, I1>([&](auto i) { wg8_ss<i.value != 0, AOFF + i.value * 128, BOFF + i.value * 16>(d, dsw, dns); });
    wg_commit();
}

__device__ __forceinline__ void ln_row(const uint4* v, int row, int lane) {
    float f[32];
#pragma unroll
    for (int j = 0; j < 4; j++) {
        f[j * 8 + 0] = bf_lo(v[j].x); f[j * 8 + 1] = bf_hi(v[j].x); f[j * 8 + 2] = bf_lo(v[j].y); f[j * 8 + 3] = bf_hi(v[j].y);
        f[j * 8 + 4] = bf_lo(v[j].z); f[j * 8 + 5] = bf_hi(v[j].z); f[j * 8 + 6] = bf_lo(v[j].w); f[j * 8 + 7] = bf_hi(v[j].w);
    }
    float s = 0.f;
#pragma unroll
    for (int i = 0; i < 32; i++) s += f[i];
#pragma unroll
    for (int o = 16; o; o >>= 1) s += __shfl_xor_sync(~0u, s, o);
    const float mean = s * (1.f / DM);
    float q = 0.f;
#pragma unroll
    for (int i = 0; i < 32; i++) { f[i] -= mean; q += f[i] * f[i]; }
#pragma unroll
    for (int o = 16; o; o >>= 1) q += __shfl_xor_sync(~0u, q, o);
    const float r = 1.f / sqrtf(q * (1.f / DM) + 1e-5f);
    uint4* dst = reinterpret_cast<uint4*>(g_xn + (size_t)row * DM);
    uint4* dst1 = g_xc + (row >> 5) * 4096 + (lane >> 3) * 256 + (row & 31) * 8 + ((lane & 7) ^ (row & 7));
#pragma unroll
    for (int j = 0; j < 4; j++) {
        const uint4 o = make_uint4(pack2(f[j * 8] * r, f[j * 8 + 1] * r), pack2(f[j * 8 + 2] * r, f[j * 8 + 3] * r),
                                   pack2(f[j * 8 + 4] * r, f[j * 8 + 5] * r), pack2(f[j * 8 + 6] * r, f[j * 8 + 7] * r));
        dst[j * 32 + lane] = o;
        dst1[(j & 1) * 2048 + (j >> 1) * 1024] = o;
    }
}
__device__ __forceinline__ void reset_exchange(const __nv_bfloat16* __restrict__ mem0) {
    const int gi = blockIdx.x * 256 + threadIdx.x;
    const uint4 poison = make_uint4(~0u, ~0u, ~0u, ~0u);
    if (gi < 1024) {
        uint4 m = reinterpret_cast<const uint4*>(mem0)[(gi & 7) * 128 + (gi >> 3)];
        if (m.x == ~0u) m.x = 0x7FFF7FFFu;
        if (m.y == ~0u) m.y = 0x7FFF7FFFu;
        if (m.z == ~0u) m.z = 0x7FFF7FFFu;
        if (m.w == ~0u) m.w = 0x7FFF7FFFu;
        g_xmem[0][gi] = m;
    } else if (gi < 4096) {
        (&g_xmem[0][0])[gi] = poison;
    } else if (gi < 4096 + 16384) {
        (&g_xo[0][0])[gi - 4096] = poison;
    } else if (gi < 4096 + 16384 + 24 * FSTR) {
        reinterpret_cast<uint4*>(&g_flag[0][0])[gi - 4096 - 16384] = poison;
    } else if (gi >= 24576 - CNT_NUM) {
        g_cnt[(24575 - gi) * 8] = 0;
    }
}

#define ONKQ 45
constexpr int ONKV = 128 - 2 * ONKQ;
constexpr uint32_t SB0 = 1024;
constexpr uint32_t C_WS = 0, C_XN = 65536, C_MB = 98304, C_WO = 114688, C_SMEM = 232448;
constexpr uint32_t C_BAR = C_SMEM - 384, C_CAL = C_BAR + 192;
constexpr uint32_t C_SLOTQ = C_WO + ONKQ * 2048, C_QX = C_SLOTQ + 8192, C_KX = C_QX + 4096,
                   C_XSL = C_KX + 4096, C_OL = C_SLOTQ + 4096;
constexpr uint32_t C_SLOTV = C_WO + ONKV * 2048, C_V = C_SLOTV + 8192, C_PL = C_V + 20480, C_SL = C_PL + 4096;
constexpr uint32_t C_DUMP = C_BAR - 512;
static_assert(C_XSL + 5120 <= C_DUMP && C_SL + 2560 <= C_DUMP, "smem overflow");
enum { B_W0 = 0, B_W1, B_W2, B_WS, B_XF0, B_XF1, B_SC, B_P0, B_P1, B_XS, B_OL, B_MF0, B_MF1, B_OF, B_RT0, B_RT1, B_VF, B_MBF, B_GO, B_DUMP, B_NUM };
struct Descs { uint64_t sw[4], ns; };
constexpr uint64_t DSW = 0x4000004000010000ull, DNS = 0x0000001000080000ull;
template <int V> using ic = std::integral_constant<int, V>;
constexpr float SM_SCALE = 0.08838834764831845f * 1.4426950408889634f;

#define TSD(i) do {} while (0)
#define TS_FLUSH(w)
#define TSX(i, c)
#define TS(i)
#define NOFILL 0
#define DLY1 2230
#define DLY2 2490
#define SWAP16 0
#define SSFIRST 1
#define EARLYB 0
#define CANARY ~0u
#define L2POS 10
#define PFX 1
#define LATELOOK 0
#define QK1 10
#define RFPOS 6
#define STPOS 12
#define OTAIL 3
#define DLYS 450
#define DLYB 1
#define VLEAD 4

#define VEARLY 8
#define QSPLIT 20
__device__ __forceinline__ bool elect() {
    uint32_t r;
    asm volatile("{\n.reg .pred p;\nelect.sync _|p, 0xffffffff;\nselp.u32 %0, 1, 0, p;\n}" : "=r"(r));
    return r;
}
__device__ __forceinline__ int uni(int v) { return __shfl_sync(~0u, v, 0); }
__device__ __forceinline__ void calibrate(uint32_t cal, float keep) {
    const uint32_t t0 = gtick();
    uint32_t t, it = 0;
    do { t = gtick(); spin_guard(it); } while (__any_sync(~0u, t == t0));
    const uint32_t c = clk();
    const uint4 p = lds4u(cal);
    const float cpt = 256.f * fminf(fmaxf(__fdividef((float)(c - p.y), (float)((t - p.x) & 0x7FFFFFF)), 16.f), 128.f);
    __syncwarp();
    sts4u(cal, make_uint4(t, c, (uint32_t)(keep > 0.f ? fmaf(keep, (float)p.z - cpt, cpt) : cpt), 0));
}
struct Stamps { uint32_t v[6]; };
__device__ __forceinline__ void load_stamps2(Stamps& t, const uint32_t* f, uint32_t l16, bool on = true) {
    const char* p = reinterpret_cast<const char*>(f) + (l16 >> 2) * FSTR;
    asm volatile("{\n.reg .pred p;\nsetp.ne.u32 p, %7, 0;\nmov.u32 %0, 63;\nmov.u32 %1, 63;\nmov.u32 %2, 63;\nmov.u32 %3, 63;\nmov.u32 %4, 63;\nmov.u32 %5, 63;\n"
                 "@p ld.relaxed.gpu.global.v2.u32 {%0, %1}, [%6];\n@p ld.relaxed.gpu.global.v2.u32 {%2, %3}, [%6 + %8];\n"
                 "@p ld.relaxed.gpu.global.v2.u32 {%4, %5}, [%6 + %9];\n}"
                 : "=&r"(t.v[0]), "=&r"(t.v[1]), "=&r"(t.v[2]), "=&r"(t.v[3]), "=&r"(t.v[4]), "=&r"(t.v[5])
                 : "l"(p), "r"((uint32_t)on), "n"(128 * FSTR), "n"(256 * FSTR) : "memory");
}
template <int N>
__device__ __forceinline__ uint32_t stamps_missing(const uint32_t* v, int s) {
    uint32_t x = 0;
#pragma unroll
    for (int i = 0; i < N; i++) x |= v[i] ^ s;
    return x & 63;
}
template <int N>
__device__ __forceinline__ uint32_t latest_stamp(const uint32_t* v, const uint4 cal) {
    int late = (int)(v[0] - (cal.x << 6));
#pragma unroll
    for (int i = 1; i < N; i++) late = max(late, (int)(v[i] - (cal.x << 6)));
    return cal.y + (((late >> 6) * (int)cal.z) >> 8);
}
__device__ __forceinline__ void wait_clock(uint32_t target, uint32_t range = 65536) {
    while (__any_sync(~0u, target - clk() < range)) {}
}

template <int BYTES>
__device__ __forceinline__ bool incomplete(uint32_t buf, uint32_t l16) {
    uint32_t m = 0;
#pragma unroll 1
    for (int o = 0; o < BYTES; o += 256) m = max(m, umax4(lds4u(buf + o + (l16 & 255))));
    return __any_sync(~0u, m == ~0u);
}
__device__ __forceinline__ void refetch(uint32_t buf, const uint4* src, uint32_t bytes, uint32_t b, int w4, int barid, uint32_t& tries) {
    spin_guard(tries);
    bar_sync(barid, 128);
    if (w4 == 0 && elect()) { mbar_expect(b, bytes); bulk_ld(buf, src, bytes, b); }
    __syncwarp();
    mbar_wait(b, 0);
    bar_sync(barid, 128);
    if (w4 == 0 && elect()) mbar_arrive(b);
    __syncwarp();
}

__device__ __forceinline__ void load_box(const CUtensorMap* tA, const CUtensorMap* tB, int cl, int rank, uint32_t dst, int j, int q, uint32_t b) {
    const bool isb = (q ^ (q >> 1)) & 1;
    tma2d(dst + q * 16384, isb ? tB : tA, cl * 256 + (rank >= 4 ? (rank - 4) * 128 + isb * 64 : rank * 64), (q >> 1) * 512 + j * 128, b);
}

template <bool ISV, int WG>
__device__ __forceinline__ void chain_main(const CUtensorMap* tA, const CUtensorMap* tB, const CUtensorMap* tWo,
                                           const uint32_t sb, const int cl, const int rank, const Descs& D, const uint32_t goal) {
    const int tid = threadIdx.x;
    uint32_t l16 = __shfl_sync(~0u, (tid & 31) * 16, tid & 31);
    int w4 = uni((tid >> 5) & 3);
    const int role = ISV ? 2 : (rank & 1), hh = ISV ? rank - 4 : rank >> 1, head = 2 * cl + hh;
    const uint32_t bar = sb + C_BAR;
    constexpr int ONK = ISV ? ONKV : ONKQ;
    const int ostart = (hh * 128 + role * ONKQ);

    uint32_t wk[24][4], wv[24][4];
    uint32_t a_adr;
    {
        if (WG == 1 && w4 == 0) calibrate(sb + C_CAL, 0.f);
        const int lane = tid & 31, kr = (lane & 7) + ((lane >> 4) << 3);
        a_adr = __shfl_sync(~0u, sb + WG * 32768 + kr * 128 + (((w4 * 2 + ((lane >> 3) & 1)) ^ (kr & 7)) << 4), lane);
#pragma unroll
        for (int j = 0; j < 3; j++) {
            mbar_wait(bar + (B_W0 + j) * 8, 0);
#pragma unroll
            for (int i = 0; i < 8; i++) {
                ldsm4t(wk[j * 8 + i], a_adr + j * 65536 + i * 2048);
                ldsm4t(wv[j * 8 + i], a_adr + j * 65536 + 16384 + i * 2048);
            }
            if (j != 1) {
                bar_sync(6, 256);
                if (j == 0 && tid == 0) TL(1, 6);
                if (WG == 0 && j == 0 && elect()) load_box(tA, tB, cl, rank, sb + C_WS, 3, w4, bar + B_WS * 8);
                if (WG == 0 && j == 2) {
                    if (elect())
                        for (int i = w4; i < ONK; i += 4) tma2d(sb + C_WO + i * 2048, tWo, cl * 64, (ostart + i) * 16, bar + B_OF * 8);
                }
                __syncwarp();
            }
        }
        if (NOFILL) { for (uint32_t o = C_WO + ONK * 2048 + tid * 16; o < C_BAR; o += 4096) sts4u(sb + o, make_uint4(0, 0, 0, 0)); bar_sync(6, 256); }
        if (WG == 1 && w4 == 1) {
            uint32_t v, it = 0;
            do {
                asm volatile("ld.acquire.gpu.global.u32 %0, [%1];" : "=r"(v) : "l"(&g_epoch) : "memory");
                spin_guard(it);
            } while (__any_sync(~0u, (int)(v - goal) < 0));
        }
        if (WG == 1 && w4 == 0) calibrate(sb + C_CAL, 0.f);
        __syncwarp();
        bar_sync(6, 256);
        asm volatile("fence.proxy.async.global;" ::: "memory");
    }

    constexpr uint32_t SLOT = ISV ? C_SLOTV : C_SLOTQ;
    constexpr int WS_A = (SB0 + C_WS + WG * 32768) >> 4, WO_A = (SB0 + C_WO) >> 4, MB_A = (SB0 + C_MB) >> 4;
#define XN_A(ks) (int)(((SB0 + C_XN + WG * 16384) >> 4) + ((ks) >> 2) * 256 + ((ks) & 3) * 2)
    const uint32_t slot = (sb + SLOT + w4 * 512), mbw = sb + C_MB + WG * 8192;
    const uint32_t sb_v = (mapa(sb, 4 + hh));
    const uint32_t sb_x = uni(mapa(sb, 2 * hh + (WG ? 1 : (~w4 & 1))));
    const uint32_t sb_o = (mapa(sb, w4));
    const uint32_t u_off = (ISV ? (head * 128 + w4 * 32) * 16 : (cl * 4 + rank) * 256 + (w4 & 1) * 128);
    const uint32_t v_row = (sb + C_V + (2 * WG + (w4 >> 1)) * 512), v_b = ((w4 & 1) * 64);
    const uint32_t u_flag = (blockIdx.x * FSTR);
    const uint32_t f_half = (w4 & 1) * role * (ONKV * 128), f_sb = uni(mapa(sb, rank + (w4 & 1) * (4 + hh - rank)));
    const uint32_t f_src = uni((ostart + (w4 & 1) * (2 - role) * ONKQ) * 256 + f_half), f_dst = uni(f_sb + C_MB + f_half);
    const uint32_t m_dst = (sb + C_MB + role * 8192), m_bar = (bar + (B_MF0 + role) * 8);
    uint32_t target;
    Stamps st1;
    uint4 cal;
    int s = -1;
    uint32_t pf[4][4];
    float xk[16], xv[16];
    uint4 oxp[4];

    auto send_planes = [&](auto n, uint32_t a, int b, const float* v, bool hold) {
        const uint32_t dump = sb + C_DUMP + (l16 >> 2), to = a + (l16 >> 2), ad = hold ? dump : to;
        const uint32_t mb = hold ? (dump & 0xFF000000u) | (SB0 + C_BAR + B_DUMP * 8) : (to & 0xFF000000u) | (SB0 + C_BAR + b * 8);
#pragma unroll
        for (int i = 0; i < n.value; i++) st_async1f(ad + i * 128, mb, v[i]);
    };
    auto store_ox = [&](int ss) {
        char* orow = reinterpret_cast<char*>(g_ox) + (ss * (32 * HD * 2) + (u_off >> 3) + (l16 >> 6) * (HD * 2) + (l16 & 48));
#pragma unroll
        for (int i = 0; i < 4; i++) st_pred4(orow + i * (8 * HD * 2), oxp[i], ss >= 0);
    };
    auto load_tokens = [&](int seg, int wina, int g) {
        const int khalf = ISV ? 1 - wina : wina;
        if (!NOFILL && elect()) {
            mbar_expect(bar + (B_XF0 + g) * 8, 16384);
            bulk_ld(sb + C_XN + g * 16384, g_xc + (seg * 4 + khalf * 2 + g) * 1024, 16384, bar + (B_XF0 + g) * 8);
        }
        __syncwarp();
    };
    auto prefetch = [&]() {
#pragma unroll
        for (int i = 0; i < 4; i++) ldsm4t(pf[i], a_adr + C_WS + (i & 1) * 16384 + (i >> 1) * 2048);
    };
    constexpr int HA = ISV ? 0 : 1, NK1 = ISV ? 0 : QK1;
    auto products = [&](auto give, auto half, auto init, auto i0, auto i1, const uint64_t d) {
        static_for<i0.value, i1.value>([&](auto i) {
            constexpr int ks = half.value * 16 + i.value, acc = !(init.value && i.value == i0.value);
            if constexpr (ks >= 24) wg32_ss<acc, WS_A + give.value * 1024 + (ks - 24) * 128, XN_A(i.value)>(give.value ? xv : xk, d);
            else if constexpr (give.value) wg32_rs<acc, XN_A(i.value)>(xv, wv[ks], d);
            else wg32_rs<acc, XN_A(i.value)>(xk, wk[ks], d);
        });
    };
    auto stream_a = [&](const uint64_t dk, const uint64_t dv, auto mid) {
        if (NOFILL) { mid(); return; }
        constexpr int F = (WG == 0 && SSFIRST) ? 8 : 0;
        wg_fence();
        products(ic<0>{}, ic<HA>{}, ic<1>{}, ic<F>{}, ic<F + 8>{}, dk);
        products(ic<1>{}, ic<HA>{}, ic<1>{}, ic<F>{}, ic<F + 8>{}, dv);
        products(ic<1>{}, ic<HA>{}, ic<0>{}, ic<8 - F>{}, ic<16 - F>{}, dv);
        mid();
        products(ic<0>{}, ic<HA>{}, ic<0>{}, ic<8 - F>{}, ic<16 - F>{}, dk);
        wg_commit();
    };
    auto token_softmax = [&]() {
        const int hi = w4 - 2, lane = l16 >> 4;
        const uint32_t src = sb + C_XSL + hi * 256 + (l16 & 255) + (l16 >> 8) * 2560;
        const int d0 = 16 * role + 8 * hi + (lane >> 2) - 2 * (lane & 3);
        mbar_wait(bar + B_XS * 8, s & 1);
        float e[10];
        float m = -INFINITY;
#pragma unroll
        for (int i = 0; i < 5; i++) {
            __syncwarp();
            float a[4];
            ldsm4f(a, src + i * 512);
            e[2 * i] = (i == 0 || d0 >= 8 * (i - 1)) ? a[0] + a[2] : -INFINITY;
            e[2 * i + 1] = (i == 0 || d0 > 8 * (i - 1)) ? a[1] + a[3] : -INFINITY;
            m = fmaxf(m, fmaxf(e[2 * i], e[2 * i + 1]));
        }
        m = fmaxf(m, __shfl_xor_sync(~0u, m, 1));
        m = fmaxf(m, __shfl_xor_sync(~0u, m, 2));
        m *= -SM_SCALE;
        float l = 0.f;
#pragma unroll
        for (int i = 0; i < 10; i++) { e[i] = ex2(fmaf(e[i], SM_SCALE, m)); l += e[i]; }
        l += __shfl_xor_sync(~0u, l, 1);
        l += __shfl_xor_sync(~0u, l, 2);
        l = rcp(l);
        const uint32_t pd = sb_v + C_PL + (s & 1) * 2048 + role * 768 + hi * 128 + (l16 >> 2), pb = sb_v + C_BAR + (B_P0 + (s & 1)) * 8;
        st_async1(pd, pb, pack2(e[0] * l, e[1] * l));
        st_async1(pd + 256, pb, pack2(e[2] * l, e[3] * l));
        st_async1(pd + 512, pb, pack2(e[4] * l, e[5] * l));
        if (role) {
            st_async1(pd + 768, pb, pack2(e[6] * l, e[7] * l));
            st_async1(pd + 1024, pb, pack2(e[8] * l, e[9] * l));
        }
        if (hi == 0 && l16 == 0) mbar_expect(bar + B_XS * 8, 3072 + role * 2048);
        __syncwarp();
    };

    auto windows = [&]() {
        asm volatile("" : "+r"(l16), "+r"(w4));
        const uint64_t* const dd = D.sw;
        TS(5);
        if constexpr (WG == 1) {
            TS(6);
            if (ISV) bar_sync(3, 256);
            uint32_t missing;
            stream_a(dd[0], dd[1], [&]() {
                if (ISV) return;
                __syncwarp();
                uint64_t c64;
                asm volatile("mov.u64 %0, %%clock64;" : "=l"(c64));
                const uint32_t zero = c64 >> 63;
                uint4 cz = cal;
                cz.x += zero;
                missing = stamps_missing<6>(st1.v, s + zero);
                target = latest_stamp<6>(st1.v, cz) + DLY1;
                asm volatile("" : "+r"(missing), "+r"(target));
            });
            if (!NOFILL) bar_arrive(7, 256);
            if (ISV) {
                if (!NOFILL) store_ox(s - 1);
                st_relaxed4(reinterpret_cast<uint4*>(reinterpret_cast<char*>(&g_xo[(s + 2) & 3][0]) + (u_off + l16)), make_uint4(~0u, ~0u, ~0u, ~0u));
            }
            auto fetch_o = [&]() {
            if (!ISV && w4 < 2 && s >= 0) {
                const char* src = reinterpret_cast<const char*>(&g_xo[s & 3][0]) + f_src;
                if (__builtin_expect(__any_sync(~0u, missing), 0)) {
                    uint32_t it = 0;
                    do { load_stamps2(st1, g_flag[0], l16); spin_guard(it); } while (__any_sync(~0u, stamps_missing<6>(st1.v, s)));
                    target = latest_stamp<6>(st1.v, lds4u(sb + C_CAL)) + DLY1;
                }
                mbar_wait(bar + B_VF * 8, s & 1);
                TS(10);
                wait_clock(target);
                if (elect()) bulk_ld(f_dst, src, ONKQ * 256 - w4 * (ONKQ * 256 - ONKV * 128), f_sb + C_BAR + B_OF * 8);
                __syncwarp();
                TS(8);
            }
            };
            if (!EARLYB) fetch_o();
            if (!NOFILL) {
                wg_wait<0>();
                reg_fence<16>(xk); reg_fence<16>(xv);
                if (w4 == 3) { bar_sync(2, 128); load_tokens(s + 1, 0, 1); }
                else bar_arrive(2, 128);
            }
            if (EARLYB) fetch_o();
            TS(7);
        } else {
            if (!NOFILL) {
                mbar_wait(bar + B_XF0 * 8, 0);
                bar_sync(7, 256);
            }
            TS(6);
            stream_a(dd[0], dd[1], []() {});
        }
        if constexpr (WG == 0) {
            if (s >= 0) {
                const uint32_t dst = sb_o + C_OL + rank * 512;
                const uint32_t can = sb + C_MB + l16 * 8 + (l16 >> 2), can2 = can + (l16 < (ONK * 2 - 64) * 16 ? 8192 : 0);
                float co[4];
                TS(7);
                uint32_t tries = 0;
                for (;; tries |= 1) {
                    asm volatile("" : "+r"(tries));
                    if (__builtin_expect(tries, 0)) {
                        wg_wait<0>();
                        refetch(sb + C_MB, &g_xo[s & 3][ostart * 16], ONK * 256, bar + B_RT0 * 8, w4, 1, tries);
                    }
                    mbar_wait(bar + B_OF * 8, s & 1);
                    TS(8);
                    wg8_chain<0, 8, WO_A, MB_A>(co, D.sw[0], D.ns);
                    if (__builtin_expect(!__any_sync(~0u, max(max(lds1u(can), lds1u(can + 4096)), lds1u(can2)) == CANARY), 1)) break;
                }
                wg_wait<1>();
                if (l16 == 0) mbar_arrive(bar + B_GO * 8);
                wg8_chain<8, ONK - OTAIL, WO_A, MB_A>(co, D.sw[0], D.ns);
                static_for<ONK - OTAIL, ONK>([&](auto i) { wg8_ss<1, WO_A + i.value * 128, MB_A + i.value * 16>(co, D.sw[0], D.ns); });
                wg_commit();
                wg_wait<1>();
                bar_arrive(5, 256);
                wg_wait<0>();
                reg_fence<4>(co);
                const bool nan = any_nan(co[0], co[1]);
                send_planes(ic<4>{}, dst, B_OL, co, nan);
                if (__builtin_expect(nan, 0)) {
                    while (incomplete<ONK * 256>(sb + C_MB, l16)) {
                        refetch(sb + C_MB, &g_xo[s & 3][ostart * 16], ONK * 256, bar + B_RT0 * 8, w4, 1, tries);
                        co[0] = co[1] = co[2] = co[3] = 0.f;
#pragma unroll 1
                        for (int i = 0; i < ONK; i++) {
                            wg_fence();
                            wg8_ss<1, WO_A, MB_A>(co, DSW + i * 128, DNS + i * 16);
                            wg_commit();
                            wg_wait<0>();
                        }
                        reg_fence<4>(co);
                    }
                    send_planes(ic<4>{}, dst, B_OL, co, false);
                }
                TS(9);
                if (l16 < 48 && w4 == 3) mbar_expect(bar + B_MF0 * 8 + (l16 >> 1), l16 == 32 ? ONK * 256 : 8192);
            } else {
                wg_wait<0>();
                if (l16 == 0) mbar_arrive(bar + B_GO * 8);
                bar_arrive(5, 256);
            }
            if (l16 < 32) mbar_arrive_cluster(mapa(bar + B_MBF * 8, 2 * hh + (l16 >> 4)));
            __syncwarp();
            if (!NOFILL) { reg_fence<16>(xk); reg_fence<16>(xv); }
        } else {
            if (w4 < 2) {
                if (w4 == 1) {
                    mbar_wait(bar + B_GO * 8, (s + 1) & 1);
                    load_tokens(s + 1, 0, 0);
                    if (PFX && ISV && s + 3 < NSEG && elect())
                        asm volatile("cp.async.bulk.prefetch.L2.global [%0], 8192;" :: "l"(g_xc + (s + 3) * 4096 + ((cl & 3) * 2 + hh) * 512) : "memory");
                    __syncwarp();
                } else if (!ISV) {
                    calibrate(sb + C_CAL, 0.75f);
                }
                if (!ISV) st_relaxed1(reinterpret_cast<char*>(&g_xmem[(s + 3) & 3][0]) + (u_off + (l16 >> 2)), ~0u);
            } else if (!NOFILL && s >= 0) {
                if (ISV && w4 == 2 && (s & 3) == 1 && s > 1 && l16 == 0) count_up(CNT_OX + (s >> 2) - 1);
                __syncwarp();
                if (!ISV) token_softmax();
                TSX(9, w4 == 2);
            }
            if (!NOFILL) mbar_wait(bar + B_XF1 * 8, 1);
            bar_sync(5, 256);
        }
        asm volatile("" : "+r"(l16), "+r"(w4));
        TSX(11, w4 == 0 && (WG || ISV));
        constexpr int NR = SWAP16 ? 2 : 4;
        constexpr uint32_t OUT = SWAP16 ? WG * 4096 : 0, IN = SWAP16 ? (WG ^ 1) * 4096 : 0;
        auto give = [&]() {
#pragma unroll
            for (int j = 0; j < NR; j++) {
                if (SWAP16) stsm4(slot + OUT + l16 + j * 2048, pack2(xv[8 * j], xv[8 * j + 1]), pack2(xv[8 * j + 2], xv[8 * j + 3]),
                                  pack2(xv[8 * j + 4], xv[8 * j + 5]), pack2(xv[8 * j + 6], xv[8 * j + 7]));
                else stsm4f(slot + l16 + j * 2048, xv + 4 * j);
            }
        };
        auto take = [&](uint32_t (*r)[4]) {
#pragma unroll
            for (int j = 0; j < NR; j++) ldsm4(r[j], slot + IN + l16 + j * 2048);
        };
        auto store_tokens = [&](const uint32_t (*r)[4]) {
            uint32_t lo[4], hi[4];
#pragma unroll
            for (int j = 0; j < 4; j++) {
                if (SWAP16) {
                    const uint32_t a = r[j >> 1][(j & 1) * 2], b = r[j >> 1][(j & 1) * 2 + 1];
                    lo[j] = pack2(xk[4 * j] + bf_lo(a), xk[4 * j + 1] + bf_hi(a));
                    hi[j] = pack2(xk[4 * j + 2] + bf_lo(b), xk[4 * j + 3] + bf_hi(b));
                } else {
                    lo[j] = pack2(xk[4 * j] + __uint_as_float(r[j % NR][0]), xk[4 * j + 1] + __uint_as_float(r[j % NR][1]));
                    hi[j] = pack2(xk[4 * j + 2] + __uint_as_float(r[j % NR][2]), xk[4 * j + 3] + __uint_as_float(r[j % NR][3]));
                }
            }
            if (!ISV) {
                const uint32_t d = sb + C_QX + WG * 4096 + w4 * 1024 + l16;
                stsm4t(d, lo[0], lo[1], lo[2], lo[3]);
                stsm4t(d + 512, hi[0], hi[1], hi[2], hi[3]);
            } else {
                const uint32_t d = v_row + ((s + 1) & 1) * 10240 + ((l16 & 384) << 4) + ((l16 & 96) << 2) + ((l16 & 112) ^ v_b);
                stsm4(d, lo[0], lo[1], lo[2], lo[3]);
                stsm4(d ^ 32, hi[0], hi[1], hi[2], hi[3]);
            }
        };
        if constexpr (WG == 1) {
            if (!NOFILL) {
                wg_fence();
                products(ic<1>{}, ic<1 - HA>{}, ic<0>{}, ic<0>{}, ic<16>{}, dd[3]);
                products(ic<0>{}, ic<1 - HA>{}, ic<0>{}, ic<0>{}, ic<NK1>{}, dd[2]);
                wg_commit();
                if (ISV) {
                    bar_arrive(7, 256);
                } else {
                    mbar_wait(bar + B_MBF * 8, (s + 1) & 1);
                    bar_sync(7, 256);
                }
                wg_wait<0>();
                reg_fence<16>(xv); reg_fence<16>(xk);
                give();
                bar_arrive(8, 256);
            }
            TS(12);
            if (!ISV && w4 == 0) {
                const uint4* src = &g_xmem[(s + 1) & 3][role * 512];
                if (NOFILL) mbar_wait(bar + B_MBF * 8, (s + 1) & 1);
                TS(3);
                wait_clock(target + DLY2, s >= 0 ? 65536 : 0);
                if (hh) { if (elect()) bulk_mc(m_dst, src, 8192, m_bar, 0x2C); }
                else if (elect()) bulk_mc(m_dst, src, 8192, m_bar, 0x13);
                __syncwarp();
                TS(4);
            }
            prefetch();
            if (!NOFILL) {
                bar_sync(9, 256);
                uint32_t r[NR][4];
                take(r);
                bar_sync(14, 256);
                wg_fence();
                products(ic<0>{}, ic<1 - HA>{}, ic<0>{}, ic<NK1>{}, ic<16>{}, dd[2]);
                wg_commit();
                wg_wait<0>();
                reg_fence<16>(xk);
                TS(13);
                store_tokens(r);
                bar_arrive(10, 256);
                if (w4 != 3) bar_arrive(13, 128);
            }
        } else {
            uint32_t r[NR][4];
            if (!NOFILL) mbar_wait(bar + B_XF0 * 8, 1);
            if (!ISV && w4 < 2 && s >= 0) {
                char* gd = reinterpret_cast<char*>(&g_xmem[(s + 1) & 3][0]) + (u_off + (l16 >> 2));
                const uint32_t src = sb + C_OL + w4 * 256 + l16 + (l16 & 256);
                mbar_wait(bar + B_OL * 8, s & 1);
                TSD(3);
                float a[3][4];
#pragma unroll
                for (int i = 0; i < 3; i++) ldsm4f(a[i], src + i * 1024);
                st_relaxed1(gd, movm(pack2((a[0][0] + a[0][2]) + (a[1][0] + a[1][2]) + (a[2][0] + a[2][2]),
                                           (a[0][1] + a[0][3]) + (a[1][1] + a[1][3]) + (a[2][1] + a[2][3]))));
                TS(11);
                if (w4 == 0 && l16 == 0) mbar_expect(bar + B_OL * 8, 3072);
                __syncwarp();
            }
            if (!NOFILL) {
                bar_sync(7, 256);
                TS(12);
                wg_fence();
                products(ic<1>{}, ic<1 - HA>{}, ic<0>{}, ic<0>{}, ic<16>{}, dd[3]);
                wg_commit();
                products(ic<0>{}, ic<1 - HA>{}, ic<0>{}, ic<0>{}, ic<6>{}, dd[2]);
                wg_commit();
                bar_sync(8, 256);
                take(r);
                wg_wait<1>();
                reg_fence<16>(xv);
                give();
                bar_arrive(9, 256);
                products(ic<0>{}, ic<1 - HA>{}, ic<0>{}, ic<6>{}, ic<16>{}, dd[2]);
                wg_commit();
                bar_arrive(14, 256);
                wg_wait<0>();
                reg_fence<16>(xk);
            }
            TS(13);
            if (!NOFILL) store_tokens(r);
            prefetch();
        }
    };

    if (tid == 0) TL(1, 2);
    if (w4 == 0) load_tokens(0, 1, WG);
    mbar_wait(bar + B_WS * 8, 0);
    if (WG == 1 && !NOFILL) mbar_wait(bar + B_XF1 * 8, 0);
    if (ISV && WG == 0) bar_arrive(3, 256);
    load_stamps2(st1, g_flag[0], l16, false);
    cal = make_uint4(0, 0, 0, 0);
    oxp[0] = oxp[1] = oxp[2] = oxp[3] = make_uint4(0, 0, 0, 0);

#pragma unroll 1
    while (true) {
        windows();
        s++;

        asm volatile("" : "+r"(l16), "+r"(a_adr), "+r"(w4));
        TS_FLUSH(WG);
        TS(0);
        float ck[4], cv[4], dk[4], dv[4];
        uint32_t b[3][4], tries = 0;
        const uint32_t kl = sb + C_KX + ((l16 & 384) << 2) + (l16 & 112);
        auto load_b = [&](auto kp) { ldsm4(b[kp.value % 3], mbw + l16 + ((kp.value & 3) ? (kp.value >> 2) * 3 + (kp.value & 3) - 1 : 12 + (kp.value >> 2)) * 512); };
        auto kpair = [&](auto kp_) {
            constexpr int kp = kp_.value, grp = kp >> 2, ph = kp & 3;
            if constexpr (kp > 0 && kp < 14) load_b(ic<kp + 2>{});
            const uint32_t* bb = b[kp % 3];
            if constexpr (ph != 0) {
                constexpr int q = (grp * 3 + ph - 1) * 2;
                static_for<(ph == 1 ? 0 : ph), ph + 1>([&](auto i) {
                    if constexpr (grp < 3) ldsm4t(pf[i.value], a_adr + C_WS + (i.value & 1) * 16384 + (grp * 2 + 2 + (i.value >> 1)) * 2048);
                });
                __syncwarp();
                mma16(cv, wv[q][0], wv[q][1], wv[q][2], wv[q][3], bb[0], bb[1]);
                mma16(ck, wk[q][0], wk[q][1], wk[q][2], wk[q][3], bb[0], bb[1]);
                mma16(dv, wv[q + 1][0], wv[q + 1][1], wv[q + 1][2], wv[q + 1][3], bb[2], bb[3]);
                mma16(dk, wk[q + 1][0], wk[q + 1][1], wk[q + 1][2], wk[q + 1][3], bb[2], bb[3]);
            } else {
                if constexpr (kp == 0) {
#pragma unroll
                    for (int i = 0; i < 4; i++) ck[i] = cv[i] = dk[i] = dv[i] = 0.f;
                }
                mma16(ck, pf[0][0], pf[0][1], pf[0][2], pf[0][3], bb[0], bb[1]);
                mma16(cv, pf[1][0], pf[1][1], pf[1][2], pf[1][3], bb[0], bb[1]);
                mma16(dk, pf[2][0], pf[2][1], pf[2][2], pf[2][3], bb[2], bb[3]);
                mma16(dv, pf[3][0], pf[3][1], pf[3][2], pf[3][3], bb[2], bb[3]);
            }
        };
        auto hand_over = [&]() {
#pragma unroll
            for (int i = 0; i < 4; i++) { cv[i] += dv[i]; ck[i] += dk[i]; }
            if (ISV) {
                stsm4f(slot + WG * 2048 + l16, cv);
            } else {
                const float *q = WG ? cv : ck, *k = WG ? ck : cv;
                stsm4t(slot + WG * 2048 + l16, pack2(q[0], q[1]), pack2(q[2], q[3]), pack2(k[0], k[1]), pack2(k[2], k[3]));
            }
        };
        auto repair = [&]() {
            bar_sync(6, 256);
            while (incomplete<8192>(mbw, l16)) {
                refetch(mbw, &g_xmem[s & 3][WG * 512], 8192, bar + (B_RT0 + WG) * 8, w4, 1 + WG, tries);
                prefetch();
                static_for<0, 3>(load_b);
                static_for<0, 16>(kpair);
                hand_over();
            }
            bar_sync(6, 256);
        };
        {
            const uint32_t can = mbw + l16 * 8 + (l16 >> 2);
            uint32_t* const flag = &g_flag[0][u_flag + WG + l16];
            for (;; tries |= 1) {
                asm volatile("" : "+r"(tries));
                if (__builtin_expect(tries, 0)) {
                    refetch(mbw, &g_xmem[s & 3][WG * 512], 8192, bar + (B_RT0 + WG) * 8, w4, 1 + WG, tries);
                }
                mbar_wait(bar + (B_MF0 + WG) * 8, s & 1);
                TS(1);
                static_for<0, 3>(load_b);
                const uint32_t c0 = lds1u(can), c1 = lds1u(can + 4096);
                const uint32_t v = ((gtick() - (ISV ? VLEAD : 0)) << 6) | s;
                kpair(ic<0>{});
                const bool early = __any_sync(~0u, max(c0, c1) == CANARY);
                st_pred1(flag, v, w4 * 512 + l16 == 1536 && !early);
                if (__builtin_expect(!early, 1)) break;
            }
            static_for<1, RFPOS>(kpair);
            if (WG == 0 && !NOFILL) bar_sync(10, 256);
            if (WG == 1 && !NOFILL && w4 == 3) {
                bar_sync(13, 128);
                if (s < NSEG - 1) load_tokens(s + 1, 1, 1);
            }
            static_for<RFPOS, 13>(kpair);
        }
        auto finish_projections = [&]() {
            static_for<13, 16>(kpair);
            hand_over();
            TS(2);
            return bar_sync_any_nan(cv[0], cv[1]);
        };
        if constexpr (!ISV) {
            const uint32_t qa = sb + C_SLOTQ + ((l16 >> 1) & 128) + ((l16 & 128) << 3) + (l16 & 112);
            const uint32_t ma = sb + C_SLOTQ + 256 + l16 + (l16 & 256);
            const uint32_t qx = sb + C_QX + l16 + (l16 & 256);
            auto ldsm_sum = [&](uint32_t* r, uint32_t a) {
                uint32_t t[4];
                ldsm4(r, a); ldsm4(t, a + 2048);
#pragma unroll
                for (int i = 0; i < 4; i++) asm("add.rn.bf16x2 %0, %0, %1;" : "+r"(r[i]) : "r"(t[i]));
            };
            auto tile = [&](float* d, const uint32_t (*q)[4], const uint32_t (*k)[4]) {
                d[0] = d[1] = d[2] = d[3] = 0.f;
#pragma unroll
                for (int i = 0; i < 4; i++) mma16(d, q[i][0], q[i][1], q[i][2], q[i][3], k[i >> 1][(i & 1) * 2], k[i >> 1][(i & 1) * 2 + 1]);
            };
            auto send = [&](int ti, const float* d, bool hold) {
                send_planes(ic<4>{}, sb_x + C_XSL + role * 2560 + ti * 512, B_XS, d, hold);
            };
            if constexpr (WG == 0) {
                auto scores = [&](auto again) {
                    bool nan = false;
                    if (w4 < 2) {
                        uint32_t k0[2][4], k1[2][4], q0[4], q1[4];
                        const uint32_t ka = kl + w4 * 256, dst = sb_v + C_SL + role * 1024 + w4 * 512;
                        ldsm4(k0[0], ka); ldsm4(k0[1], ka + 2048);
                        ldsm4(k1[0], ka + 128); ldsm4(k1[1], ka + 128 + 2048);
                        __syncwarp();
                        if (!again.value) nan = finish_projections();
                        TS(3);
                        ldsm_sum(q0, qa); ldsm_sum(q1, qa + 512);
                        float s0[4] = {0.f, 0.f, 0.f, 0.f}, s1[4] = {0.f, 0.f, 0.f, 0.f}, s2[4] = {0.f, 0.f, 0.f, 0.f}, s3[4] = {0.f, 0.f, 0.f, 0.f};
                        mma16(s0, q0[0], q0[1], q0[2], q0[3], k0[0][0], k0[0][1]);
                        mma16(s1, q0[0], q0[1], q0[2], q0[3], k0[1][0], k0[1][1]);
                        mma16(s2, q0[0], q0[1], q0[2], q0[3], k1[0][0], k1[0][1]);
                        mma16(s3, q0[0], q0[1], q0[2], q0[3], k1[1][0], k1[1][1]);
                        mma16(s0, q1[0], q1[1], q1[2], q1[3], k0[0][2], k0[0][3]);
                        mma16(s1, q1[0], q1[1], q1[2], q1[3], k0[1][2], k0[1][3]);
                        mma16(s2, q1[0], q1[1], q1[2], q1[3], k1[0][2], k1[0][3]);
                        mma16(s3, q1[0], q1[1], q1[2], q1[3], k1[1][2], k1[1][3]);
                        const float out[4] = {s0[0] + s1[2], s0[1] + s1[3], s2[0] + s3[2], s2[1] + s3[3]};
                        send_planes(ic<4>{}, dst, B_SC, out, nan);
                        if (!again.value) bar_arrive(12, 256);
                        TS(4);
                    } else if (w4 == 2) {
                        uint32_t q0[4], q1[4], km[2][4], q[4][4];
                        const uint32_t dst = sb_v + C_SL + 2048 + role * 256;
                        if (!again.value) nan = finish_projections();
                        ldsm_sum(q0, qa); ldsm_sum(km[0], ma); ldsm_sum(km[1], ma + 1024); ldsm_sum(q1, qa + 512);
                        __syncwarp();
#pragma unroll
                        for (int i = 0; i < 4; i++) ldsm4(q[i], qx + 256 + i * 1024);
                        float s0[4] = {0.f, 0.f, 0.f, 0.f}, s1[4] = {0.f, 0.f, 0.f, 0.f}, d0[4];
                        mma16(s0, q0[0], q0[1], q0[2], q0[3], km[0][0], km[0][1]);
                        mma16(s1, q0[0], q0[1], q0[2], q0[3], km[1][0], km[1][1]);
                        mma16(s0, q1[0], q1[1], q1[2], q1[3], km[0][2], km[0][3]);
                        mma16(s1, q1[0], q1[1], q1[2], q1[3], km[1][2], km[1][3]);
                        const float out[2] = {s0[0] + s1[2], s0[1] + s1[3]};
                        send_planes(ic<2>{}, dst, B_SC, out, nan);
                        if (!NOFILL) tile(d0, q, km);
                        if (!again.value) bar_sync(12, 256);
                        if (!NOFILL) send(0, d0, nan);
                    } else {
                        if (!again.value) {
                            nan = finish_projections();
                            if (s < NSEG - 1) load_tokens(s + 1, 1, 0);
                        }
                        uint32_t q[4][4], k0[2][4], k1[2][4], km[2][4];
                        float d0[4], d1[4], d2[4];
                        if (!NOFILL) {
#pragma unroll
                            for (int i = 0; i < 4; i++) ldsm4(q[i], qx + i * 1024);
                            ldsm4(k0[0], kl); ldsm4(k0[1], kl + 2048);
                            ldsm4(k1[0], kl + 128); ldsm4(k1[1], kl + 128 + 2048);
                            tile(d1, q, k0); tile(d2, q, k1);
                            ldsm_sum(km[0], ma); ldsm_sum(km[1], ma + 1024);
                            tile(d0, q, km);
                        }
                        if (!again.value) bar_sync(12, 256);
                        if (!NOFILL) { send(0, d0, nan); send(1, d1, nan); send(2, d2, nan); }
                    }
                    return nan;
                };
                if (__builtin_expect(__any_sync(~0u, scores(ic<0>{})), 0)) { repair(); scores(ic<1>{}); }
                if (__builtin_expect(s == NSEG - 1, 0)) break;
            } else {
                const bool nan = finish_projections();
                mbar_wait(bar + B_WS * 8, 0);
                if (!LATELOOK) load_stamps2(st1, g_flag[0], l16, w4 < 2);
                cal = lds4u(sb + C_CAL);
                if (!NOFILL) {
                    uint32_t q[4][4], k0[2][4];
                    float d1[4];
#pragma unroll
                    for (int i = 0; i < 4; i++) ldsm4(q[i], qx + 256 + i * 1024);
                    ldsm4(k0[0], kl + w4 * 128); ldsm4(k0[1], kl + w4 * 128 + 2048);
                    tile(d1, q, k0);
                    mbar_wait(bar + B_XF1 * 8, s == NSEG - 1);
                    bar_sync(12, 256);
                    if (LATELOOK) load_stamps2(st1, g_flag[0], l16, w4 < 2);
                    send(1 + w4, d1, false);
                } else {
                    bar_sync(12, 256);
                }
                if (__builtin_expect(__any_sync(~0u, nan), 0)) { repair(); load_stamps2(st1, g_flag[0], l16, false); cal = lds4u(sb + C_CAL); }
                if (__builtin_expect(s == NSEG - 1, 0)) {
                    asm volatile("" : "+r"(l16));
                    if (w4 >= 2 && !NOFILL) token_softmax();
                    break;
                }
            }
        } else {
            const uint32_t lane_b = sb + C_V + w4 * 512 + ((l16 & 384) << 4) + (l16 & 112);
            auto load_vx = [&](uint32_t (*vx)[4], int ss) {
#pragma unroll
                for (int j = 0; j < 4; j++) ldsm4(vx[j], ((lane_b + (ss & 1) * 10240) ^ (j * 32)) + j * 128);
            };
            auto load_vm = [&](uint32_t* vm, int ss) { ldsm4(vm, sb + C_V + (ss & 1) * 10240 + w4 * 512 + 8192 + (l16 ^ ((l16 >> 2) & 96))); };
            auto token_output = [&](int ss) {
                uint32_t vx[4][4], vm[4];
                const uint32_t pl = sb + C_PL + (ss & 1) * 2048 + l16;
                auto lds_frag = [&](uint32_t a) { uint32_t r[4]; ldsm4(r, a); return make_uint4(r[0], r[1], r[2], r[3]); };
                load_vm(vm, ss);
                load_vx(vx, ss);
                mbar_wait(bar + (B_P0 + (ss & 1)) * 8, (ss >> 1) & 1);
                uint32_t dep = 0;
#pragma unroll
                for (int mh = 1; mh >= 0; mh--) {
                    uint2 pm;
                    asm volatile("ldmatrix.sync.aligned.m8n8.x2.shared.b16 {%0,%1}, [%2];" : "=r"(pm.x), "=r"(pm.y) : "r"(pl + mh * 768 + dep) : "memory");
                    const uint4 p0 = lds_frag(pl + mh * 768 + 256);
                    float o[4][4];
#pragma unroll
                    for (int j = 0; j < 4; j++) { o[j][0] = o[j][1] = o[j][2] = o[j][3] = 0.f; mma8(o[j], pm.x, pm.y, vm[j]); }
#pragma unroll
                    for (int j = 0; j < 4; j++) mma16(o[j], p0.x, p0.y, p0.z, p0.w, vx[j][0], vx[j][1]);
                    if (mh) {
                        const uint4 p1 = lds_frag(pl + 1536);
#pragma unroll
                        for (int j = 0; j < 4; j++) mma16(o[j], p1.x, p1.y, p1.z, p1.w, vx[j][2], vx[j][3]);
                    }
                    oxp[2 * mh] = make_uint4(pack2(o[0][0], o[0][1]), pack2(o[1][0], o[1][1]), pack2(o[2][0], o[2][1]), pack2(o[3][0], o[3][1]));
                    oxp[2 * mh + 1] = make_uint4(pack2(o[0][2], o[0][3]), pack2(o[1][2], o[1][3]), pack2(o[2][2], o[2][3]), pack2(o[3][2], o[3][3]));
                    asm volatile("" : "+r"(oxp[2 * mh].x), "+r"(oxp[2 * mh].y), "+r"(oxp[2 * mh].z), "+r"(oxp[2 * mh].w),
                                 "+r"(oxp[2 * mh + 1].x), "+r"(oxp[2 * mh + 1].y), "+r"(oxp[2 * mh + 1].z), "+r"(oxp[2 * mh + 1].w));
                    dep = oxp[2].x == ~0u ? 16 : 0;
                }
            };
            const uint32_t vd = v_row + (s & 1) * 10240 + 8192 + ((l16 & 96) << 2) + ((l16 & 112) ^ v_b ^ ((l16 & 128) >> 2));
            uint32_t vx[4][4], vm[4];
            if (WG == 0) { load_vx(vx, s); __syncwarp(); }
            if (__builtin_expect(__any_sync(~0u, finish_projections()), 0)) { repair(); if (WG == 0) load_vx(vx, s); }
            float r[4];
            ldsm4f(r, slot + (WG ^ 1) * 2048 + l16);
            stsm2(vd, pack2(ck[0] + r[0], ck[1] + r[1]), pack2(ck[2] + r[2], ck[3] + r[3]));
            TSX(3, WG == 0 && w4 == 0);
            if (WG == 1) {
                bar_arrive(11, 256);
                if (w4 == 3 && l16 < 32) mbar_arrive_cluster(mapa(bar + B_VF * 8, 2 * hh + (l16 >> 4)));
                if (w4 == 2 && s < NSEG - 1) load_tokens(s + 1, 1, 0);
                if (!NOFILL) {
                    token_output(s - 1);
                    if (w4 == 1 && l16 == 0 && s > 0) mbar_expect(bar + (B_P0 + ((s - 1) & 1)) * 8, 2048);
                    mbar_wait(bar + B_XF1 * 8, s == NSEG - 1);
                }
            }
            if (WG == 0) bar_sync(11, 256);
            if (__builtin_expect(s == NSEG - 1, 0)) {
                bar_sync(6, 256);
                if (WG == 1) {
                    if (!NOFILL) {
                        store_ox(s - 1);
                        token_output(s);
                        store_ox(s);
                    }
                    bar_sync(2, 128);
                    if (w4 == 0 && l16 == 0) {
                        if (NOFILL) for (int i = 0; i < 15; i++) count_up(CNT_OX + i);
                        count_up(CNT_OX + 15);
                    }
                    __syncwarp();
                }
                mbar_wait(bar + B_SC * 8, s & 1);
                break;
            }
            if constexpr (WG == 0) {
                load_vm(vm, s);
                const uint32_t oo = u_off + ((l16 & 48) << 3) + ((l16 >> 2) & 112);
                char* dst = reinterpret_cast<char*>(&g_xo[s & 3][0]) + oo;
                mbar_wait(bar + B_SC * 8, s & 1);
                TS(4);
                float a0[4], b0[4], a1[4], b1[4], a2[4];
                ldsm4f(a0, sb + C_SL + l16); ldsm4f(b0, sb + C_SL + 1024 + l16);
                ldsm4f(a1, sb + C_SL + 512 + l16); ldsm4f(b1, sb + C_SL + 1536 + l16);
                ldsm4f(a2, sb + C_SL + 2048 + l16);
                const float e[10] = {a0[0] + b0[0], a0[1] + b0[1], a0[2] + b0[2], a0[3] + b0[3], a1[0] + b1[0], a1[1] + b1[1], a1[2] + b1[2], a1[3] + b1[3],
                                     a2[0] + a2[2], a2[1] + a2[3]};
                float m = fmaxf(fmaxf(fmaxf(e[0], e[1]), fmaxf(e[2], e[3])), fmaxf(fmaxf(e[4], e[5]), fmaxf(e[6], e[7])));
                m = fmaxf(m, fmaxf(e[8], e[9]));
                m = fmaxf(fmaxf(m, __shfl_xor_sync(~0u, m, 1)), fmaxf(__shfl_xor_sync(~0u, m, 2), __shfl_xor_sync(~0u, m, 3)));
                m *= -SM_SCALE;
                float x[10];
#pragma unroll
                for (int i = 0; i < 10; i++) x[i] = ex2(fmaf(e[i], SM_SCALE, m));
                float o[4][4];
                const uint32_t p0 = pack2(x[0], x[1]), p1 = pack2(x[2], x[3]), j0 = __float_as_uint(x[1]), j1 = __float_as_uint(x[3]);
#pragma unroll
                for (int j = 0; j < 4; j++) { o[j][0] = o[j][1] = o[j][2] = o[j][3] = 0.f; mma16(o[j], p0, j0, p1, j1, vx[j][0], vx[j][1]); }
                const uint32_t p2 = pack2(x[4], x[5]), p3 = pack2(x[6], x[7]), j2 = __float_as_uint(x[5]), j3 = __float_as_uint(x[7]);
#pragma unroll
                for (int j = 0; j < 4; j++) mma16(o[j], p2, j2, p3, j3, vx[j][2], vx[j][3]);
                const uint32_t p4 = pack2(x[8], x[9]), j4 = __float_as_uint(x[9]);
                float l = (((x[0] + x[1]) + (x[2] + x[3])) + ((x[4] + x[5]) + (x[6] + x[7]))) + (x[8] + x[9]);
                l = (l + __shfl_xor_sync(~0u, l, 1)) + (__shfl_xor_sync(~0u, l, 2) + __shfl_xor_sync(~0u, l, 3));
#pragma unroll
                for (int j = 0; j < 4; j++) mma8(o[j], p4, j4, vm[j]);
                l = rcp(l);
                st_relaxed4(reinterpret_cast<uint4*>(dst), make_uint4(pack2(o[0][0] * l, o[0][1] * l), pack2(o[1][0] * l, o[1][1] * l),
                                                                      pack2(o[2][0] * l, o[2][1] * l), pack2(o[3][0] * l, o[3][1] * l)));
                bar_arrive(3, 256);
                if (w4 == 0 && l16 == 0) mbar_expect(bar + B_SC * 8, 2560);
            }
        }
    }
}

__global__ void __cluster_dims__(6, 1, 1) __launch_bounds__(256, 1)
chain_kernel(const __grid_constant__ CUtensorMap tq, const __grid_constant__ CUtensorMap tk, const __grid_constant__ CUtensorMap tv,
             const __grid_constant__ CUtensorMap two, const __grid_constant__ Descs D, const __grid_constant__ Descs DV,
             const __nv_bfloat16* __restrict__ x, const __nv_bfloat16* __restrict__ mem0) {
    extern __shared__ __align__(1024) uint8_t smem[];
    const uint32_t sb = smem_u32(smem);
    const int rank = blockIdx.x % 6, cl = blockIdx.x / 6, role = rank >= 4 ? 2 : rank & 1;
    const int tid = threadIdx.x, lane = tid & 31, gw = blockIdx.x * 8 + uni(tid >> 5);
    const CUtensorMap *tA = role == 2 ? &tv : &tq, *tB = role == 2 ? &tv : &tk;
    uint4 cur[4], nxt[4];
#pragma unroll
    for (int j = 0; j < 4; j++) {
        cur[j] = reinterpret_cast<const uint4*>(x)[gw * 128 + j * 32 + lane];
        nxt[j] = reinterpret_cast<const uint4*>(x)[(gw + 768) * 128 + j * 32 + lane];
    }
    if (gw < 512 && lane < 16) asm volatile("prefetch.global.L2 [%0];" :: "l"(x + (gw + 1536) * DM + lane * 64));
    if ((gw & 7) == 0) {
        if (tid == 0) { TL(1, 0); TLSM(1); }
        if ((sb & 0xFFFFFF) != SB0 || mapa(sb, 5) != (SB0 | 0x5000000u)) sts1u(1, 0);
        const uint32_t b = sb + C_BAR + lane * 8;
        uint32_t tx = 0;
        if (lane <= B_WS) tx = 65536;
        if (lane == B_MF0 || lane == B_MF1) tx = 8192;
        if (lane == B_OF) tx = (role == 2 ? ONKV : ONKQ) * (256 + 2048);
        if (lane == B_SC) tx = 2560;
        if (lane == B_P0 || lane == B_P1) tx = 2048;
        if (lane == B_XS || lane == B_OL) tx = (lane == B_XS && role) ? 5120 : 3072;
        if (lane < B_NUM) mbar_init(b, lane == B_MBF ? 12 : (lane == B_GO ? 4 : 1));
        if (tx) mbar_expect(b, tx);
        asm volatile("fence.mbarrier_init.release.cluster;" ::: "memory");
        fence_async();
        __syncwarp();
#pragma unroll 1
        for (int i = 0; i < 12; i++)
            if (elect()) load_box(tA, tB, cl, rank, sb + (i >> 2) * 65536, i >> 2, i & 3, sb + C_BAR + (i >> 2) * 8);
    }
    __syncwarp();
    asm volatile("barrier.cluster.arrive.release.aligned;" ::: "memory");
    reset_exchange(mem0);
#pragma unroll 1
    for (int row = gw; row < SEQ; row += 768) {
        uint4 v[4];
#pragma unroll
        for (int j = 0; j < 4; j++) {
            v[j] = cur[j]; cur[j] = nxt[j];
            if (row + 1536 < SEQ) nxt[j] = reinterpret_cast<const uint4*>(x)[(row + 1536) * 128 + j * 32 + lane];
        }
        ln_row(v, row, lane);
    }
    if (tid == 0) TL(1, 5);
    __syncthreads();
    uint32_t goal = 0;
    if (tid == 160) {
        __threadfence();
        goal = (atomicAdd(&g_epoch, 1u) / 96 + 1) * 96;
        asm volatile("griddepcontrol.launch_dependents;" ::: "memory");
        TL(1, 4);
    }
    __syncwarp();
    asm volatile("barrier.cluster.wait.acquire.aligned;" ::: "memory");
    goal = uni(goal);
    const int wg = uni(threadIdx.x >> 7);
    if (role == 2) {
        if (wg == 0) chain_main<true, 0>(&tv, &tv, &two, sb, cl, rank, DV, goal);
        else chain_main<true, 1>(&tv, &tv, &two, sb, cl, rank, DV, goal);
    } else {
        if (wg == 0) chain_main<false, 0>(&tq, &tk, &two, sb, cl, rank, D, goal);
        else chain_main<false, 1>(&tq, &tk, &two, sb, cl, rank, D, goal);
    }
    __syncwarp();
    cluster_sync();
    if (threadIdx.x == 0) TL(1, 1);
}

__device__ __forceinline__ void wg256(float* d, uint32_t da, uint32_t db, uint32_t accum) {
    asm volatile("{\n.reg .b64 da, db;\n.reg .pred p;\nsetp.ne.u32 p, %130, 0;\nmov.b64 da, {%128, " DESC_HI_SW128 "};\nmov.b64 db, {%129, " DESC_HI_SW128 "};\n"
                 "wgmma.mma_async.sync.aligned.m64n256k16.f32.bf16.bf16 {"
                 "%0,%1,%2,%3,%4,%5,%6,%7,%8,%9,%10,%11,%12,%13,%14,%15,%16,%17,%18,%19,%20,%21,%22,%23,%24,%25,%26,%27,%28,%29,%30,%31,"
                 "%32,%33,%34,%35,%36,%37,%38,%39,%40,%41,%42,%43,%44,%45,%46,%47,%48,%49,%50,%51,%52,%53,%54,%55,%56,%57,%58,%59,%60,%61,%62,%63,"
                 "%64,%65,%66,%67,%68,%69,%70,%71,%72,%73,%74,%75,%76,%77,%78,%79,%80,%81,%82,%83,%84,%85,%86,%87,%88,%89,%90,%91,%92,%93,%94,%95,"
                 "%96,%97,%98,%99,%100,%101,%102,%103,%104,%105,%106,%107,%108,%109,%110,%111,%112,%113,%114,%115,%116,%117,%118,%119,%120,%121,%122,%123,%124,%125,%126,%127"
                 "}, da, db, p, 1, 1, 0, 1;\n}"
                 : ACC16(d), ACC16((d + 16)), ACC16((d + 32)), ACC16((d + 48)), ACC16((d + 64)), ACC16((d + 80)), ACC16((d + 96)), ACC16((d + 112))
                 : "r"(da), "r"(db), "r"(accum));
}
__device__ __forceinline__ void wg128(float* d, uint32_t da, uint32_t db, uint32_t accum) {
    asm volatile("{\n.reg .b64 da, db;\n.reg .pred p;\nsetp.ne.u32 p, %66, 0;\nmov.b64 da, {%64, " DESC_HI_SW128 "};\nmov.b64 db, {%65, " DESC_HI_SW128 "};\n"
                 "wgmma.mma_async.sync.aligned.m64n128k16.f32.bf16.bf16 {"
                 "%0,%1,%2,%3,%4,%5,%6,%7,%8,%9,%10,%11,%12,%13,%14,%15,%16,%17,%18,%19,%20,%21,%22,%23,%24,%25,%26,%27,%28,%29,%30,%31,"
                 "%32,%33,%34,%35,%36,%37,%38,%39,%40,%41,%42,%43,%44,%45,%46,%47,%48,%49,%50,%51,%52,%53,%54,%55,%56,%57,%58,%59,%60,%61,%62,%63"
                 "}, da, db, p, 1, 1, 0, 1;\n}"
                 : ACC16(d), ACC16((d + 16)), ACC16((d + 32)), ACC16((d + 48))
                 : "r"(da), "r"(db), "r"(accum));
}
__device__ __forceinline__ float sigmoidf_(float v) { return rcp(1.f + ex2(-1.4426950408889634f * v)); }
__device__ __forceinline__ void wait_count(int idx, uint32_t n) {
    uint32_t v, it = 0;
    while (true) {
        asm volatile("ld.acquire.gpu.global.u32 %0, [%1];" : "=r"(v) : "l"(&g_cnt[idx * 8]) : "memory");
        if (v >= n) break;
        __nanosleep(100);
        spin_guard(it);
    }
    asm volatile("fence.proxy.async.global;" ::: "memory");
}

constexpr int G_STAGES = 4, G_PAIRS = 18;
constexpr uint32_t G_STAGE = 49152, G_EPI = G_STAGES * G_STAGE, G_BAR = G_EPI + 32768, G_SMEM = G_BAR + 256;
__device__ __forceinline__ int glu_job(int p, int j) {
    if (j < 12) return j * G_PAIRS + p;
    if (p < 14) return j == 12 ? 224 + p : (j == 13 ? 242 + p : -1);
    return j < 14 ? 216 + (j - 12) * 4 + (p - 14) : (j == 14 ? 224 + p : -1);
}

__global__ void __cluster_dims__(2, 1, 1) __launch_bounds__(384, 1)
glu_kernel(const __grid_constant__ CUtensorMap tXn, const __grid_constant__ CUtensorMap tG, const __grid_constant__ CUtensorMap tU,
           const __grid_constant__ CUtensorMap tHst, const __grid_constant__ CUtensorMap tHld, const __grid_constant__ CUtensorMap tD,
           const __grid_constant__ CUtensorMap tYst) {
    extern __shared__ __align__(1024) uint8_t smem[];
    const uint32_t sb = smem_u32(smem);
    const uint32_t full = sb + G_BAR, empty = full + 64;
    const int tid = threadIdx.x, lane = tid & 31;
    const int warp = uni(tid >> 5), wg = warp >> 2;
    const int rank = blockIdx.x & 1, pair = blockIdx.x >> 1;
    asm volatile("griddepcontrol.launch_dependents;" ::: "memory");
    if (tid == 0) {
        TL(2, 0); TLSM(2);
        for (int i = 0; i < G_STAGES; i++) { mbar_init(full + i * 8, 1); mbar_init(empty + i * 8, 16); }
        asm volatile("fence.mbarrier_init.release.cluster;" ::: "memory");
        fence_async();
    }
    __syncthreads();
    cluster_sync();
    if (wg == 0) {
        asm volatile("setmaxnreg.dec.sync.aligned.u32 40;");
        if (warp == 0) {
            if (lane == 0) {
                uint32_t st = 0, ph = 1;
                asm volatile("fence.acq_rel.gpu;\nfence.proxy.async.global;" ::: "memory");
                for (int j = 0, job; (job = glu_job(pair, j)) >= 0; j++) {
                    const bool dn = job >= 224;
                    const int mp = dn ? (job - 224) >> 2 : job / 28, nt = dn ? job & 3 : job % 28, rb = mp * 2 + rank;
                    const CUtensorMap* tA = dn ? &tHld : &tXn;
                    const CUtensorMap* tB = dn ? &tD : (rank ? &tU : &tG);
                    const int bcol = dn ? nt * 256 + rank * 128 : nt * 128, nkb = dn ? FF / 64 : DM / 64;
                    if (j == 12) TL(2, 2);
                    if (dn) wait_count(CNT_H + rb, 56);
                    for (int kb = 0; kb < nkb; kb++) {
                        mbar_wait(empty + st * 8, ph);
                        const uint32_t base = sb + st * G_STAGE;
                        mbar_expect(full + st * 8, G_STAGE);
                        tma2d(base, tA, kb * 64, rb * 128, full + st * 8);
                        tma2d_mc(base + 16384 + rank * 16384, tB, bcol, kb * 64, full + st * 8, 3);
                        tma2d_mc(base + 16384 + rank * 16384 + 8192, tB, bcol + 64, kb * 64, full + st * 8, 3);
                        if (++st == G_STAGES) { st = 0; ph ^= 1; }
                    }
                }
            }
        } else if (warp < 3) {
            const int cw = warp - 1;
            const uint32_t epi = sb + G_EPI + cw * 16384;
            bar_arrive(3 + cw, 160);
            for (int j = 0, job; (job = glu_job(pair, j)) >= 0; j++) {
                const bool dn = job >= 224;
                const int mp = dn ? (job - 224) >> 2 : job / 28, nt = dn ? job & 3 : job % 28, rb = mp * 2 + rank;
                for (int hp = 0; hp <= (int)dn; hp++) {
                    bar_sync(1 + cw, 160);
                    if (lane == 0) {
                        const int col = dn ? nt * 256 + hp * 128 : nt * 128;
                        tma2d_store(dn ? &tYst : &tHst, col, rb * 128 + cw * 64, epi);
                        tma2d_store(dn ? &tYst : &tHst, col + 64, rb * 128 + cw * 64, epi + 8192);
                        asm volatile("cp.async.bulk.commit_group;\ncp.async.bulk.wait_group.read 0;" ::: "memory");
                    }
                    __syncwarp();
                    bar_arrive(3 + cw, 160);
                    if (lane == 0) {
                        asm volatile("cp.async.bulk.wait_group 0;\nfence.proxy.async.global;" ::: "memory");
                        count_up(dn ? CNT_Y + rb * 8 + nt * 2 + hp : CNT_H + rb);
                    }
                    __syncwarp();
                }
            }
        }
        cluster_sync();
    } else {
        asm volatile("setmaxnreg.inc.sync.aligned.u32 232;");
        const int cw = wg - 1, w4 = warp & 3;
        const uint32_t empty_dst = mapa(empty, lane & 1);
        const int er = w4 * 16 + (lane & 15), ec = lane >> 4;
        const uint32_t epi = sb + G_EPI + cw * 16384 + er * 128;
        uint32_t st = 0, ph = 0;
        float acc[128];
        auto put = [&](const uint32_t* o) {
            bar_sync(3 + cw, 160);
#pragma unroll
            for (int q = 0; q < 8; q++) stsm4(epi + (q >> 2) * 8192 + (((2 * (q & 3) + ec) ^ (er & 7)) << 4), o[q * 4], o[q * 4 + 1], o[q * 4 + 2], o[q * 4 + 3]);
            fence_async();
            bar_arrive(1 + cw, 160);
        };
        for (int j = 0, job; (job = glu_job(pair, j)) >= 0; j++) {
            const bool dn = job >= 224;
            const int nkb = dn ? FF / 64 : DM / 64;
            uint32_t prev = 0;
#pragma unroll 1
            for (int kb = 0; kb < nkb; kb++) {
                mbar_wait(full + st * 8, ph);
                const uint32_t base = sb + st * G_STAGE;
                const uint32_t da = (((base + cw * 8192) & 0x3FFFF) >> 4) | (1u << 16);
                const uint32_t db = (((base + 16384) & 0x3FFFF) >> 4) | (512u << 16);
                wg_fence();
#pragma unroll
                for (int k = 0; k < 4; k++) wg256(acc, da + k * 2, db + k * 128, (kb | k) != 0);
                wg_commit();
                if (kb > 0) {
                    wg_wait<1>();
                    if (lane < 2) mbar_arrive_cluster(empty_dst + prev * 8);
                }
                prev = st;
                if (++st == G_STAGES) { st = 0; ph ^= 1; }
            }
            wg_wait<0>();
            reg_fence<128>(acc);
            if (lane < 2) mbar_arrive_cluster(empty_dst + prev * 8);
            uint32_t o[32];
            if (!dn) {
#pragma unroll
                for (int i = 0; i < 32; i++) o[i] = pack2(sigmoidf_(acc[2 * i]) * acc[64 + 2 * i], sigmoidf_(acc[2 * i + 1]) * acc[65 + 2 * i]);
                put(o);
            } else {
#pragma unroll
                for (int hp = 0; hp < 2; hp++) {
#pragma unroll
                    for (int i = 0; i < 32; i++) {
                        const float a = acc[hp * 64 + 2 * i], b = acc[hp * 64 + 2 * i + 1];
                        o[i] = pack2(sigmoidf_(a) * a, sigmoidf_(b) * b);
                    }
                    put(o);
                }
            }
        }
        bar_sync(3 + cw, 160);
        if (tid == 128) TL(2, 1);
        cluster_sync();
    }
}

constexpr int O_STAGES = 7;
constexpr uint32_t O_STAGE = 32768, O_BAR = O_STAGES * O_STAGE, O_SMEM = O_BAR + 256;

__global__ void __cluster_dims__(2, 1, 1) __launch_bounds__(384, 1)
out_kernel(const __grid_constant__ CUtensorMap tOx, const __grid_constant__ CUtensorMap tWo, const __grid_constant__ CUtensorMap tX,
           const __grid_constant__ CUtensorMap tY, const __grid_constant__ CUtensorMap tOut) {
    extern __shared__ __align__(1024) uint8_t smem[];
    const uint32_t sb = smem_u32(smem);
    const uint32_t full = sb + O_BAR, empty = full + 64;
    const int tid = threadIdx.x, lane = tid & 31;
    const int warp = uni(tid >> 5), wg = warp >> 2;
    const int rank = blockIdx.x & 1, nt = (blockIdx.x >> 1) & 7, rb = (blockIdx.x >> 4) * 2 + rank;
    constexpr int NKB = HD / 64;
    if (tid == 0) {
        TL(3, 0); TLSM(3);
        for (int i = 0; i < O_STAGES; i++) { mbar_init(full + i * 8, 1); mbar_init(empty + i * 8, 16); }
        asm volatile("fence.mbarrier_init.release.cluster;" ::: "memory");
        fence_async();
    }
    __syncthreads();
    cluster_sync();
    if (wg == 0) {
        if (tid == 0) {
            uint32_t st = 0, ph = 1;
            for (int kb = 0; kb < O_STAGES; kb++) {
                mbar_expect(full + kb * 8, O_STAGE);
                tma2d_mc(sb + kb * O_STAGE + 16384 + rank * 8192, &tWo, nt * 128 + rank * 64, kb * 64, full + kb * 8, 3);
            }
            wait_count(CNT_OX + rb, 32);
            TL(3, 2);
            for (int kb = 0; kb < NKB + 2; kb++) {
                const uint32_t base = sb + st * O_STAGE;
                if (kb >= O_STAGES) {
                    mbar_wait(empty + st * 8, ph);
                    mbar_expect(full + st * 8, O_STAGE);
                }
                if (kb < NKB) {
                    tma2d(base, &tOx, kb * 64, rb * 128, full + st * 8);
                    if (kb >= O_STAGES) tma2d_mc(base + 16384 + rank * 8192, &tWo, nt * 128 + rank * 64, kb * 64, full + st * 8, 3);
                } else {
                    if (kb == NKB) wait_count(CNT_Y + rb * 8 + nt, 2);
                    tma2d(base, &tX, nt * 128 + (kb - NKB) * 64, rb * 128, full + st * 8);
                    tma2d(base + 16384, &tY, nt * 128 + (kb - NKB) * 64, rb * 128, full + st * 8);
                }
                if (++st == O_STAGES) { st = 0; ph ^= 1; }
            }
        }
        __syncwarp();
    } else {
        const int cw = wg - 1, w4 = warp & 3;
        const uint32_t empty_dst = mapa(empty, lane & 1);
        const int er = cw * 64 + w4 * 16 + (lane & 15), ec = lane >> 4;
        uint32_t st = 0, ph = 0, prev = 0;
        float acc[64];
#pragma unroll 1
        for (int kb = 0; kb < NKB; kb++) {
            mbar_wait(full + st * 8, ph);
            const uint32_t base = sb + st * O_STAGE;
            const uint32_t da = (((base + cw * 8192) & 0x3FFFF) >> 4) | (1u << 16);
            const uint32_t db = (((base + 16384) & 0x3FFFF) >> 4) | (512u << 16);
            wg_fence();
#pragma unroll
            for (int k = 0; k < 4; k++) wg128(acc, da + k * 2, db + k * 128, (kb | k) != 0);
            wg_commit();
            if (kb > 0) {
                wg_wait<1>();
                if (lane < 2) mbar_arrive_cluster(empty_dst + prev * 8);
            }
            prev = st;
            if (++st == O_STAGES) { st = 0; ph ^= 1; }
        }
        wg_wait<0>();
        reg_fence<64>(acc);
#pragma unroll
        for (int bx = 0; bx < 2; bx++) {
            mbar_wait(full + st * 8, ph);
            const uint32_t base = sb + st * O_STAGE;
#pragma unroll
            for (int j = 0; j < 4; j++) {
                uint32_t xv[4], yv[4];
                const uint32_t ad = base + er * 128 + (((2 * j + ec) ^ (er & 7)) << 4);
                ldsm4(xv, ad); ldsm4(yv, ad + 16384);
                const float* a = acc + bx * 32 + j * 8;
#pragma unroll
                for (int i = 0; i < 4; i++)
                    xv[i] = pack2(fmaf(a[2 * i], bf_lo(yv[i]), bf_lo(xv[i])), fmaf(a[2 * i + 1], bf_hi(yv[i]), bf_hi(xv[i])));
                stsm4(ad, xv[0], xv[1], xv[2], xv[3]);
            }
            fence_async();
            bar_sync(1 + cw, 128);
            if ((tid & 127) == 0) {
                tma2d_store(&tOut, nt * 128 + bx * 64, rb * 128 + cw * 64, base + cw * 8192);
                asm volatile("cp.async.bulk.commit_group;" ::: "memory");
            }
            if (++st == O_STAGES) { st = 0; ph ^= 1; }
        }
        if ((tid & 127) == 0) asm volatile("cp.async.bulk.wait_group 0;" ::: "memory");
        if (tid == 128) TL(3, 1);
        __syncwarp();
    }
    cluster_sync();
}

typedef CUresult (*EncodeFn)(CUtensorMap*, CUtensorMapDataType, cuuint32_t, void*, const cuuint64_t*, const cuuint64_t*, const cuuint32_t*,
                             const cuuint32_t*, CUtensorMapInterleave, CUtensorMapSwizzle, CUtensorMapL2promotion, CUtensorMapFloatOOBfill);

CUtensorMap make_map(EncodeFn enc, const void* p, int rows, int cols, int box_rows) {
    CUtensorMap m;
    cuuint64_t dims[2] = {(cuuint64_t)cols, (cuuint64_t)rows}, strides[1] = {(cuuint64_t)cols * 2};
    cuuint32_t box[2] = {64, (cuuint32_t)box_rows}, es[2] = {1, 1};
    enc(&m, CU_TENSOR_MAP_DATA_TYPE_BFLOAT16, 2, const_cast<void*>(p), dims, strides, box, es, CU_TENSOR_MAP_INTERLEAVE_NONE,
        CU_TENSOR_MAP_SWIZZLE_128B, CU_TENSOR_MAP_L2_PROMOTION_L2_128B, CU_TENSOR_MAP_FLOAT_OOB_FILL_NONE);
    return m;
}

}

#define PDL 7
extern "C" void kernel_launch(void* const* d_in, const int* in_sizes, int n_in, void* d_out, int out_size) {
    const __nv_bfloat16* x = (const __nv_bfloat16*)d_in[0];
    const __nv_bfloat16* mem0 = (const __nv_bfloat16*)d_in[1];
    void* fn = nullptr;
    cudaDriverEntryPointQueryResult qr;
    cudaGetDriverEntryPoint("cuTensorMapEncodeTiled", &fn, cudaEnableDefault, &qr);
    EncodeFn enc = (EncodeFn)fn;
    void *xn, *ox, *h, *y;
    cudaGetSymbolAddress(&xn, g_xn); cudaGetSymbolAddress(&ox, g_ox); cudaGetSymbolAddress(&h, g_h); cudaGetSymbolAddress(&y, g_y);

    const CUtensorMap tq = make_map(enc, d_in[2], DM, HD, 128), tk = make_map(enc, d_in[3], DM, HD, 128), tv = make_map(enc, d_in[4], DM, HD, 128);
    const CUtensorMap two16 = make_map(enc, d_in[5], HD, DM, 16);
    const CUtensorMap txn128 = make_map(enc, xn, SEQ, DM, 128), tg = make_map(enc, d_in[8], DM, FF, 64), tu = make_map(enc, d_in[9], DM, FF, 64);
    const CUtensorMap th64 = make_map(enc, h, SEQ, FF, 64), th128 = make_map(enc, h, SEQ, FF, 128), td = make_map(enc, d_in[10], FF, DM, 64);
    const CUtensorMap ty64 = make_map(enc, y, SEQ, DM, 64), ty128 = make_map(enc, y, SEQ, DM, 128), tx128 = make_map(enc, x, SEQ, DM, 128);
    const CUtensorMap tox = make_map(enc, ox, SEQ, HD, 128), two64 = make_map(enc, d_in[5], HD, DM, 64), tout = make_map(enc, d_out, SEQ, DM, 64);

    cudaFuncSetAttribute(chain_kernel, cudaFuncAttributeMaxDynamicSharedMemorySize, C_SMEM);
    cudaFuncSetAttribute(glu_kernel, cudaFuncAttributeMaxDynamicSharedMemorySize, G_SMEM);
    cudaFuncSetAttribute(out_kernel, cudaFuncAttributeMaxDynamicSharedMemorySize, O_SMEM);

    Descs D;
    for (int i = 0; i < 4; i++) D.sw[i] = DSW;
    D.ns = DNS;
    cudaStream_t st = cudaStreamPerThread;
    cudaLaunchAttribute at;
    at.id = cudaLaunchAttributeProgrammaticStreamSerialization;
    at.val.programmaticStreamSerializationAllowed = 1;
    cudaLaunchConfig_t cfg = {};
    cfg.stream = st; cfg.attrs = &at; cfg.numAttrs = 0;
    cfg.gridDim = dim3(96); cfg.blockDim = dim3(256); cfg.dynamicSmemBytes = C_SMEM;
    cudaLaunchKernelEx(&cfg, chain_kernel, tq, tk, tv, two16, D, D, x, mem0);
    cfg.gridDim = dim3(2 * G_PAIRS); cfg.blockDim = dim3(384); cfg.dynamicSmemBytes = G_SMEM; cfg.numAttrs = (PDL >> 1) & 1;
    cudaLaunchKernelEx(&cfg, glu_kernel, txn128, tg, tu, th64, th128, td, ty64);
    cfg.gridDim = dim3(128); cfg.dynamicSmemBytes = O_SMEM; cfg.numAttrs = (PDL >> 2) & 1;
    cudaLaunchKernelEx(&cfg, out_kernel, tox, two64, tx128, ty128, tout);
}
```

```cpp
#include <cuda_runtime.h>
#include <cuda_bf16.h>
#include <cuda.h>
#include <stdint.h>
#include <type_traits>

namespace {

constexpr int SEQ = 2048, DM = 1024, HD = 4096, FF = 3584, NSEG = 64;

__device__ __align__(1024) __nv_bfloat16 g_xn[SEQ * DM];
__device__ __align__(1024) uint4 g_xc[SEQ * DM / 8];
__device__ __align__(1024) __nv_bfloat16 g_ox[SEQ * HD];
__device__ __align__(1024) __nv_bfloat16 g_h[SEQ * FF];
__device__ __align__(1024) __nv_bfloat16 g_y[SEQ * DM];
__device__ __align__(1024) uint4 g_xmem[4][1024];
__device__ __align__(1024) uint4 g_xo[4][4096];
#define FSTR 8
__device__ __align__(1024) uint32_t g_flag[1][96 * FSTR];
enum { CNT_H = 0, CNT_OX = 16, CNT_Y = 32, CNT_NUM = 160 };
__device__ __align__(1024) uint32_t g_cnt[CNT_NUM * 8];
__device__ __align__(128) uint32_t g_epoch;
#define TL(k, i)
#define TLSM(k)

__device__ __forceinline__ uint32_t smem_u32(const void* p) { return (uint32_t)__cvta_generic_to_shared(p); }
__device__ __forceinline__ uint32_t mapa(uint32_t a, uint32_t r) {
    uint32_t o; asm("mapa.shared::cluster.u32 %0, %1, %2;" : "=r"(o) : "r"(a), "r"(r)); return o;
}
__device__ __forceinline__ void mbar_init(uint32_t a, uint32_t cnt) {
    asm volatile("mbarrier.init.shared.b64 [%0], %1;" :: "r"(a), "r"(cnt) : "memory");
}
__device__ __forceinline__ void mbar_expect(uint32_t a, uint32_t bytes) {
    asm volatile("mbarrier.arrive.expect_tx.shared.b64 _, [%0], %1;" :: "r"(a), "r"(bytes) : "memory");
}
__device__ __forceinline__ void mbar_arrive_cluster(uint32_t a) {
    asm volatile("mbarrier.arrive.shared::cluster.b64 _, [%0];" :: "r"(a) : "memory");
}
__device__ __forceinline__ void spin_guard(uint32_t& it) {
    asm volatile("{\n.reg .pred p;\nadd.u32 %0, %0, 1;\nsetp.gt.u32 p, %0, 0x400000;\n@p st.shared.u32 [%0], %0;\n}" : "+r"(it));
}
__device__ __forceinline__ void mbar_wait(uint32_t a, uint32_t par) {
    asm volatile("{\n.reg .pred p;\nWL:\nmbarrier.try_wait.parity.shared::cta.b64 p, [%0], %1;\n@!p bra WL;\n}" :: "r"(a), "r"(par) : "memory");
}
__device__ __forceinline__ void mbar_arrive(uint32_t a) { asm volatile("mbarrier.arrive.shared.b64 _, [%0];" :: "r"(a) : "memory"); }
__device__ __forceinline__ void tma2d(uint32_t dst, const CUtensorMap* m, int c0, int c1, uint32_t bar) {
    asm volatile("cp.async.bulk.tensor.2d.shared::cluster.global.mbarrier::complete_tx::bytes [%0], [%1, {%3, %4}], [%2];"
                 :: "r"(dst), "l"(m), "r"(bar), "r"(c0), "r"(c1) : "memory");
}
__device__ __forceinline__ void tma2d_mc(uint32_t dst, const CUtensorMap* m, int c0, int c1, uint32_t bar, uint16_t mask) {
    asm volatile("cp.async.bulk.tensor.2d.shared::cluster.global.mbarrier::complete_tx::bytes.multicast::cluster [%0], [%1, {%3, %4}], [%2], %5;"
                 :: "r"(dst), "l"(m), "r"(bar), "r"(c0), "r"(c1), "h"(mask) : "memory");
}
__device__ __forceinline__ void bulk_mc(uint32_t dst, const void* src, uint32_t bytes, uint32_t bar, uint16_t mask) {
    asm volatile("cp.async.bulk.shared::cluster.global.mbarrier::complete_tx::bytes.multicast::cluster [%0], [%1], %2, [%3], %4;"
                 :: "r"(dst), "l"(src), "r"(bytes), "r"(bar), "h"(mask) : "memory");
}
__device__ __forceinline__ void bulk_ld(uint32_t dst, const void* src, uint32_t bytes, uint32_t bar) {
    asm volatile("cp.async.bulk.shared::cluster.global.mbarrier::complete_tx::bytes [%0], [%1], %2, [%3];"
                 :: "r"(dst), "l"(src), "r"(bytes), "r"(bar) : "memory");
}
__device__ __forceinline__ uint32_t gtick() { uint64_t c; asm volatile("mov.u64 %0, %%globaltimer;" : "=l"(c)); return (uint32_t)c >> 5; }
__device__ __forceinline__ uint32_t gtick_dep(uint32_t zero) {
    uint32_t c;
    asm volatile("{\n.reg .pred p;\nsetp.eq.u32 p, %1, 0;\nmov.u32 %0, 0;\n@p mov.u32 %0, %%globaltimer_lo;\n}" : "=r"(c) : "r"(zero));
    return c >> 5;
}
__device__ __forceinline__ uint32_t ld_relaxed1(const void* p) {
    uint32_t v; asm volatile("ld.relaxed.gpu.global.u32 %0, [%1];" : "=r"(v) : "l"(p) : "memory"); return v;
}
__device__ __forceinline__ bool any_nan(float a, float b) {
    uint32_t r;
    asm volatile("{\n.reg .pred p;\nsetp.nan.f32 p, %1, %2;\nvote.sync.any.pred p, p, 0xffffffff;\nselp.u32 %0, 1, 0, p;\n}" : "=r"(r) : "f"(a), "f"(b));
    return r;
}
__device__ __forceinline__ bool bar_sync_any_nan(float a, float b) {
    uint32_t r;
    asm volatile("{\n.reg .pred p;\nsetp.nan.f32 p, %1, %2;\nbarrier.cta.red.or.aligned.pred p, 6, 256, p;\nselp.u32 %0, 1, 0, p;\n}"
                 : "=r"(r) : "f"(a), "f"(b) : "memory");
    return r;
}
__device__ __forceinline__ void bar_arrive(int id, int n) { asm volatile("bar.arrive %0, %1;" :: "r"(id), "r"(n) : "memory"); }
__device__ __forceinline__ uint32_t clk() { uint64_t c; asm volatile("mov.u64 %0, %%clock64;" : "=l"(c)); return (uint32_t)c; }
__device__ __forceinline__ void tma2d_store(const CUtensorMap* m, int c0, int c1, uint32_t src) {
    asm volatile("cp.async.bulk.tensor.2d.global.shared::cta.bulk_group [%0, {%1, %2}], [%3];"
                 :: "l"(m), "r"(c0), "r"(c1), "r"(src) : "memory");
}
__device__ __forceinline__ void bar_sync(int id, int n) { asm volatile("bar.sync %0, %1;" :: "r"(id), "r"(n) : "memory"); }
__device__ __forceinline__ void fence_async() { asm volatile("fence.proxy.async.shared::cta;" ::: "memory"); }
__device__ __forceinline__ void cluster_sync() {
    asm volatile("barrier.cluster.arrive.release.aligned;\nbarrier.cluster.wait.acquire.aligned;" ::: "memory");
}
__device__ __forceinline__ void ldsm4(uint32_t* r, uint32_t a) {
    asm volatile("ldmatrix.sync.aligned.m8n8.x4.shared.b16 {%0,%1,%2,%3}, [%4];"
                 : "=r"(r[0]), "=r"(r[1]), "=r"(r[2]), "=r"(r[3]) : "r"(a) : "memory");
}
__device__ __forceinline__ void ldsm4t(uint32_t* r, uint32_t a) {
    asm volatile("ldmatrix.sync.aligned.m8n8.x4.trans.shared.b16 {%0,%1,%2,%3}, [%4];"
                 : "=r"(r[0]), "=r"(r[1]), "=r"(r[2]), "=r"(r[3]) : "r"(a) : "memory");
}
__device__ __forceinline__ void stsm4(uint32_t a, uint32_t r0, uint32_t r1, uint32_t r2, uint32_t r3) {
    asm volatile("stmatrix.sync.aligned.m8n8.x4.shared.b16 [%0], {%1,%2,%3,%4};" :: "r"(a), "r"(r0), "r"(r1), "r"(r2), "r"(r3) : "memory");
}
__device__ __forceinline__ void stsm4f(uint32_t a, const float* v) {
    asm volatile("{\n.reg .b32 a, b, c, d;\nmov.b32 a, %1;\nmov.b32 b, %2;\nmov.b32 c, %3;\nmov.b32 d, %4;\n"
                 "stmatrix.sync.aligned.m8n8.x4.shared.b16 [%0], {a, b, c, d};\n}" :: "r"(a), "f"(v[0]), "f"(v[1]), "f"(v[2]), "f"(v[3]) : "memory");
}
__device__ __forceinline__ void ldsm4f(float* v, uint32_t a) {
    uint32_t r[4];
    ldsm4(r, a);
#pragma unroll
    for (int i = 0; i < 4; i++) v[i] = __uint_as_float(r[i]);
}
__device__ __forceinline__ void stsm4t(uint32_t a, uint32_t r0, uint32_t r1, uint32_t r2, uint32_t r3) {
    asm volatile("stmatrix.sync.aligned.m8n8.x4.trans.shared.b16 [%0], {%1,%2,%3,%4};" :: "r"(a), "r"(r0), "r"(r1), "r"(r2), "r"(r3) : "memory");
}
__device__ __forceinline__ void stsm2(uint32_t a, uint32_t r0, uint32_t r1) {
    asm volatile("stmatrix.sync.aligned.m8n8.x2.shared.b16 [%0], {%1,%2};" :: "r"(a), "r"(r0), "r"(r1) : "memory");
}
__device__ __forceinline__ void stsm2t(uint32_t a, uint32_t r0, uint32_t r1) {
    asm volatile("stmatrix.sync.aligned.m8n8.x2.trans.shared.b16 [%0], {%1,%2};" :: "r"(a), "r"(r0), "r"(r1) : "memory");
}
__device__ __forceinline__ uint32_t movm(uint32_t a) {
    uint32_t d; asm volatile("movmatrix.sync.aligned.m8n8.trans.b16 %0, %1;" : "=r"(d) : "r"(a)); return d;
}
__device__ __forceinline__ void mma16(float* d, uint32_t a0, uint32_t a1, uint32_t a2, uint32_t a3, uint32_t b0, uint32_t b1) {
    asm volatile("mma.sync.aligned.m16n8k16.row.col.f32.bf16.bf16.f32 {%0,%1,%2,%3}, {%4,%5,%6,%7}, {%8,%9}, {%0,%1,%2,%3};"
                 : "+f"(d[0]), "+f"(d[1]), "+f"(d[2]), "+f"(d[3]) : "r"(a0), "r"(a1), "r"(a2), "r"(a3), "r"(b0), "r"(b1));
}
__device__ __forceinline__ void mma8(float* d, uint32_t a0, uint32_t a1, uint32_t b0) {
    asm volatile("mma.sync.aligned.m16n8k8.row.col.f32.bf16.bf16.f32 {%0,%1,%2,%3}, {%4,%5}, {%6}, {%0,%1,%2,%3};"
                 : "+f"(d[0]), "+f"(d[1]), "+f"(d[2]), "+f"(d[3]) : "r"(a0), "r"(a1), "r"(b0));
}
__device__ __forceinline__ uint32_t pack2(float lo, float hi) {
    uint32_t r; asm("cvt.rn.bf16x2.f32 %0, %1, %2;" : "=r"(r) : "f"(hi), "f"(lo)); return r;
}
__device__ __forceinline__ float bf_lo(uint32_t v) { return __uint_as_float(v << 16); }
__device__ __forceinline__ float bf_hi(uint32_t v) { return __uint_as_float(v & 0xFFFF0000u); }
__device__ __forceinline__ float ex2(float x) { float y; asm("ex2.approx.ftz.f32 %0, %1;" : "=f"(y) : "f"(x)); return y; }
__device__ __forceinline__ float rcp(float x) { float y; asm("rcp.approx.ftz.f32 %0, %1;" : "=f"(y) : "f"(x)); return y; }
__device__ __forceinline__ void sts4f(uint32_t a, float x, float y, float z, float w) {
    asm volatile("st.shared.v4.f32 [%0], {%1,%2,%3,%4};" :: "r"(a), "f"(x), "f"(y), "f"(z), "f"(w) : "memory");
}
__device__ __forceinline__ void sts1u(uint32_t a, uint32_t v) { asm volatile("st.shared.u32 [%0], %1;" :: "r"(a), "r"(v) : "memory"); }
__device__ __forceinline__ void sts4u(uint32_t a, uint4 v) {
    asm volatile("st.shared.v4.u32 [%0], {%1,%2,%3,%4};" :: "r"(a), "r"(v.x), "r"(v.y), "r"(v.z), "r"(v.w) : "memory");
}
__device__ __forceinline__ float4 lds4f(uint32_t a) {
    float4 v; asm volatile("ld.shared.v4.f32 {%0,%1,%2,%3}, [%4];" : "=f"(v.x), "=f"(v.y), "=f"(v.z), "=f"(v.w) : "r"(a) : "memory"); return v;
}
__device__ __forceinline__ float2 lds2f(uint32_t a) {
    float2 v; asm volatile("ld.shared.v2.f32 {%0,%1}, [%2];" : "=f"(v.x), "=f"(v.y) : "r"(a) : "memory"); return v;
}
__device__ __forceinline__ uint4 lds4u(uint32_t a) {
    uint4 v; asm volatile("ld.shared.v4.u32 {%0,%1,%2,%3}, [%4];" : "=r"(v.x), "=r"(v.y), "=r"(v.z), "=r"(v.w) : "r"(a) : "memory"); return v;
}
__device__ __forceinline__ uint32_t lds1u(uint32_t a) {
    uint32_t v; asm volatile("ld.shared.u32 %0, [%1];" : "=r"(v) : "r"(a) : "memory"); return v;
}
__device__ __forceinline__ uint2 lds2u(uint32_t a) {
    uint2 v; asm volatile("ld.shared.v2.u32 {%0,%1}, [%2];" : "=r"(v.x), "=r"(v.y) : "r"(a) : "memory"); return v;
}
__device__ __forceinline__ void st_async4(uint32_t a, uint32_t bar, float x, float y, float z, float w) {
    asm volatile("st.async.shared::cluster.mbarrier::complete_tx::bytes.v4.f32 [%0], {%1,%2,%3,%4}, [%5];"
                 :: "r"(a), "f"(x), "f"(y), "f"(z), "f"(w), "r"(bar) : "memory");
}
__device__ __forceinline__ void st_async2(uint32_t a, uint32_t bar, float x, float y) {
    asm volatile("st.async.shared::cluster.mbarrier::complete_tx::bytes.v2.f32 [%0], {%1,%2}, [%3];"
                 :: "r"(a), "f"(x), "f"(y), "r"(bar) : "memory");
}
template <int OFF>
__device__ __forceinline__ void st_async1f(uint32_t a, uint32_t bar, float x) {
    asm volatile("st.async.shared::cluster.mbarrier::complete_tx::bytes.f32 [%0 + %3], %1, [%2];" :: "r"(a), "f"(x), "r"(bar), "n"(OFF) : "memory");
}
__device__ __forceinline__ uint32_t late_zero() {
    uint64_t c;
    asm volatile("mov.u64 %0, %%clock64;" : "=l"(c));
    return c >> 63;
}
__device__ __forceinline__ void st_async1(uint32_t a, uint32_t bar, uint32_t x) {
    asm volatile("st.async.shared::cluster.mbarrier::complete_tx::bytes.b32 [%0], %1, [%2];" :: "r"(a), "r"(x), "r"(bar) : "memory");
}
__device__ __forceinline__ uint4 ld_relaxed4(const uint4* p) {
    uint4 v;
    asm volatile("ld.relaxed.gpu.global.v4.u32 {%0,%1,%2,%3}, [%4];" : "=r"(v.x), "=r"(v.y), "=r"(v.z), "=r"(v.w) : "l"(p) : "memory");
    return v;
}
__device__ __forceinline__ void st_relaxed4(uint4* p, uint4 v) {
    asm volatile("st.relaxed.gpu.global.v4.u32 [%0], {%1,%2,%3,%4};" :: "l"(p), "r"(v.x), "r"(v.y), "r"(v.z), "r"(v.w) : "memory");
}
__device__ __forceinline__ void count_up(int idx) {
    asm volatile("red.release.gpu.global.add.u32 [%0], 1;" :: "l"(&g_cnt[idx * 8]) : "memory");
}
__device__ __forceinline__ void st_pred1(void* p, uint32_t v, bool on) {
    asm volatile("{\n.reg .pred p;\nsetp.ne.u32 p, %2, 0;\n@p st.relaxed.gpu.global.u32 [%0], %1;\n}" :: "l"(p), "r"(v), "r"((uint32_t)on) : "memory");
}
__device__ __forceinline__ void st_pred4(void* p, uint4 v, bool on) {
    asm volatile("{\n.reg .pred p;\nsetp.ne.u32 p, %5, 0;\n@p st.global.v4.u32 [%0], {%1,%2,%3,%4};\n}"
                 :: "l"(p), "r"(v.x), "r"(v.y), "r"(v.z), "r"(v.w), "r"((uint32_t)on) : "memory");
}
__device__ __forceinline__ void st_relaxed1(void* p, uint32_t v) {
    asm volatile("st.relaxed.gpu.global.u32 [%0], %1;" :: "l"(p), "r"(v) : "memory");
}
__device__ __forceinline__ uint32_t umax4(uint4 v) { return max(max(v.x, v.y), max(v.z, v.w)); }
__device__ __forceinline__ void wg_fence() { asm volatile("wgmma.fence.sync.aligned;" ::: "memory"); }
__device__ __forceinline__ void wg_commit() { asm volatile("wgmma.commit_group.sync.aligned;" ::: "memory"); }
template <int N> __device__ __forceinline__ void wg_wait() { asm volatile("wgmma.wait_group.sync.aligned %0;" :: "n"(N) : "memory"); }
template <int N> __device__ __forceinline__ void reg_fence(float* d) {
#pragma unroll
    for (int i = 0; i < N; i++) asm volatile("" : "+f"(d[i]) :: "memory");
}
#define ACC16(d) "+f"(d[0]), "+f"(d[1]), "+f"(d[2]), "+f"(d[3]), "+f"(d[4]), "+f"(d[5]), "+f"(d[6]), "+f"(d[7]), \
                 "+f"(d[8]), "+f"(d[9]), "+f"(d[10]), "+f"(d[11]), "+f"(d[12]), "+f"(d[13]), "+f"(d[14]), "+f"(d[15])
#define DESC_HI_SW128 "0x40000040"
#define OUT16(d) "=f"(d[0]), "=f"(d[1]), "=f"(d[2]), "=f"(d[3]), "=f"(d[4]), "=f"(d[5]), "=f"(d[6]), "=f"(d[7]), \
                 "=f"(d[8]), "=f"(d[9]), "=f"(d[10]), "=f"(d[11]), "=f"(d[12]), "=f"(d[13]), "=f"(d[14]), "=f"(d[15])
template <int ACCUM, int BOFF>
__device__ __forceinline__ void wg32_rs(float* d, const uint32_t* a, uint64_t dsw) {
    if (ACCUM)
        asm volatile("{\n.reg .b64 db;\nadd.s64 db, %20, %21;\n"
                     "wgmma.mma_async.sync.aligned.m64n32k16.f32.bf16.bf16 {%0,%1,%2,%3,%4,%5,%6,%7,%8,%9,%10,%11,%12,%13,%14,%15}, "
                     "{%16,%17,%18,%19}, db, 1, 1, 1, 0;\n}"
                     : ACC16(d) : "r"(a[0]), "r"(a[1]), "r"(a[2]), "r"(a[3]), "l"(dsw), "n"(BOFF));
    else
        asm volatile("{\n.reg .b64 db;\nadd.s64 db, %20, %21;\n"
                     "wgmma.mma_async.sync.aligned.m64n32k16.f32.bf16.bf16 {%0,%1,%2,%3,%4,%5,%6,%7,%8,%9,%10,%11,%12,%13,%14,%15}, "
                     "{%16,%17,%18,%19}, db, 0, 1, 1, 0;\n}"
                     : OUT16(d) : "r"(a[0]), "r"(a[1]), "r"(a[2]), "r"(a[3]), "l"(dsw), "n"(BOFF));
}
template <int ACCUM, int AOFF, int BOFF>
__device__ __forceinline__ void wg32_ss(float* d, uint64_t dsw) {
    if (ACCUM)
        asm volatile("{\n.reg .b64 da, db;\nadd.s64 da, %16, %17;\nadd.s64 db, %16, %18;\n"
                     "wgmma.mma_async.sync.aligned.m64n32k16.f32.bf16.bf16 {%0,%1,%2,%3,%4,%5,%6,%7,%8,%9,%10,%11,%12,%13,%14,%15}, "
                     "da, db, 1, 1, 1, 1, 0;\n}"
                     : ACC16(d) : "l"(dsw), "n"(AOFF), "n"(BOFF));
    else
        asm volatile("{\n.reg .b64 da, db;\nadd.s64 da, %16, %17;\nadd.s64 db, %16, %18;\n"
                     "wgmma.mma_async.sync.aligned.m64n32k16.f32.bf16.bf16 {%0,%1,%2,%3,%4,%5,%6,%7,%8,%9,%10,%11,%12,%13,%14,%15}, "
                     "da, db, 0, 1, 1, 1, 0;\n}"
                     : OUT16(d) : "l"(dsw), "n"(AOFF), "n"(BOFF));
}
template <int ACCUM, int AOFF, int BOFF>
__device__ __forceinline__ void wg8_ss(float* d, uint64_t dsw, uint64_t dns) {
    if (!ACCUM)
        asm volatile("{\n.reg .b64 da, db;\nadd.s64 da, %4, %6;\nadd.s64 db, %5, %7;\n"
                     "wgmma.mma_async.sync.aligned.m64n8k16.f32.bf16.bf16 {%0,%1,%2,%3}, da, db, 0, 1, 1, 1, 0;\n}"
                     : "=f"(d[0]), "=f"(d[1]), "=f"(d[2]), "=f"(d[3]) : "l"(dsw), "l"(dns), "n"(AOFF), "n"(BOFF));
    else
        asm volatile("{\n.reg .b64 da, db;\nadd.s64 da, %4, %6;\nadd.s64 db, %5, %7;\n"
                     "wgmma.mma_async.sync.aligned.m64n8k16.f32.bf16.bf16 {%0,%1,%2,%3}, da, db, 1, 1, 1, 1, 0;\n}"
                     : "+f"(d[0]), "+f"(d[1]), "+f"(d[2]), "+f"(d[3]) : "l"(dsw), "l"(dns), "n"(AOFF), "n"(BOFF));
}
template <int I0, int I1, class F>
__device__ __forceinline__ void static_for(F&& f) {
    if constexpr (I0 < I1) { f(std::integral_constant<int, I0>{}); static_for<I0 + 1, I1>(f); }
}
template <int I0, int I1, int AOFF, int BOFF>
__device__ __forceinline__ void wg8_chain(float* d, uint64_t dsw, uint64_t dns) {
    wg_fence();
    static_for<I0, I1>([&](auto i) { wg8_ss<i.value != 0, AOFF + i.value * 128, BOFF + i.value * 16>(d, dsw, dns); });
    wg_commit();
}

__device__ __forceinline__ void ln_row(const uint4* v, int row, int lane) {
    float f[32];
#pragma unroll
    for (int j = 0; j < 4; j++) {
        f[j * 8 + 0] = bf_lo(v[j].x); f[j * 8 + 1] = bf_hi(v[j].x); f[j * 8 + 2] = bf_lo(v[j].y); f[j * 8 + 3] = bf_hi(v[j].y);
        f[j * 8 + 4] = bf_lo(v[j].z); f[j * 8 + 5] = bf_hi(v[j].z); f[j * 8 + 6] = bf_lo(v[j].w); f[j * 8 + 7] = bf_hi(v[j].w);
    }
    float s = 0.f;
#pragma unroll
    for (int i = 0; i < 32; i++) s += f[i];
#pragma unroll
    for (int o = 16; o; o >>= 1) s += __shfl_xor_sync(~0u, s, o);
    const float mean = s * (1.f / DM);
    float q = 0.f;
#pragma unroll
    for (int i = 0; i < 32; i++) { f[i] -= mean; q += f[i] * f[i]; }
#pragma unroll
    for (int o = 16; o; o >>= 1) q += __shfl_xor_sync(~0u, q, o);
    const float r = 1.f / sqrtf(q * (1.f / DM) + 1e-5f);
    uint4* dst = reinterpret_cast<uint4*>(g_xn + (size_t)row * DM);
    uint4* dst1 = g_xc + (row >> 5) * 4096 + (lane >> 3) * 256 + (row & 31) * 8 + ((lane & 7) ^ (row & 7));
#pragma unroll
    for (int j = 0; j < 4; j++) {
        const uint4 o = make_uint4(pack2(f[j * 8] * r, f[j * 8 + 1] * r), pack2(f[j * 8 + 2] * r, f[j * 8 + 3] * r),
                                   pack2(f[j * 8 + 4] * r, f[j * 8 + 5] * r), pack2(f[j * 8 + 6] * r, f[j * 8 + 7] * r));
        dst[j * 32 + lane] = o;
        dst1[(j & 1) * 2048 + (j >> 1) * 1024] = o;
    }
}
__device__ __forceinline__ void reset_exchange(const __nv_bfloat16* __restrict__ mem0) {
    const int gi = blockIdx.x * 256 + threadIdx.x;
    const uint4 poison = make_uint4(~0u, ~0u, ~0u, ~0u);
    if (gi < 1024) {
        uint4 m = reinterpret_cast<const uint4*>(mem0)[(gi & 7) * 128 + (gi >> 3)];
        if (m.x == ~0u) m.x = 0x7FFF7FFFu;
        if (m.y == ~0u) m.y = 0x7FFF7FFFu;
        if (m.z == ~0u) m.z = 0x7FFF7FFFu;
        if (m.w == ~0u) m.w = 0x7FFF7FFFu;
        g_xmem[0][gi] = m;
    } else if (gi < 4096) {
        (&g_xmem[0][0])[gi] = poison;
    } else if (gi < 4096 + 16384) {
        (&g_xo[0][0])[gi - 4096] = poison;
    } else if (gi < 4096 + 16384 + 24 * FSTR) {
        reinterpret_cast<uint4*>(&g_flag[0][0])[gi - 4096 - 16384] = poison;
    } else if (gi >= 24576 - CNT_NUM) {
        g_cnt[(24575 - gi) * 8] = 0;
    }
}

#define ONKQ 45
constexpr int ONKV = 128 - 2 * ONKQ;
constexpr uint32_t SB0 = 1024;
constexpr uint32_t C_WS = 0, C_XN = 65536, C_MB = 98304, C_WO = 114688, C_SMEM = 232448;
constexpr uint32_t C_BAR = C_SMEM - 384, C_CAL = C_BAR + 192;
constexpr uint32_t C_SLOTQ = C_WO + ONKQ * 2048, C_QX = C_SLOTQ + 8192, C_KX = C_QX + 4096,
                   C_XSL = C_KX + 4096, C_OL = C_SLOTQ + 4096;
constexpr uint32_t C_SLOTV = C_WO + ONKV * 2048, C_V = C_SLOTV + 8192, C_PL = C_V + 20480, C_SL = C_PL + 4096;
constexpr uint32_t C_DUMP = C_BAR - 512;
static_assert(C_XSL + 5120 <= C_DUMP && C_SL + 2560 <= C_DUMP, "smem overflow");
enum { B_W0 = 0, B_W1, B_W2, B_WS, B_XF0, B_XF1, B_SC, B_P0, B_P1, B_XS, B_OL, B_MF0, B_MF1, B_OF, B_RT0, B_RT1, B_VF, B_MBF, B_GO, B_DUMP, B_NUM };
struct Descs { uint64_t sw[4], ns; };
constexpr uint64_t DSW = 0x4000004000010000ull, DNS = 0x0000001000080000ull;
template <int V> using ic = std::integral_constant<int, V>;
constexpr float SM_SCALE = 0.08838834764831845f * 1.4426950408889634f;

#define TSD(i) do {} while (0)
#define TS_FLUSH(w)
#define TSX(i, c)
#define TS(i)
#define NOFILL 0
#define DLY1 2230
#define DLY2 2490
#define SWAP16 0
#define SSFIRST 1
#define EARLYB 0
#define CANARY ~0u
#define L2POS 10
#define PFX 1
#define QK1 10
#define RFPOS 6
#define STPOS 12
#define OHEAD 8
#define OTAIL 3
#define DLYS 450
#define DLYB 1
#define VLEAD 4

#define VEARLY 8
#define QSPLIT 20
__device__ __forceinline__ bool elect() {
    uint32_t r;
    asm volatile("{\n.reg .pred p;\nelect.sync _|p, 0xffffffff;\nselp.u32 %0, 1, 0, p;\n}" : "=r"(r));
    return r;
}
__device__ __forceinline__ int uni(int v) { return __shfl_sync(~0u, v, 0); }
__device__ __forceinline__ void calibrate(uint32_t cal, float keep) {
    const uint32_t t0 = gtick();
    uint32_t t, it = 0;
    do { t = gtick(); spin_guard(it); } while (__any_sync(~0u, t == t0));
    const uint32_t c = clk();
    const uint4 p = lds4u(cal);
    const float cpt = 256.f * fminf(fmaxf(__fdividef((float)(c - p.y), (float)((t - p.x) & 0x7FFFFFF)), 16.f), 128.f);
    __syncwarp();
    sts4u(cal, make_uint4(t, c, (uint32_t)(keep > 0.f ? fmaf(keep, (float)p.z - cpt, cpt) : cpt), 0));
}
struct Stamps { uint32_t v[6]; };
__device__ __forceinline__ void load_stamps2(Stamps& t, const uint32_t* f, uint32_t l16, bool on = true) {
    const char* p = reinterpret_cast<const char*>(f) + (l16 >> 2) * FSTR;
    asm volatile("{\n.reg .pred p;\nsetp.ne.u32 p, %7, 0;\nmov.u32 %0, 63;\nmov.u32 %1, 63;\nmov.u32 %2, 63;\nmov.u32 %3, 63;\nmov.u32 %4, 63;\nmov.u32 %5, 63;\n"
                 "@p ld.relaxed.gpu.global.v2.u32 {%0, %1}, [%6];\n@p ld.relaxed.gpu.global.v2.u32 {%2, %3}, [%6 + %8];\n"
                 "@p ld.relaxed.gpu.global.v2.u32 {%4, %5}, [%6 + %9];\n}"
                 : "=&r"(t.v[0]), "=&r"(t.v[1]), "=&r"(t.v[2]), "=&r"(t.v[3]), "=&r"(t.v[4]), "=&r"(t.v[5])
                 : "l"(p), "r"((uint32_t)on), "n"(128 * FSTR), "n"(256 * FSTR) : "memory");
}
template <int N>
__device__ __forceinline__ uint32_t stamps_missing(const uint32_t* v, int s) {
    uint32_t x = 0;
#pragma unroll
    for (int i = 0; i < N; i++) x |= v[i] ^ s;
    return x & 63;
}
template <int N>
__device__ __forceinline__ uint32_t latest_stamp(const uint32_t* v, const uint4 cal) {
    int late = (int)(v[0] - (cal.x << 6));
#pragma unroll
    for (int i = 1; i < N; i++) late = max(late, (int)(v[i] - (cal.x << 6)));
    return cal.y + (((late >> 6) * (int)cal.z) >> 8);
}
__device__ __forceinline__ void wait_clock(uint32_t target, uint32_t range = 65536) {
    while (__any_sync(~0u, target - clk() < range)) {}
}

template <int BYTES>
__device__ __forceinline__ bool incomplete(uint32_t buf, uint32_t l16) {
    uint32_t m = 0;
#pragma unroll 1
    for (int o = 0; o < BYTES; o += 256) m = max(m, umax4(lds4u(buf + o + (l16 & 255))));
    return __any_sync(~0u, m == ~0u);
}
__device__ __forceinline__ void refetch(uint32_t buf, const uint4* src, uint32_t bytes, uint32_t b, int w4, int barid, uint32_t& tries) {
    spin_guard(tries);
    bar_sync(barid, 128);
    if (w4 == 0 && elect()) { mbar_expect(b, bytes); bulk_ld(buf, src, bytes, b); }
    __syncwarp();
    mbar_wait(b, 0);
    bar_sync(barid, 128);
    if (w4 == 0 && elect()) mbar_arrive(b);
    __syncwarp();
}

__device__ __forceinline__ void load_box(const CUtensorMap* tA, const CUtensorMap* tB, int cl, int rank, uint32_t dst, int j, int q, uint32_t b) {
    const bool isb = (q ^ (q >> 1)) & 1;
    tma2d(dst + q * 16384, isb ? tB : tA, cl * 256 + (rank >= 4 ? (rank - 4) * 128 + isb * 64 : rank * 64), (q >> 1) * 512 + j * 128, b);
}

template <bool ISV, int WG>
__device__ __forceinline__ void chain_main(const CUtensorMap* tA, const CUtensorMap* tB, const CUtensorMap* tWo,
                                           const uint32_t sb, const int cl, const int rank, const Descs& D, const uint32_t goal) {
    const int tid = threadIdx.x;
    uint32_t l16 = __shfl_sync(~0u, (tid & 31) * 16, tid & 31);
    int w4 = uni((tid >> 5) & 3);
    const int role = ISV ? 2 : (rank & 1), hh = ISV ? rank - 4 : rank >> 1, head = 2 * cl + hh;
    const uint32_t bar = sb + C_BAR;
    constexpr int ONK = ISV ? ONKV : ONKQ;
    const int ostart = (hh * 128 + role * ONKQ);

    uint32_t wk[24][4], wv[24][4];
    uint32_t a_adr;
    {
        if (WG == 1 && w4 == 0) calibrate(sb + C_CAL, 0.f);
        const int lane = tid & 31, kr = (lane & 7) + ((lane >> 4) << 3);
        a_adr = __shfl_sync(~0u, sb + WG * 32768 + kr * 128 + (((w4 * 2 + ((lane >> 3) & 1)) ^ (kr & 7)) << 4), lane);
#pragma unroll
        for (int j = 0; j < 3; j++) {
            mbar_wait(bar + (B_W0 + j) * 8, 0);
#pragma unroll
            for (int i = 0; i < 8; i++) {
                ldsm4t(wk[j * 8 + i], a_adr + j * 65536 + i * 2048);
                ldsm4t(wv[j * 8 + i], a_adr + j * 65536 + 16384 + i * 2048);
            }
            if (j != 1) {
                bar_sync(6, 256);
                if (j == 0 && tid == 0) TL(1, 6);
                if (WG == 0 && j == 0 && elect()) load_box(tA, tB, cl, rank, sb + C_WS, 3, w4, bar + B_WS * 8);
                if (WG == 0 && j == 2) {
                    if (elect())
                        for (int i = w4; i < ONK; i += 4) tma2d(sb + C_WO + i * 2048, tWo, cl * 64, (ostart + i) * 16, bar + B_OF * 8);
                }
                __syncwarp();
            }
        }
        if (NOFILL) { for (uint32_t o = C_WO + ONK * 2048 + tid * 16; o < C_BAR; o += 4096) sts4u(sb + o, make_uint4(0, 0, 0, 0)); bar_sync(6, 256); }
        if (WG == 1 && w4 == 1) {
            uint32_t v, it = 0;
            do {
                asm volatile("ld.acquire.gpu.global.u32 %0, [%1];" : "=r"(v) : "l"(&g_epoch) : "memory");
                spin_guard(it);
            } while (__any_sync(~0u, (int)(v - goal) < 0));
        }
        if (WG == 1 && w4 == 0) calibrate(sb + C_CAL, 0.f);
        __syncwarp();
        bar_sync(6, 256);
        asm volatile("fence.proxy.async.global;" ::: "memory");
    }

    constexpr uint32_t SLOT = ISV ? C_SLOTV : C_SLOTQ;
    constexpr int WS_A = (SB0 + C_WS + WG * 32768) >> 4, WO_A = (SB0 + C_WO) >> 4, MB_A = (SB0 + C_MB) >> 4;
#define XN_A(ks) (int)(((SB0 + C_XN + WG * 16384) >> 4) + ((ks) >> 2) * 256 + ((ks) & 3) * 2)
    const uint32_t slot = (sb + SLOT + w4 * 512), mbw = sb + C_MB + WG * 8192;
    const uint32_t sb_v = (mapa(sb, 4 + hh));
    const uint32_t sb_x = uni(mapa(sb, 2 * hh + (WG ? 1 : (~w4 & 1))));
    const uint32_t sb_o = (mapa(sb, w4));
    const uint32_t u_off = (ISV ? (head * 128 + w4 * 32) * 16 : (cl * 4 + rank) * 256 + (w4 & 1) * 128);
    const uint32_t v_row = (sb + C_V + (2 * WG + (w4 >> 1)) * 512), v_b = ((w4 & 1) * 64);
    const uint32_t u_flag = (blockIdx.x * FSTR);
    const uint32_t f_half = (w4 & 1) * role * (ONKV * 128), f_sb = uni(mapa(sb, rank + (w4 & 1) * (4 + hh - rank)));
    const uint32_t f_src = uni((ostart + (w4 & 1) * (2 - role) * ONKQ) * 256 + f_half), f_dst = uni(f_sb + C_MB + f_half);
    const uint32_t m_dst = (sb + C_MB + role * 8192), m_bar = (bar + (B_MF0 + role) * 8);
    uint32_t target;
    Stamps st1;
    uint4 cal;
    int s = -1;
    uint32_t pf[4][4];
    float xk[16], xv[16];
    float xsc[4];
    uint4 oxp[4];

    auto send_planes = [&](auto n, uint32_t a, int b, const float* v, bool hold) {
        const uint32_t dump = sb + C_DUMP + (l16 >> 2), to = a + (l16 >> 2), ad = hold ? dump : to;
        const uint32_t mb = hold ? (dump & 0xFF000000u) | (SB0 + C_BAR + B_DUMP * 8) : (to & 0xFF000000u) | (SB0 + C_BAR + b * 8);
        static_for<0, n.value>([&](auto i) { st_async1f<i.value * 128>(ad, mb, v[i.value]); });
    };
    auto send_scores = [&]() {
        bar_sync(12, 256);
        if (!NOFILL) send_planes(ic<4>{}, sb_x + C_XSL + role * 2560 + (1 + w4) * 512, B_XS, xsc, s < 0);
    };
    auto store_ox = [&](int ss) {
        char* orow = reinterpret_cast<char*>(g_ox) + (ss * (32 * HD * 2) + (u_off >> 3) + (l16 >> 6) * (HD * 2) + (l16 & 48));
#pragma unroll
        for (int i = 0; i < 4; i++) st_pred4(orow + i * (8 * HD * 2), oxp[i], ss >= 0);
    };
    auto load_tokens = [&](int seg, int wina, int g) {
        const int khalf = ISV ? 1 - wina : wina;
        if (!NOFILL && elect()) {
            mbar_expect(bar + (B_XF0 + g) * 8, 16384);
            bulk_ld(sb + C_XN + g * 16384, g_xc + (seg * 4 + khalf * 2 + g) * 1024, 16384, bar + (B_XF0 + g) * 8);
        }
        __syncwarp();
    };
    auto prefetch = [&]() {
#pragma unroll
        for (int i = 0; i < 4; i++) ldsm4t(pf[i], a_adr + C_WS + (i & 1) * 16384 + (i >> 1) * 2048);
    };
    constexpr int HA = ISV ? 0 : 1, NK1 = ISV ? 0 : QK1;
    auto products = [&](auto give, auto half, auto init, auto i0, auto i1, const uint64_t d) {
        static_for<i0.value, i1.value>([&](auto i) {
            constexpr int ks = half.value * 16 + i.value, acc = !(init.value && i.value == i0.value);
            if constexpr (ks >= 24) wg32_ss<acc, WS_A + give.value * 1024 + (ks - 24) * 128, XN_A(i.value)>(give.value ? xv : xk, d);
            else if constexpr (give.value) wg32_rs<acc, XN_A(i.value)>(xv, wv[ks], d);
            else wg32_rs<acc, XN_A(i.value)>(xk, wk[ks], d);
        });
    };
    auto stream_a = [&](const uint64_t dk, const uint64_t dv, auto mid) {
        if (NOFILL) { mid(); return; }
        constexpr int F = (WG == 0 && SSFIRST) ? 8 : 0;
        wg_fence();
        products(ic<0>{}, ic<HA>{}, ic<1>{}, ic<F>{}, ic<F + 8>{}, dk);
        products(ic<1>{}, ic<HA>{}, ic<1>{}, ic<F>{}, ic<F + 8>{}, dv);
        products(ic<1>{}, ic<HA>{}, ic<0>{}, ic<8 - F>{}, ic<16 - F>{}, dv);
        mid();
        products(ic<0>{}, ic<HA>{}, ic<0>{}, ic<8 - F>{}, ic<16 - F>{}, dk);
        wg_commit();
    };
    auto token_softmax = [&]() {
        const int hi = w4 - 2, lane = l16 >> 4;
        const uint32_t src = sb + C_XSL + hi * 256 + (l16 & 255) + (l16 >> 8) * 2560;
        const int d0 = 16 * role + 8 * hi + (lane >> 2) - 2 * (lane & 3);
        mbar_wait(bar + B_XS * 8, s & 1);
        float e[10];
        float m = -INFINITY;
#pragma unroll
        for (int i = 0; i < 5; i++) {
            __syncwarp();
            float a[4];
            ldsm4f(a, src + i * 512);
            e[2 * i] = (i == 0 || d0 >= 8 * (i - 1)) ? a[0] + a[2] : -INFINITY;
            e[2 * i + 1] = (i == 0 || d0 > 8 * (i - 1)) ? a[1] + a[3] : -INFINITY;
            m = fmaxf(m, fmaxf(e[2 * i], e[2 * i + 1]));
        }
        m = fmaxf(m, __shfl_xor_sync(~0u, m, 1));
        m = fmaxf(m, __shfl_xor_sync(~0u, m, 2));
        m *= -SM_SCALE;
        float l = 0.f;
#pragma unroll
        for (int i = 0; i < 10; i++) { e[i] = ex2(fmaf(e[i], SM_SCALE, m)); l += e[i]; }
        l += __shfl_xor_sync(~0u, l, 1);
        l += __shfl_xor_sync(~0u, l, 2);
        l = rcp(l);
        const uint32_t pd = sb_v + C_PL + (s & 1) * 2048 + role * 768 + hi * 128 + (l16 >> 2), pb = sb_v + C_BAR + (B_P0 + (s & 1)) * 8;
        st_async1(pd, pb, pack2(e[0] * l, e[1] * l));
        st_async1(pd + 256, pb, pack2(e[2] * l, e[3] * l));
        st_async1(pd + 512, pb, pack2(e[4] * l, e[5] * l));
        if (role) {
            st_async1(pd + 768, pb, pack2(e[6] * l, e[7] * l));
            st_async1(pd + 1024, pb, pack2(e[8] * l, e[9] * l));
        }
        if (hi == 0 && l16 == 0) mbar_expect(bar + B_XS * 8, 3072 + role * 2048);
        __syncwarp();
    };

    auto windows = [&]() {
        asm volatile("" : "+r"(l16), "+r"(w4));
        const uint64_t* const dd = D.sw;
        TS(5);
        if constexpr (WG == 1) {
            TS(6);
            if (ISV) bar_sync(3, 256); else send_scores();
            uint32_t missing;
            stream_a(dd[0], dd[1], [&]() {
                if (ISV) return;
                __syncwarp();
                const uint32_t zero = late_zero();
                uint4 cz = cal;
                cz.x += zero;
                missing = stamps_missing<6>(st1.v, s + zero);
                target = latest_stamp<6>(st1.v, cz) + DLY1;
                asm volatile("" : "+r"(missing), "+r"(target));
            });
            if (!NOFILL) bar_arrive(7, 256);
            if (ISV) {
                if (!NOFILL) store_ox(s - 1);
                st_relaxed4(reinterpret_cast<uint4*>(reinterpret_cast<char*>(&g_xo[(s + 2) & 3][0]) + (u_off + l16)), make_uint4(~0u, ~0u, ~0u, ~0u));
            }
            auto fetch_o = [&]() {
            if (!ISV && w4 < 2 && s >= 0) {
                const char* src = reinterpret_cast<const char*>(&g_xo[s & 3][0]) + f_src;
                if (__builtin_expect(__any_sync(~0u, missing), 0)) {
                    uint32_t it = 0;
                    do { load_stamps2(st1, g_flag[0], l16); spin_guard(it); } while (__any_sync(~0u, stamps_missing<6>(st1.v, s)));
                    target = latest_stamp<6>(st1.v, lds4u(sb + C_CAL)) + DLY1;
                }
                mbar_wait(bar + B_VF * 8, s & 1);
                TS(10);
                wait_clock(target);
                if (elect()) bulk_ld(f_dst, src, ONKQ * 256 - w4 * (ONKQ * 256 - ONKV * 128), f_sb + C_BAR + B_OF * 8);
                __syncwarp();
                TS(8);
            }
            };
            if (!EARLYB) fetch_o();
            if (!NOFILL) {
                wg_wait<0>();
                reg_fence<16>(xk); reg_fence<16>(xv);
                if (w4 == 3) { bar_sync(2, 128); load_tokens(s + 1, 0, 1); }
                else bar_arrive(2, 128);
            }
            if (EARLYB) fetch_o();
            TS(7);
        } else {
            if (!NOFILL) {
                mbar_wait(bar + B_XF0 * 8, 0);
                bar_sync(7, 256);
            }
            TS(6);
            stream_a(dd[0], dd[1], []() {});
        }
        if constexpr (WG == 0) {
            if (s >= 0) {
                const uint32_t dst = sb_o + C_OL + rank * 512;
                uint32_t can = sb + C_MB + l16 * 8 + (l16 >> 2), can2 = can + (l16 < (ONK * 2 - 64) * 16 ? 8192 : 0);
                asm volatile("" : "+r"(can), "+r"(can2));
                float co[4];
                TS(7);
                uint32_t tries = 0;
                mbar_wait(bar + B_OF * 8, s & 1);
                TS(8);
                const uint32_t c0 = lds1u(can), c1 = lds1u(can + 4096), c2 = lds1u(can2);
                __syncwarp();
                wg8_chain<0, OHEAD, WO_A, MB_A>(co, D.sw[0], D.ns);
                __syncwarp();
                {
                    const uint32_t z = late_zero();
                    if (__builtin_expect(__any_sync(~0u, max(max(c0 | z, c1 | z), c2) == CANARY), 0)) {
                        wg_wait<0>();
                        do refetch(sb + C_MB, &g_xo[s & 3][ostart * 16], ONK * 256, bar + B_RT0 * 8, w4, 1, tries);
                        while (__any_sync(~0u, max(max(lds1u(can), lds1u(can + 4096)), lds1u(can2)) == CANARY));
                        wg8_chain<0, OHEAD, WO_A, MB_A>(co, DSW, DNS);
                    }
                }
                wg_wait<1>();
                if (l16 == 0) mbar_arrive(bar + B_GO * 8);
                wg8_chain<OHEAD, ONK - OTAIL, WO_A, MB_A>(co, D.sw[0], D.ns);
                static_for<ONK - OTAIL, ONK>([&](auto i) { wg8_ss<1, WO_A + i.value * 128, MB_A + i.value * 16>(co, D.sw[0], D.ns); });
                wg_commit();
                wg_wait<1>();
                bar_arrive(5, 256);
                wg_wait<0>();
                reg_fence<4>(co);
                const bool nan = co[0] != co[0] || co[1] != co[1];
                send_planes(ic<4>{}, dst, B_OL, co, nan);
                if (__builtin_expect(__any_sync(~0u, nan), 0)) {
                    while (incomplete<ONK * 256>(sb + C_MB, l16)) {
                        refetch(sb + C_MB, &g_xo[s & 3][ostart * 16], ONK * 256, bar + B_RT0 * 8, w4, 1, tries);
                        co[0] = co[1] = co[2] = co[3] = 0.f;
#pragma unroll 1
                        for (int i = 0; i < ONK; i++) {
                            wg_fence();
                            wg8_ss<1, WO_A, MB_A>(co, DSW + i * 128, DNS + i * 16);
                            wg_commit();
                            wg_wait<0>();
                        }
                        reg_fence<4>(co);
                    }
                    send_planes(ic<4>{}, dst, B_OL, co, !nan);
                }
                TS(9);
                if (l16 < 48 && w4 == 3) mbar_expect(bar + B_MF0 * 8 + (l16 >> 1), l16 == 32 ? ONK * 256 : 8192);
            } else {
                wg_wait<0>();
                if (l16 == 0) mbar_arrive(bar + B_GO * 8);
                bar_arrive(5, 256);
            }
            if (l16 < 32) mbar_arrive_cluster(mapa(bar + B_MBF * 8, 2 * hh + (l16 >> 4)));
            __syncwarp();
            if (!NOFILL) { reg_fence<16>(xk); reg_fence<16>(xv); }
        } else {
            if (w4 < 2) {
                if (w4 == 1) {
                    mbar_wait(bar + B_GO * 8, (s + 1) & 1);
                    load_tokens(s + 1, 0, 0);
                    if (PFX && ISV && s + 3 < NSEG && elect())
                        asm volatile("cp.async.bulk.prefetch.L2.global [%0], 8192;" :: "l"(g_xc + (s + 3) * 4096 + ((cl & 3) * 2 + hh) * 512) : "memory");
                    __syncwarp();
                } else if (!ISV) {
                    calibrate(sb + C_CAL, 0.75f);
                }
                if (!ISV) st_relaxed1(reinterpret_cast<char*>(&g_xmem[(s + 3) & 3][0]) + (u_off + (l16 >> 2)), ~0u);
            } else if (!NOFILL && s >= 0) {
                if (ISV && w4 == 2 && (s & 3) == 1 && s > 1 && l16 == 0) count_up(CNT_OX + (s >> 2) - 1);
                __syncwarp();
                if (!ISV) token_softmax();
                TSX(9, w4 == 2);
            }
            if (!NOFILL) mbar_wait(bar + B_XF1 * 8, 1);
            bar_sync(5, 256);
        }
        asm volatile("" : "+r"(l16), "+r"(w4));
        TSX(11, w4 == 0 && (WG || ISV));
        uint32_t v_dst = ISV ? v_row + ((s + 1) & 1) * 10240 + ((l16 & 384) << 4) + ((l16 & 96) << 2) + ((l16 & 112) ^ v_b)
                             : sb + C_QX + WG * 4096 + w4 * 1024 + l16;
        uint32_t v_dst2 = v_dst ^ 32;
        if (WG == 0) {
            v_dst = __shfl_sync(~0u, v_dst, l16 >> 4);
            if (ISV) v_dst2 = __shfl_sync(~0u, v_dst2, l16 >> 4);
        }
        constexpr int NR = SWAP16 ? 2 : 4;
        constexpr uint32_t OUT = SWAP16 ? WG * 4096 : 0, IN = SWAP16 ? (WG ^ 1) * 4096 : 0;
        auto give = [&]() {
#pragma unroll
            for (int j = 0; j < NR; j++) {
                if (SWAP16) stsm4(slot + OUT + l16 + j * 2048, pack2(xv[8 * j], xv[8 * j + 1]), pack2(xv[8 * j + 2], xv[8 * j + 3]),
                                  pack2(xv[8 * j + 4], xv[8 * j + 5]), pack2(xv[8 * j + 6], xv[8 * j + 7]));
                else stsm4f(slot + l16 + j * 2048, xv + 4 * j);
            }
        };
        auto take = [&](uint32_t (*r)[4]) {
#pragma unroll
            for (int j = 0; j < NR; j++) ldsm4(r[j], slot + IN + l16 + j * 2048);
        };
        auto store_tokens = [&](const uint32_t (*r)[4]) {
            uint32_t lo[4], hi[4];
#pragma unroll
            for (int j = 0; j < 4; j++) {
                if (SWAP16) {
                    const uint32_t a = r[j >> 1][(j & 1) * 2], b = r[j >> 1][(j & 1) * 2 + 1];
                    lo[j] = pack2(xk[4 * j] + bf_lo(a), xk[4 * j + 1] + bf_hi(a));
                    hi[j] = pack2(xk[4 * j + 2] + bf_lo(b), xk[4 * j + 3] + bf_hi(b));
                } else {
                    lo[j] = pack2(xk[4 * j] + __uint_as_float(r[j % NR][0]), xk[4 * j + 1] + __uint_as_float(r[j % NR][1]));
                    hi[j] = pack2(xk[4 * j + 2] + __uint_as_float(r[j % NR][2]), xk[4 * j + 3] + __uint_as_float(r[j % NR][3]));
                }
            }
            if (!ISV) {
                stsm4t(v_dst, lo[0], lo[1], lo[2], lo[3]);
                stsm4t(v_dst + 512, hi[0], hi[1], hi[2], hi[3]);
            } else {
                stsm4(v_dst, lo[0], lo[1], lo[2], lo[3]);
                stsm4(v_dst2, hi[0], hi[1], hi[2], hi[3]);
            }
        };
        if constexpr (WG == 1) {
            if (!NOFILL) {
                wg_fence();
                products(ic<1>{}, ic<1 - HA>{}, ic<0>{}, ic<0>{}, ic<16>{}, dd[3]);
                products(ic<0>{}, ic<1 - HA>{}, ic<0>{}, ic<0>{}, ic<NK1>{}, dd[2]);
                wg_commit();
                if (ISV) {
                    bar_arrive(7, 256);
                } else {
                    mbar_wait(bar + B_MBF * 8, (s + 1) & 1);
                    bar_sync(7, 256);
                }
                wg_wait<0>();
                reg_fence<16>(xv); reg_fence<16>(xk);
                give();
                bar_arrive(8, 256);
            }
            TS(12);
            prefetch();
            if (!ISV && w4 == 0) {
                const uint4* src = &g_xmem[(s + 1) & 3][role * 512];
                if (NOFILL) mbar_wait(bar + B_MBF * 8, (s + 1) & 1);
                TS(3);
                wait_clock(target + DLY2, s >= 0 ? 65536 : 0);
                if (hh) { if (elect()) bulk_mc(m_dst, src, 8192, m_bar, 0x2C); }
                else if (elect()) bulk_mc(m_dst, src, 8192, m_bar, 0x13);
                __syncwarp();
                TS(4);
            }
            if (!NOFILL) {
                bar_sync(9, 256);
                uint32_t r[NR][4];
                take(r);
                bar_sync(14, 256);
                wg_fence();
                products(ic<0>{}, ic<1 - HA>{}, ic<0>{}, ic<NK1>{}, ic<16>{}, dd[2]);
                wg_commit();
                wg_wait<0>();
                reg_fence<16>(xk);
                TS(13);
                store_tokens(r);
                bar_arrive(10, 256);
                if (w4 != 3) bar_arrive(13, 128);
            }
        } else {
            uint32_t r[NR][4];
            if (!NOFILL) mbar_wait(bar + B_XF0 * 8, 1);
            if (!ISV && w4 < 2 && s >= 0) {
                char* gd = reinterpret_cast<char*>(&g_xmem[(s + 1) & 3][0]) + (u_off + (l16 >> 2));
                const uint32_t src = sb + C_OL + w4 * 256 + l16 + (l16 & 256);
                mbar_wait(bar + B_OL * 8, s & 1);
                TSD(3);
                float a[3][4];
#pragma unroll
                for (int i = 0; i < 3; i++) ldsm4f(a[i], src + i * 1024);
                st_relaxed1(gd, movm(pack2((a[0][0] + a[0][2]) + (a[1][0] + a[1][2]) + (a[2][0] + a[2][2]),
                                           (a[0][1] + a[0][3]) + (a[1][1] + a[1][3]) + (a[2][1] + a[2][3]))));
                TS(11);
                if (w4 == 0 && l16 == 0) mbar_expect(bar + B_OL * 8, 3072);
                __syncwarp();
            }
            if (!NOFILL) {
                bar_sync(7, 256);
                TS(12);
                wg_fence();
                products(ic<1>{}, ic<1 - HA>{}, ic<0>{}, ic<0>{}, ic<16>{}, dd[3]);
                wg_commit();
                products(ic<0>{}, ic<1 - HA>{}, ic<0>{}, ic<0>{}, ic<6>{}, dd[2]);
                wg_commit();
                bar_sync(8, 256);
                take(r);
                wg_wait<1>();
                reg_fence<16>(xv);
                give();
                bar_arrive(9, 256);
                products(ic<0>{}, ic<1 - HA>{}, ic<0>{}, ic<6>{}, ic<16>{}, dd[2]);
                wg_commit();
                bar_arrive(14, 256);
                wg_wait<0>();
                reg_fence<16>(xk);
            }
            TS(13);
            if (!NOFILL) store_tokens(r);
            prefetch();
        }
    };

    if (tid == 0) TL(1, 2);
    if (w4 == 0) load_tokens(0, 1, WG);
    mbar_wait(bar + B_WS * 8, 0);
    if (WG == 1 && !NOFILL) mbar_wait(bar + B_XF1 * 8, 0);
    if (WG == 0) bar_arrive(ISV ? 3 : 12, 256);
    xsc[0] = xsc[1] = xsc[2] = xsc[3] = 0.f;
    load_stamps2(st1, g_flag[0], l16, false);
    cal = make_uint4(0, 0, 0, 0);
    oxp[0] = oxp[1] = oxp[2] = oxp[3] = make_uint4(0, 0, 0, 0);

#pragma unroll 1
    while (true) {
        windows();
        s++;

        asm volatile("" : "+r"(l16), "+r"(a_adr), "+r"(w4));
        TS_FLUSH(WG);
        TS(0);
        float ck[4], cv[4], dk[4], dv[4];
        uint32_t b[3][4], tries = 0;
        const uint32_t kl = sb + C_KX + ((l16 & 384) << 2) + (l16 & 112);
        auto load_b = [&](auto kp) { ldsm4(b[kp.value % 3], mbw + l16 + ((kp.value & 3) ? (kp.value >> 2) * 3 + (kp.value & 3) - 1 : 12 + (kp.value >> 2)) * 512); };
        auto kpair = [&](auto kp_) {
            constexpr int kp = kp_.value, grp = kp >> 2, ph = kp & 3;
            if constexpr (kp > 0 && kp < 14) load_b(ic<kp + 2>{});
            const uint32_t* bb = b[kp % 3];
            if constexpr (ph != 0) {
                constexpr int q = (grp * 3 + ph - 1) * 2;
                static_for<(ph == 1 ? 0 : ph), ph + 1>([&](auto i) {
                    if constexpr (grp < 3) ldsm4t(pf[i.value], a_adr + C_WS + (i.value & 1) * 16384 + (grp * 2 + 2 + (i.value >> 1)) * 2048);
                });
                __syncwarp();
                mma16(cv, wv[q][0], wv[q][1], wv[q][2], wv[q][3], bb[0], bb[1]);
                mma16(ck, wk[q][0], wk[q][1], wk[q][2], wk[q][3], bb[0], bb[1]);
                mma16(dv, wv[q + 1][0], wv[q + 1][1], wv[q + 1][2], wv[q + 1][3], bb[2], bb[3]);
                mma16(dk, wk[q + 1][0], wk[q + 1][1], wk[q + 1][2], wk[q + 1][3], bb[2], bb[3]);
            } else {
                if constexpr (kp == 0) {
#pragma unroll
                    for (int i = 0; i < 4; i++) ck[i] = cv[i] = dk[i] = dv[i] = 0.f;
                }
                mma16(ck, pf[0][0], pf[0][1], pf[0][2], pf[0][3], bb[0], bb[1]);
                mma16(cv, pf[1][0], pf[1][1], pf[1][2], pf[1][3], bb[0], bb[1]);
                mma16(dk, pf[2][0], pf[2][1], pf[2][2], pf[2][3], bb[2], bb[3]);
                mma16(dv, pf[3][0], pf[3][1], pf[3][2], pf[3][3], bb[2], bb[3]);
            }
        };
        auto hand_over = [&]() {
#pragma unroll
            for (int i = 0; i < 4; i++) { cv[i] += dv[i]; ck[i] += dk[i]; }
            if (ISV) {
                stsm4f(slot + WG * 2048 + l16, cv);
            } else {
                const float *q = WG ? cv : ck, *k = WG ? ck : cv;
                stsm4t(slot + WG * 2048 + l16, pack2(q[0], q[1]), pack2(q[2], q[3]), pack2(k[0], k[1]), pack2(k[2], k[3]));
            }
        };
        auto repair = [&]() {
            bar_sync(6, 256);
            while (incomplete<8192>(mbw, l16)) {
                refetch(mbw, &g_xmem[s & 3][WG * 512], 8192, bar + (B_RT0 + WG) * 8, w4, 1 + WG, tries);
                prefetch();
                static_for<0, 3>(load_b);
                static_for<0, 16>(kpair);
                hand_over();
            }
            bar_sync(6, 256);
        };
        {
            const uint32_t can = mbw + l16 * 8 + (l16 >> 2);
            uint32_t* const flag = &g_flag[0][u_flag + WG + l16];
            for (;; tries |= 1) {
                asm volatile("" : "+r"(tries));
                if (__builtin_expect(tries, 0)) {
                    refetch(mbw, &g_xmem[s & 3][WG * 512], 8192, bar + (B_RT0 + WG) * 8, w4, 1 + WG, tries);
                }
                mbar_wait(bar + (B_MF0 + WG) * 8, s & 1);
                TS(1);
                static_for<0, 3>(load_b);
                const uint32_t c0 = lds1u(can), c1 = lds1u(can + 4096);
                const uint32_t v = ((gtick() - (ISV ? VLEAD : 0)) << 6) | s;
                kpair(ic<0>{});
                const bool early = __any_sync(~0u, max(c0, c1) == CANARY);
                st_pred1(flag, v, w4 * 512 + l16 == 1536 && !early);
                if (__builtin_expect(!early, 1)) break;
            }
            static_for<1, RFPOS>(kpair);
            if (WG == 0 && !NOFILL) bar_sync(10, 256);
            if (WG == 1 && !NOFILL && w4 == 3) {
                bar_sync(13, 128);
                if (s < NSEG - 1) load_tokens(s + 1, 1, 1);
            }
            static_for<RFPOS, 13>(kpair);
        }
        auto finish_projections = [&]() {
            static_for<13, 16>(kpair);
            hand_over();
            TS(2);
            return bar_sync_any_nan(cv[0], cv[1]);
        };
        if constexpr (!ISV) {
            const uint32_t qa = sb + C_SLOTQ + ((l16 >> 1) & 128) + ((l16 & 128) << 3) + (l16 & 112);
            const uint32_t ma = sb + C_SLOTQ + 256 + l16 + (l16 & 256);
            const uint32_t qx = sb + C_QX + l16 + (l16 & 256);
            auto ldsm_sum = [&](uint32_t* r, uint32_t a) {
                uint32_t t[4];
                ldsm4(r, a); ldsm4(t, a + 2048);
#pragma unroll
                for (int i = 0; i < 4; i++) asm("add.rn.bf16x2 %0, %0, %1;" : "+r"(r[i]) : "r"(t[i]));
            };
            auto tile = [&](float* d, const uint32_t (*q)[4], const uint32_t (*k)[4]) {
                d[0] = d[1] = d[2] = d[3] = 0.f;
#pragma unroll
                for (int i = 0; i < 4; i++) mma16(d, q[i][0], q[i][1], q[i][2], q[i][3], k[i >> 1][(i & 1) * 2], k[i >> 1][(i & 1) * 2 + 1]);
            };
            auto send = [&](int ti, const float* d, bool hold) {
                send_planes(ic<4>{}, sb_x + C_XSL + role * 2560 + ti * 512, B_XS, d, hold);
            };
            if constexpr (WG == 0) {
                auto scores = [&](auto again) {
                    bool nan = false;
                    if (w4 < 2) {
                        uint32_t k0[2][4], k1[2][4], q0[4], q1[4];
                        const uint32_t ka = kl + w4 * 256, dst = sb_v + C_SL + role * 1024 + w4 * 512;
                        ldsm4(k0[0], ka); ldsm4(k0[1], ka + 2048);
                        ldsm4(k1[0], ka + 128); ldsm4(k1[1], ka + 128 + 2048);
                        __syncwarp();
                        if (!again.value) nan = finish_projections();
                        TS(3);
                        ldsm_sum(q0, qa); ldsm_sum(q1, qa + 512);
                        float s0[4] = {0.f, 0.f, 0.f, 0.f}, s1[4] = {0.f, 0.f, 0.f, 0.f}, s2[4] = {0.f, 0.f, 0.f, 0.f}, s3[4] = {0.f, 0.f, 0.f, 0.f};
                        mma16(s0, q0[0], q0[1], q0[2], q0[3], k0[0][0], k0[0][1]);
                        mma16(s1, q0[0], q0[1], q0[2], q0[3], k0[1][0], k0[1][1]);
                        mma16(s2, q0[0], q0[1], q0[2], q0[3], k1[0][0], k1[0][1]);
                        mma16(s3, q0[0], q0[1], q0[2], q0[3], k1[1][0], k1[1][1]);
                        mma16(s0, q1[0], q1[1], q1[2], q1[3], k0[0][2], k0[0][3]);
                        mma16(s1, q1[0], q1[1], q1[2], q1[3], k0[1][2], k0[1][3]);
                        mma16(s2, q1[0], q1[1], q1[2], q1[3], k1[0][2], k1[0][3]);
                        mma16(s3, q1[0], q1[1], q1[2], q1[3], k1[1][2], k1[1][3]);
                        const float out[4] = {s0[0] + s1[2], s0[1] + s1[3], s2[0] + s3[2], s2[1] + s3[3]};
                        send_planes(ic<4>{}, dst, B_SC, out, nan);
                        if (!again.value) bar_arrive(12, 256);
                        TS(4);
                    } else if (w4 == 2) {
                        uint32_t q0[4], q1[4], km[2][4], q[4][4];
                        const uint32_t dst = sb_v + C_SL + 2048 + role * 256;
                        if (!again.value) nan = finish_projections();
                        ldsm_sum(q0, qa); ldsm_sum(km[0], ma); ldsm_sum(km[1], ma + 1024); ldsm_sum(q1, qa + 512);
                        __syncwarp();
#pragma unroll
                        for (int i = 0; i < 4; i++) ldsm4(q[i], qx + 256 + i * 1024);
                        float s0[4] = {0.f, 0.f, 0.f, 0.f}, s1[4] = {0.f, 0.f, 0.f, 0.f}, d0[4];
                        mma16(s0, q0[0], q0[1], q0[2], q0[3], km[0][0], km[0][1]);
                        mma16(s1, q0[0], q0[1], q0[2], q0[3], km[1][0], km[1][1]);
                        mma16(s0, q1[0], q1[1], q1[2], q1[3], km[0][2], km[0][3]);
                        mma16(s1, q1[0], q1[1], q1[2], q1[3], km[1][2], km[1][3]);
                        const float out[2] = {s0[0] + s1[2], s0[1] + s1[3]};
                        send_planes(ic<2>{}, dst, B_SC, out, nan);
                        if (!NOFILL) tile(d0, q, km);
                        if (!again.value) bar_sync(12, 256);
                        if (!NOFILL) send(0, d0, nan);
                    } else {
                        if (!again.value) {
                            nan = finish_projections();
                            if (s < NSEG - 1) load_tokens(s + 1, 1, 0);
                        }
                        uint32_t q[4][4], k0[2][4], k1[2][4], km[2][4];
                        float d0[4], d1[4], d2[4];
                        if (!NOFILL) {
#pragma unroll
                            for (int i = 0; i < 4; i++) ldsm4(q[i], qx + i * 1024);
                            ldsm4(k0[0], kl); ldsm4(k0[1], kl + 2048);
                            ldsm4(k1[0], kl + 128); ldsm4(k1[1], kl + 128 + 2048);
                            tile(d1, q, k0); tile(d2, q, k1);
                            ldsm_sum(km[0], ma); ldsm_sum(km[1], ma + 1024);
                            tile(d0, q, km);
                        }
                        if (!again.value) bar_sync(12, 256);
                        if (!NOFILL) { send(0, d0, nan); send(1, d1, nan); send(2, d2, nan); }
                    }
                    return nan;
                };
                if (__builtin_expect(__any_sync(~0u, scores(ic<0>{})), 0)) { repair(); scores(ic<1>{}); bar_arrive(12, 256); }
                if (__builtin_expect(s == NSEG - 1, 0)) break;
            } else {
                const bool nan = finish_projections();
                load_stamps2(st1, g_flag[0], l16, w4 < 2);
                if (!NOFILL) mbar_wait(bar + B_XF1 * 8, s == NSEG - 1);
                cal = lds4u(sb + C_CAL);
                if (!NOFILL) {
                    uint32_t q[4][4], k0[2][4];
                    float d1[4] = {0.f, 0.f, 0.f, 0.f};
#pragma unroll
                    for (int i = 0; i < 4; i++) { ldsm4(q[i], qx + 256 + i * 1024); xsc[i] = 0.f; }
                    ldsm4(k0[0], kl + w4 * 128); ldsm4(k0[1], kl + w4 * 128 + 2048);
#pragma unroll
                    for (int i = 0; i < 4; i++) mma16((i & 1) ? d1 : xsc, q[i][0], q[i][1], q[i][2], q[i][3], k0[i >> 1][(i & 1) * 2], k0[i >> 1][(i & 1) * 2 + 1]);
#pragma unroll
                    for (int i = 0; i < 4; i++) xsc[i] += d1[i];
                }
                if (__builtin_expect(__any_sync(~0u, nan), 0)) {
                    bar_sync(12, 256);
                    repair();
                    load_stamps2(st1, g_flag[0], l16, false);
                    cal = lds4u(sb + C_CAL);
                }
                if (__builtin_expect(s == NSEG - 1, 0)) {
                    asm volatile("" : "+r"(l16));
                    send_scores();
                    if (w4 >= 2 && !NOFILL) token_softmax();
                    break;
                }
            }
        } else {
            const uint32_t lane_b = sb + C_V + w4 * 512 + ((l16 & 384) << 4) + (l16 & 112);
            auto load_vx = [&](uint32_t (*vx)[4], int ss) {
#pragma unroll
                for (int j = 0; j < 4; j++) ldsm4(vx[j], ((lane_b + (ss & 1) * 10240) ^ (j * 32)) + j * 128);
            };
            auto load_vm = [&](uint32_t* vm, int ss) { ldsm4(vm, sb + C_V + (ss & 1) * 10240 + w4 * 512 + 8192 + (l16 ^ ((l16 >> 2) & 96))); };
            auto token_output = [&](int ss) {
                uint32_t vx[4][4], vm[4];
                const uint32_t pl = sb + C_PL + (ss & 1) * 2048 + l16;
                auto lds_frag = [&](uint32_t a) { uint32_t r[4]; ldsm4(r, a); return make_uint4(r[0], r[1], r[2], r[3]); };
                load_vm(vm, ss);
                load_vx(vx, ss);
                mbar_wait(bar + (B_P0 + (ss & 1)) * 8, (ss >> 1) & 1);
                uint32_t dep = 0;
#pragma unroll
                for (int mh = 1; mh >= 0; mh--) {
                    uint2 pm;
                    asm volatile("ldmatrix.sync.aligned.m8n8.x2.shared.b16 {%0,%1}, [%2];" : "=r"(pm.x), "=r"(pm.y) : "r"(pl + mh * 768 + dep) : "memory");
                    const uint4 p0 = lds_frag(pl + mh * 768 + 256);
                    float o[4][4];
#pragma unroll
                    for (int j = 0; j < 4; j++) { o[j][0] = o[j][1] = o[j][2] = o[j][3] = 0.f; mma8(o[j], pm.x, pm.y, vm[j]); }
#pragma unroll
                    for (int j = 0; j < 4; j++) mma16(o[j], p0.x, p0.y, p0.z, p0.w, vx[j][0], vx[j][1]);
                    if (mh) {
                        const uint4 p1 = lds_frag(pl + 1536);
#pragma unroll
                        for (int j = 0; j < 4; j++) mma16(o[j], p1.x, p1.y, p1.z, p1.w, vx[j][2], vx[j][3]);
                    }
                    oxp[2 * mh] = make_uint4(pack2(o[0][0], o[0][1]), pack2(o[1][0], o[1][1]), pack2(o[2][0], o[2][1]), pack2(o[3][0], o[3][1]));
                    oxp[2 * mh + 1] = make_uint4(pack2(o[0][2], o[0][3]), pack2(o[1][2], o[1][3]), pack2(o[2][2], o[2][3]), pack2(o[3][2], o[3][3]));
                    asm volatile("" : "+r"(oxp[2 * mh].x), "+r"(oxp[2 * mh].y), "+r"(oxp[2 * mh].z), "+r"(oxp[2 * mh].w),
                                 "+r"(oxp[2 * mh + 1].x), "+r"(oxp[2 * mh + 1].y), "+r"(oxp[2 * mh + 1].z), "+r"(oxp[2 * mh + 1].w));
                    dep = oxp[2].x == ~0u ? 16 : 0;
                }
            };
            const uint32_t vd = v_row + (s & 1) * 10240 + 8192 + ((l16 & 96) << 2) + ((l16 & 112) ^ v_b ^ ((l16 & 128) >> 2));
            uint32_t vx[4][4], vm[4];
            if (WG == 0) { load_vx(vx, s); __syncwarp(); }
            if (__builtin_expect(__any_sync(~0u, finish_projections()), 0)) { repair(); if (WG == 0) load_vx(vx, s); }
            float r[4];
            ldsm4f(r, slot + (WG ^ 1) * 2048 + l16);
            stsm2(vd, pack2(ck[0] + r[0], ck[1] + r[1]), pack2(ck[2] + r[2], ck[3] + r[3]));
            TSX(3, WG == 0 && w4 == 0);
            if (WG == 1) {
                bar_arrive(11, 256);
                if (w4 == 3 && l16 < 32) mbar_arrive_cluster(mapa(bar + B_VF * 8, 2 * hh + (l16 >> 4)));
                if (w4 == 2 && s < NSEG - 1) load_tokens(s + 1, 1, 0);
                if (!NOFILL) {
                    token_output(s - 1);
                    if (w4 == 1 && l16 == 0 && s > 0) mbar_expect(bar + (B_P0 + ((s - 1) & 1)) * 8, 2048);
                    mbar_wait(bar + B_XF1 * 8, s == NSEG - 1);
                }
            }
            if (WG == 0) bar_sync(11, 256);
            if (__builtin_expect(s == NSEG - 1, 0)) {
                bar_sync(6, 256);
                if (WG == 1) {
                    if (!NOFILL) {
                        store_ox(s - 1);
                        token_output(s);
                        store_ox(s);
                    }
                    bar_sync(2, 128);
                    if (w4 == 0 && l16 == 0) {
                        if (NOFILL) for (int i = 0; i < 15; i++) count_up(CNT_OX + i);
                        count_up(CNT_OX + 15);
                    }
                    __syncwarp();
                }
                mbar_wait(bar + B_SC * 8, s & 1);
                break;
            }
            if constexpr (WG == 0) {
                load_vm(vm, s);
                const uint32_t oo = u_off + ((l16 & 48) << 3) + ((l16 >> 2) & 112);
                char* dst = reinterpret_cast<char*>(&g_xo[s & 3][0]) + oo;
                mbar_wait(bar + B_SC * 8, s & 1);
                TS(4);
                float a0[4], b0[4], a1[4], b1[4], a2[4];
                ldsm4f(a0, sb + C_SL + l16); ldsm4f(b0, sb + C_SL + 1024 + l16);
                ldsm4f(a1, sb + C_SL + 512 + l16); ldsm4f(b1, sb + C_SL + 1536 + l16);
                ldsm4f(a2, sb + C_SL + 2048 + l16);
                const float e[10] = {a0[0] + b0[0], a0[1] + b0[1], a0[2] + b0[2], a0[3] + b0[3], a1[0] + b1[0], a1[1] + b1[1], a1[2] + b1[2], a1[3] + b1[3],
                                     a2[0] + a2[2], a2[1] + a2[3]};
                float m = fmaxf(fmaxf(fmaxf(e[0], e[1]), fmaxf(e[2], e[3])), fmaxf(fmaxf(e[4], e[5]), fmaxf(e[6], e[7])));
                m = fmaxf(m, fmaxf(e[8], e[9]));
                m = fmaxf(fmaxf(m, __shfl_xor_sync(~0u, m, 1)), fmaxf(__shfl_xor_sync(~0u, m, 2), __shfl_xor_sync(~0u, m, 3)));
                m *= -SM_SCALE;
                float x[10];
#pragma unroll
                for (int i = 0; i < 10; i++) x[i] = ex2(fmaf(e[i], SM_SCALE, m));
                float o[4][4];
                const uint32_t p0 = pack2(x[0], x[1]), p1 = pack2(x[2], x[3]), j0 = __float_as_uint(x[1]), j1 = __float_as_uint(x[3]);
#pragma unroll
                for (int j = 0; j < 4; j++) { o[j][0] = o[j][1] = o[j][2] = o[j][3] = 0.f; mma16(o[j], p0, j0, p1, j1, vx[j][0], vx[j][1]); }
                const uint32_t p2 = pack2(x[4], x[5]), p3 = pack2(x[6], x[7]), j2 = __float_as_uint(x[5]), j3 = __float_as_uint(x[7]);
#pragma unroll
                for (int j = 0; j < 4; j++) mma16(o[j], p2, j2, p3, j3, vx[j][2], vx[j][3]);
                const uint32_t p4 = pack2(x[8], x[9]), j4 = __float_as_uint(x[9]);
                float l = (((x[0] + x[1]) + (x[2] + x[3])) + ((x[4] + x[5]) + (x[6] + x[7]))) + (x[8] + x[9]);
                l = (l + __shfl_xor_sync(~0u, l, 1)) + (__shfl_xor_sync(~0u, l, 2) + __shfl_xor_sync(~0u, l, 3));
#pragma unroll
                for (int j = 0; j < 4; j++) mma8(o[j], p4, j4, vm[j]);
                l = rcp(l);
                st_relaxed4(reinterpret_cast<uint4*>(dst), make_uint4(pack2(o[0][0] * l, o[0][1] * l), pack2(o[1][0] * l, o[1][1] * l),
                                                                      pack2(o[2][0] * l, o[2][1] * l), pack2(o[3][0] * l, o[3][1] * l)));
                bar_arrive(3, 256);
                if (w4 == 0 && l16 == 0) mbar_expect(bar + B_SC * 8, 2560);
            }
        }
    }
}

__global__ void __cluster_dims__(6, 1, 1) __launch_bounds__(256, 1)
chain_kernel(const __grid_constant__ CUtensorMap tq, const __grid_constant__ CUtensorMap tk, const __grid_constant__ CUtensorMap tv,
             const __grid_constant__ CUtensorMap two, const __grid_constant__ Descs D, const __grid_constant__ Descs DV,
             const __nv_bfloat16* __restrict__ x, const __nv_bfloat16* __restrict__ mem0) {
    extern __shared__ __align__(1024) uint8_t smem[];
    const uint32_t sb = smem_u32(smem);
    const int rank = blockIdx.x % 6, cl = blockIdx.x / 6, role = rank >= 4 ? 2 : rank & 1;
    const int tid = threadIdx.x, lane = tid & 31, gw = blockIdx.x * 8 + uni(tid >> 5);
    const CUtensorMap *tA = role == 2 ? &tv : &tq, *tB = role == 2 ? &tv : &tk;
    uint4 cur[4], nxt[4];
#pragma unroll
    for (int j = 0; j < 4; j++) {
        cur[j] = reinterpret_cast<const uint4*>(x)[gw * 128 + j * 32 + lane];
        nxt[j] = reinterpret_cast<const uint4*>(x)[(gw + 768) * 128 + j * 32 + lane];
    }
    if (gw < 512 && lane < 16) asm volatile("prefetch.global.L2 [%0];" :: "l"(x + (gw + 1536) * DM + lane * 64));
    if ((gw & 7) == 0) {
        if (tid == 0) { TL(1, 0); TLSM(1); }
        if ((sb & 0xFFFFFF) != SB0 || mapa(sb, 5) != (SB0 | 0x5000000u)) sts1u(1, 0);
        const uint32_t b = sb + C_BAR + lane * 8;
        uint32_t tx = 0;
        if (lane <= B_WS) tx = 65536;
        if (lane == B_MF0 || lane == B_MF1) tx = 8192;
        if (lane == B_OF) tx = (role == 2 ? ONKV : ONKQ) * (256 + 2048);
        if (lane == B_SC) tx = 2560;
        if (lane == B_P0 || lane == B_P1) tx = 2048;
        if (lane == B_XS || lane == B_OL) tx = (lane == B_XS && role) ? 5120 : 3072;
        if (lane < B_NUM) mbar_init(b, lane == B_MBF ? 12 : (lane == B_GO ? 4 : 1));
        if (tx) mbar_expect(b, tx);
        asm volatile("fence.mbarrier_init.release.cluster;" ::: "memory");
        fence_async();
        __syncwarp();
#pragma unroll 1
        for (int i = 0; i < 12; i++)
            if (elect()) load_box(tA, tB, cl, rank, sb + (i >> 2) * 65536, i >> 2, i & 3, sb + C_BAR + (i >> 2) * 8);
    }
    __syncwarp();
    asm volatile("barrier.cluster.arrive.release.aligned;" ::: "memory");
    reset_exchange(mem0);
#pragma unroll 1
    for (int row = gw; row < SEQ; row += 768) {
        uint4 v[4];
#pragma unroll
        for (int j = 0; j < 4; j++) {
            v[j] = cur[j]; cur[j] = nxt[j];
            if (row + 1536 < SEQ) nxt[j] = reinterpret_cast<const uint4*>(x)[(row + 1536) * 128 + j * 32 + lane];
        }
        ln_row(v, row, lane);
    }
    if (tid == 0) TL(1, 5);
    __syncthreads();
    uint32_t goal = 0;
    if (tid == 160) {
        __threadfence();
        goal = (atomicAdd(&g_epoch, 1u) / 96 + 1) * 96;
        asm volatile("griddepcontrol.launch_dependents;" ::: "memory");
        TL(1, 4);
    }
    __syncwarp();
    asm volatile("barrier.cluster.wait.acquire.aligned;" ::: "memory");
    goal = uni(goal);
    const int wg = uni(threadIdx.x >> 7);
    if (role == 2) {
        if (wg == 0) chain_main<true, 0>(&tv, &tv, &two, sb, cl, rank, DV, goal);
        else chain_main<true, 1>(&tv, &tv, &two, sb, cl, rank, DV, goal);
    } else {
        if (wg == 0) chain_main<false, 0>(&tq, &tk, &two, sb, cl, rank, D, goal);
        else chain_main<false, 1>(&tq, &tk, &two, sb, cl, rank, D, goal);
    }
    __syncwarp();
    cluster_sync();
    if (threadIdx.x == 0) TL(1, 1);
}

__device__ __forceinline__ void wg256(float* d, uint32_t da, uint32_t db, uint32_t accum) {
    asm volatile("{\n.reg .b64 da, db;\n.reg .pred p;\nsetp.ne.u32 p, %130, 0;\nmov.b64 da, {%128, " DESC_HI_SW128 "};\nmov.b64 db, {%129, " DESC_HI_SW128 "};\n"
                 "wgmma.mma_async.sync.aligned.m64n256k16.f32.bf16.bf16 {"
                 "%0,%1,%2,%3,%4,%5,%6,%7,%8,%9,%10,%11,%12,%13,%14,%15,%16,%17,%18,%19,%20,%21,%22,%23,%24,%25,%26,%27,%28,%29,%30,%31,"
                 "%32,%33,%34,%35,%36,%37,%38,%39,%40,%41,%42,%43,%44,%45,%46,%47,%48,%49,%50,%51,%52,%53,%54,%55,%56,%57,%58,%59,%60,%61,%62,%63,"
                 "%64,%65,%66,%67,%68,%69,%70,%71,%72,%73,%74,%75,%76,%77,%78,%79,%80,%81,%82,%83,%84,%85,%86,%87,%88,%89,%90,%91,%92,%93,%94,%95,"
                 "%96,%97,%98,%99,%100,%101,%102,%103,%104,%105,%106,%107,%108,%109,%110,%111,%112,%113,%114,%115,%116,%117,%118,%119,%120,%121,%122,%123,%124,%125,%126,%127"
                 "}, da, db, p, 1, 1, 0, 1;\n}"
                 : ACC16(d), ACC16((d + 16)), ACC16((d + 32)), ACC16((d + 48)), ACC16((d + 64)), ACC16((d + 80)), ACC16((d + 96)), ACC16((d + 112))
                 : "r"(da), "r"(db), "r"(accum));
}
__device__ __forceinline__ void wg128(float* d, uint32_t da, uint32_t db, uint32_t accum) {
    asm volatile("{\n.reg .b64 da, db;\n.reg .pred p;\nsetp.ne.u32 p, %66, 0;\nmov.b64 da, {%64, " DESC_HI_SW128 "};\nmov.b64 db, {%65, " DESC_HI_SW128 "};\n"
                 "wgmma.mma_async.sync.aligned.m64n128k16.f32.bf16.bf16 {"
                 "%0,%1,%2,%3,%4,%5,%6,%7,%8,%9,%10,%11,%12,%13,%14,%15,%16,%17,%18,%19,%20,%21,%22,%23,%24,%25,%26,%27,%28,%29,%30,%31,"
                 "%32,%33,%34,%35,%36,%37,%38,%39,%40,%41,%42,%43,%44,%45,%46,%47,%48,%49,%50,%51,%52,%53,%54,%55,%56,%57,%58,%59,%60,%61,%62,%63"
                 "}, da, db, p, 1, 1, 0, 1;\n}"
                 : ACC16(d), ACC16((d + 16)), ACC16((d + 32)), ACC16((d + 48))
                 : "r"(da), "r"(db), "r"(accum));
}
__device__ __forceinline__ float sigmoidf_(float v) { return rcp(1.f + ex2(-1.4426950408889634f * v)); }
__device__ __forceinline__ void wait_count(int idx, uint32_t n) {
    uint32_t v, it = 0;
    while (true) {
        asm volatile("ld.acquire.gpu.global.u32 %0, [%1];" : "=r"(v) : "l"(&g_cnt[idx * 8]) : "memory");
        if (v >= n) break;
        __nanosleep(100);
        spin_guard(it);
    }
    asm volatile("fence.proxy.async.global;" ::: "memory");
}

constexpr int G_STAGES = 4, G_PAIRS = 18;
constexpr uint32_t G_STAGE = 49152, G_EPI = G_STAGES * G_STAGE, G_BAR = G_EPI + 32768, G_SMEM = G_BAR + 256;
__device__ __forceinline__ int glu_job(int p, int j) {
    if (j < 12) return j * G_PAIRS + p;
    if (p < 14) return j == 12 ? 224 + p : (j == 13 ? 242 + p : -1);
    return j < 14 ? 216 + (j - 12) * 4 + (p - 14) : (j == 14 ? 224 + p : -1);
}

__global__ void __cluster_dims__(2, 1, 1) __launch_bounds__(384, 1)
glu_kernel(const __grid_constant__ CUtensorMap tXn, const __grid_constant__ CUtensorMap tG, const __grid_constant__ CUtensorMap tU,
           const __grid_constant__ CUtensorMap tHst, const __grid_constant__ CUtensorMap tHld, const __grid_constant__ CUtensorMap tD,
           const __grid_constant__ CUtensorMap tYst) {
    extern __shared__ __align__(1024) uint8_t smem[];
    const uint32_t sb = smem_u32(smem);
    const uint32_t full = sb + G_BAR, empty = full + 64;
    const int tid = threadIdx.x, lane = tid & 31;
    const int warp = uni(tid >> 5), wg = warp >> 2;
    const int rank = blockIdx.x & 1, pair = blockIdx.x >> 1;
    asm volatile("griddepcontrol.launch_dependents;" ::: "memory");
    if (tid == 0) {
        TL(2, 0); TLSM(2);
        for (int i = 0; i < G_STAGES; i++) { mbar_init(full + i * 8, 1); mbar_init(empty + i * 8, 16); }
        asm volatile("fence.mbarrier_init.release.cluster;" ::: "memory");
        fence_async();
    }
    __syncthreads();
    cluster_sync();
    if (wg == 0) {
        asm volatile("setmaxnreg.dec.sync.aligned.u32 40;");
        if (warp == 0) {
            if (lane == 0) {
                uint32_t st = 0, ph = 1;
                asm volatile("fence.acq_rel.gpu;\nfence.proxy.async.global;" ::: "memory");
                for (int j = 0, job; (job = glu_job(pair, j)) >= 0; j++) {
                    const bool dn = job >= 224;
                    const int mp = dn ? (job - 224) >> 2 : job / 28, nt = dn ? job & 3 : job % 28, rb = mp * 2 + rank;
                    const CUtensorMap* tA = dn ? &tHld : &tXn;
                    const CUtensorMap* tB = dn ? &tD : (rank ? &tU : &tG);
                    const int bcol = dn ? nt * 256 + rank * 128 : nt * 128, nkb = dn ? FF / 64 : DM / 64;
                    if (j == 12) TL(2, 2);
                    if (dn) wait_count(CNT_H + rb, 56);
                    for (int kb = 0; kb < nkb; kb++) {
                        mbar_wait(empty + st * 8, ph);
                        const uint32_t base = sb + st * G_STAGE;
                        mbar_expect(full + st * 8, G_STAGE);
                        tma2d(base, tA, kb * 64, rb * 128, full + st * 8);
                        tma2d_mc(base + 16384 + rank * 16384, tB, bcol, kb * 64, full + st * 8, 3);
                        tma2d_mc(base + 16384 + rank * 16384 + 8192, tB, bcol + 64, kb * 64, full + st * 8, 3);
                        if (++st == G_STAGES) { st = 0; ph ^= 1; }
                    }
                }
            }
        } else if (warp < 3) {
            const int cw = warp - 1;
            const uint32_t epi = sb + G_EPI + cw * 16384;
            bar_arrive(3 + cw, 160);
            for (int j = 0, job; (job = glu_job(pair, j)) >= 0; j++) {
                const bool dn = job >= 224;
                const int mp = dn ? (job - 224) >> 2 : job / 28, nt = dn ? job & 3 : job % 28, rb = mp * 2 + rank;
                for (int hp = 0; hp <= (int)dn; hp++) {
                    bar_sync(1 + cw, 160);
                    if (lane == 0) {
                        const int col = dn ? nt * 256 + hp * 128 : nt * 128;
                        tma2d_store(dn ? &tYst : &tHst, col, rb * 128 + cw * 64, epi);
                        tma2d_store(dn ? &tYst : &tHst, col + 64, rb * 128 + cw * 64, epi + 8192);
                        asm volatile("cp.async.bulk.commit_group;\ncp.async.bulk.wait_group.read 0;" ::: "memory");
                    }
                    __syncwarp();
                    bar_arrive(3 + cw, 160);
                    if (lane == 0) {
                        asm volatile("cp.async.bulk.wait_group 0;\nfence.proxy.async.global;" ::: "memory");
                        count_up(dn ? CNT_Y + rb * 8 + nt * 2 + hp : CNT_H + rb);
                    }
                    __syncwarp();
                }
            }
        }
        cluster_sync();
    } else {
        asm volatile("setmaxnreg.inc.sync.aligned.u32 232;");
        const int cw = wg - 1, w4 = warp & 3;
        const uint32_t empty_dst = mapa(empty, lane & 1);
        const int er = w4 * 16 + (lane & 15), ec = lane >> 4;
        const uint32_t epi = sb + G_EPI + cw * 16384 + er * 128;
        uint32_t st = 0, ph = 0;
        float acc[128];
        auto put = [&](const uint32_t* o) {
            bar_sync(3 + cw, 160);
#pragma unroll
            for (int q = 0; q < 8; q++) stsm4(epi + (q >> 2) * 8192 + (((2 * (q & 3) + ec) ^ (er & 7)) << 4), o[q * 4], o[q * 4 + 1], o[q * 4 + 2], o[q * 4 + 3]);
            fence_async();
            bar_arrive(1 + cw, 160);
        };
        for (int j = 0, job; (job = glu_job(pair, j)) >= 0; j++) {
            const bool dn = job >= 224;
            const int nkb = dn ? FF / 64 : DM / 64;
            uint32_t prev = 0;
#pragma unroll 1
            for (int kb = 0; kb < nkb; kb++) {
                mbar_wait(full + st * 8, ph);
                const uint32_t base = sb + st * G_STAGE;
                const uint32_t da = (((base + cw * 8192) & 0x3FFFF) >> 4) | (1u << 16);
                const uint32_t db = (((base + 16384) & 0x3FFFF) >> 4) | (512u << 16);
                wg_fence();
#pragma unroll
                for (int k = 0; k < 4; k++) wg256(acc, da + k * 2, db + k * 128, (kb | k) != 0);
                wg_commit();
                if (kb > 0) {
                    wg_wait<1>();
                    if (lane < 2) mbar_arrive_cluster(empty_dst + prev * 8);
                }
                prev = st;
                if (++st == G_STAGES) { st = 0; ph ^= 1; }
            }
            wg_wait<0>();
            reg_fence<128>(acc);
            if (lane < 2) mbar_arrive_cluster(empty_dst + prev * 8);
            uint32_t o[32];
            if (!dn) {
#pragma unroll
                for (int i = 0; i < 32; i++) o[i] = pack2(sigmoidf_(acc[2 * i]) * acc[64 + 2 * i], sigmoidf_(acc[2 * i + 1]) * acc[65 + 2 * i]);
                put(o);
            } else {
#pragma unroll
                for (int hp = 0; hp < 2; hp++) {
#pragma unroll
                    for (int i = 0; i < 32; i++) {
                        const float a = acc[hp * 64 + 2 * i], b = acc[hp * 64 + 2 * i + 1];
                        o[i] = pack2(sigmoidf_(a) * a, sigmoidf_(b) * b);
                    }
                    put(o);
                }
            }
        }
        bar_sync(3 + cw, 160);
        if (tid == 128) TL(2, 1);
        cluster_sync();
    }
}

constexpr int O_STAGES = 7;
constexpr uint32_t O_STAGE = 32768, O_BAR = O_STAGES * O_STAGE, O_SMEM = O_BAR + 256;

__global__ void __cluster_dims__(2, 1, 1) __launch_bounds__(384, 1)
out_kernel(const __grid_constant__ CUtensorMap tOx, const __grid_constant__ CUtensorMap tWo, const __grid_constant__ CUtensorMap tX,
           const __grid_constant__ CUtensorMap tY, const __grid_constant__ CUtensorMap tOut) {
    extern __shared__ __align__(1024) uint8_t smem[];
    const uint32_t sb = smem_u32(smem);
    const uint32_t full = sb + O_BAR, empty = full + 64;
    const int tid = threadIdx.x, lane = tid & 31;
    const int warp = uni(tid >> 5), wg = warp >> 2;
    const int rank = blockIdx.x & 1, nt = (blockIdx.x >> 1) & 7, rb = (blockIdx.x >> 4) * 2 + rank;
    constexpr int NKB = HD / 64;
    if (tid == 0) {
        TL(3, 0); TLSM(3);
        for (int i = 0; i < O_STAGES; i++) { mbar_init(full + i * 8, 1); mbar_init(empty + i * 8, 16); }
        asm volatile("fence.mbarrier_init.release.cluster;" ::: "memory");
        fence_async();
    }
    __syncthreads();
    cluster_sync();
    if (wg == 0) {
        if (tid == 0) {
            uint32_t st = 0, ph = 1;
            for (int kb = 0; kb < O_STAGES; kb++) {
                mbar_expect(full + kb * 8, O_STAGE);
                tma2d_mc(sb + kb * O_STAGE + 16384 + rank * 8192, &tWo, nt * 128 + rank * 64, kb * 64, full + kb * 8, 3);
            }
            wait_count(CNT_OX + rb, 32);
            TL(3, 2);
            for (int kb = 0; kb < NKB + 2; kb++) {
                const uint32_t base = sb + st * O_STAGE;
                if (kb >= O_STAGES) {
                    mbar_wait(empty + st * 8, ph);
                    mbar_expect(full + st * 8, O_STAGE);
                }
                if (kb < NKB) {
                    tma2d(base, &tOx, kb * 64, rb * 128, full + st * 8);
                    if (kb >= O_STAGES) tma2d_mc(base + 16384 + rank * 8192, &tWo, nt * 128 + rank * 64, kb * 64, full + st * 8, 3);
                } else {
                    if (kb == NKB) wait_count(CNT_Y + rb * 8 + nt, 2);
                    tma2d(base, &tX, nt * 128 + (kb - NKB) * 64, rb * 128, full + st * 8);
                    tma2d(base + 16384, &tY, nt * 128 + (kb - NKB) * 64, rb * 128, full + st * 8);
                }
                if (++st == O_STAGES) { st = 0; ph ^= 1; }
            }
        }
        __syncwarp();
    } else {
        const int cw = wg - 1, w4 = warp & 3;
        const uint32_t empty_dst = mapa(empty, lane & 1);
        const int er = cw * 64 + w4 * 16 + (lane & 15), ec = lane >> 4;
        uint32_t st = 0, ph = 0, prev = 0;
        float acc[64];
#pragma unroll 1
        for (int kb = 0; kb < NKB; kb++) {
            mbar_wait(full + st * 8, ph);
            const uint32_t base = sb + st * O_STAGE;
            const uint32_t da = (((base + cw * 8192) & 0x3FFFF) >> 4) | (1u << 16);
            const uint32_t db = (((base + 16384) & 0x3FFFF) >> 4) | (512u << 16);
            wg_fence();
#pragma unroll
            for (int k = 0; k < 4; k++) wg128(acc, da + k * 2, db + k * 128, (kb | k) != 0);
            wg_commit();
            if (kb > 0) {
                wg_wait<1>();
                if (lane < 2) mbar_arrive_cluster(empty_dst + prev * 8);
            }
            prev = st;
            if (++st == O_STAGES) { st = 0; ph ^= 1; }
        }
        wg_wait<0>();
        reg_fence<64>(acc);
#pragma unroll
        for (int bx = 0; bx < 2; bx++) {
            mbar_wait(full + st * 8, ph);
            const uint32_t base = sb + st * O_STAGE;
#pragma unroll
            for (int j = 0; j < 4; j++) {
                uint32_t xv[4], yv[4];
                const uint32_t ad = base + er * 128 + (((2 * j + ec) ^ (er & 7)) << 4);
                ldsm4(xv, ad); ldsm4(yv, ad + 16384);
                const float* a = acc + bx * 32 + j * 8;
#pragma unroll
                for (int i = 0; i < 4; i++)
                    xv[i] = pack2(fmaf(a[2 * i], bf_lo(yv[i]), bf_lo(xv[i])), fmaf(a[2 * i + 1], bf_hi(yv[i]), bf_hi(xv[i])));
                stsm4(ad, xv[0], xv[1], xv[2], xv[3]);
            }
            fence_async();
            bar_sync(1 + cw, 128);
            if ((tid & 127) == 0) {
                tma2d_store(&tOut, nt * 128 + bx * 64, rb * 128 + cw * 64, base + cw * 8192);
                asm volatile("cp.async.bulk.commit_group;" ::: "memory");
            }
            if (++st == O_STAGES) { st = 0; ph ^= 1; }
        }
        if ((tid & 127) == 0) asm volatile("cp.async.bulk.wait_group 0;" ::: "memory");
        if (tid == 128) TL(3, 1);
        __syncwarp();
    }
    cluster_sync();
}

typedef CUresult (*EncodeFn)(CUtensorMap*, CUtensorMapDataType, cuuint32_t, void*, const cuuint64_t*, const cuuint64_t*, const cuuint32_t*,
                             const cuuint32_t*, CUtensorMapInterleave, CUtensorMapSwizzle, CUtensorMapL2promotion, CUtensorMapFloatOOBfill);

CUtensorMap make_map(EncodeFn enc, const void* p, int rows, int cols, int box_rows) {
    CUtensorMap m;
    cuuint64_t dims[2] = {(cuuint64_t)cols, (cuuint64_t)rows}, strides[1] = {(cuuint64_t)cols * 2};
    cuuint32_t box[2] = {64, (cuuint32_t)box_rows}, es[2] = {1, 1};
    enc(&m, CU_TENSOR_MAP_DATA_TYPE_BFLOAT16, 2, const_cast<void*>(p), dims, strides, box, es, CU_TENSOR_MAP_INTERLEAVE_NONE,
        CU_TENSOR_MAP_SWIZZLE_128B, CU_TENSOR_MAP_L2_PROMOTION_L2_128B, CU_TENSOR_MAP_FLOAT_OOB_FILL_NONE);
    return m;
}

}

#define PDL 7
extern "C" void kernel_launch(void* const* d_in, const int* in_sizes, int n_in, void* d_out, int out_size) {
    const __nv_bfloat16* x = (const __nv_bfloat16*)d_in[0];
    const __nv_bfloat16* mem0 = (const __nv_bfloat16*)d_in[1];
    void* fn = nullptr;
    cudaDriverEntryPointQueryResult qr;
    cudaGetDriverEntryPoint("cuTensorMapEncodeTiled", &fn, cudaEnableDefault, &qr);
    EncodeFn enc = (EncodeFn)fn;
    void *xn, *ox, *h, *y;
    cudaGetSymbolAddress(&xn, g_xn); cudaGetSymbolAddress(&ox, g_ox); cudaGetSymbolAddress(&h, g_h); cudaGetSymbolAddress(&y, g_y);

    const CUtensorMap tq = make_map(enc, d_in[2], DM, HD, 128), tk = make_map(enc, d_in[3], DM, HD, 128), tv = make_map(enc, d_in[4], DM, HD, 128);
    const CUtensorMap two16 = make_map(enc, d_in[5], HD, DM, 16);
    const CUtensorMap txn128 = make_map(enc, xn, SEQ, DM, 128), tg = make_map(enc, d_in[8], DM, FF, 64), tu = make_map(enc, d_in[9], DM, FF, 64);
    const CUtensorMap th64 = make_map(enc, h, SEQ, FF, 64), th128 = make_map(enc, h, SEQ, FF, 128), td = make_map(enc, d_in[10], FF, DM, 64);
    const CUtensorMap ty64 = make_map(enc, y, SEQ, DM, 64), ty128 = make_map(enc, y, SEQ, DM, 128), tx128 = make_map(enc, x, SEQ, DM, 128);
    const CUtensorMap tox = make_map(enc, ox, SEQ, HD, 128), two64 = make_map(enc, d_in[5], HD, DM, 64), tout = make_map(enc, d_out, SEQ, DM, 64);

    cudaFuncSetAttribute(chain_kernel, cudaFuncAttributeMaxDynamicSharedMemorySize, C_SMEM);
    cudaFuncSetAttribute(glu_kernel, cudaFuncAttributeMaxDynamicSharedMemorySize, G_SMEM);
    cudaFuncSetAttribute(out_kernel, cudaFuncAttributeMaxDynamicSharedMemorySize, O_SMEM);

    Descs D;
    for (int i = 0; i < 4; i++) D.sw[i] = DSW;
    D.ns = DNS;
    cudaStream_t st = cudaStreamPerThread;
    cudaLaunchAttribute at;
    at.id = cudaLaunchAttributeProgrammaticStreamSerialization;
    at.val.programmaticStreamSerializationAllowed = 1;
    cudaLaunchConfig_t cfg = {};
    cfg.stream = st; cfg.attrs = &at; cfg.numAttrs = 0;
    cfg.gridDim = dim3(96); cfg.blockDim = dim3(256); cfg.dynamicSmemBytes = C_SMEM;
    cudaLaunchKernelEx(&cfg, chain_kernel, tq, tk, tv, two16, D, D, x, mem0);
    cfg.gridDim = dim3(2 * G_PAIRS); cfg.blockDim = dim3(384); cfg.dynamicSmemBytes = G_SMEM; cfg.numAttrs = (PDL >> 1) & 1;
    cudaLaunchKernelEx(&cfg, glu_kernel, txn128, tg, tu, th64, th128, td, ty64);
    cfg.gridDim = dim3(128); cfg.dynamicSmemBytes = O_SMEM; cfg.numAttrs = (PDL >> 2) & 1;
    cudaLaunchKernelEx(&cfg, out_kernel, tox, two64, tx128, ty128, tout);
}
```

```cpp
#include <cuda_runtime.h>
#include <cuda_bf16.h>
#include <cuda.h>
#include <stdint.h>
#include <type_traits>

namespace {

constexpr int SEQ = 2048, DM = 1024, HD = 4096, FF = 3584, NSEG = 64;

__device__ __align__(1024) __nv_bfloat16 g_xn[SEQ * DM];
__device__ __align__(1024) uint4 g_xc[SEQ * DM / 8];
__device__ __align__(1024) __nv_bfloat16 g_ox[SEQ * HD];
__device__ __align__(1024) __nv_bfloat16 g_h[SEQ * FF];
__device__ __align__(1024) __nv_bfloat16 g_y[SEQ * DM];
__device__ __align__(1024) uint4 g_xmem[4][1024];
__device__ __align__(1024) uint4 g_xo[4][4096];
#define FSTR 8
__device__ __align__(1024) uint32_t g_flag[1][96 * FSTR];
enum { CNT_H = 0, CNT_OX = 16, CNT_Y = 32, CNT_NUM = 160 };
__device__ __align__(1024) uint32_t g_cnt[CNT_NUM * 8];
__device__ __align__(128) uint32_t g_epoch;
#define TL(k, i)
#define TLSM(k)

__device__ __forceinline__ uint32_t smem_u32(const void* p) { return (uint32_t)__cvta_generic_to_shared(p); }
__device__ __forceinline__ uint32_t mapa(uint32_t a, uint32_t r) {
    uint32_t o; asm("mapa.shared::cluster.u32 %0, %1, %2;" : "=r"(o) : "r"(a), "r"(r)); return o;
}
__device__ __forceinline__ void mbar_init(uint32_t a, uint32_t cnt) {
    asm volatile("mbarrier.init.shared.b64 [%0], %1;" :: "r"(a), "r"(cnt) : "memory");
}
__device__ __forceinline__ void mbar_expect(uint32_t a, uint32_t bytes) {
    asm volatile("mbarrier.arrive.expect_tx.shared.b64 _, [%0], %1;" :: "r"(a), "r"(bytes) : "memory");
}
__device__ __forceinline__ void mbar_arrive_cluster(uint32_t a) {
    asm volatile("mbarrier.arrive.shared::cluster.b64 _, [%0];" :: "r"(a) : "memory");
}
__device__ __forceinline__ void spin_guard(uint32_t& it) {
    asm volatile("{\n.reg .pred p;\nadd.u32 %0, %0, 1;\nsetp.gt.u32 p, %0, 0x400000;\n@p st.shared.u32 [%0], %0;\n}" : "+r"(it));
}
__device__ __forceinline__ void mbar_wait(uint32_t a, uint32_t par) {
    asm volatile("{\n.reg .pred p;\nWL:\nmbarrier.try_wait.parity.shared::cta.b64 p, [%0], %1;\n@!p bra WL;\n}" :: "r"(a), "r"(par) : "memory");
}
__device__ __forceinline__ void mbar_arrive(uint32_t a) { asm volatile("mbarrier.arrive.shared.b64 _, [%0];" :: "r"(a) : "memory"); }
__device__ __forceinline__ void tma2d(uint32_t dst, const CUtensorMap* m, int c0, int c1, uint32_t bar) {
    asm volatile("cp.async.bulk.tensor.2d.shared::cluster.global.mbarrier::complete_tx::bytes [%0], [%1, {%3, %4}], [%2];"
                 :: "r"(dst), "l"(m), "r"(bar), "r"(c0), "r"(c1) : "memory");
}
__device__ __forceinline__ void tma2d_mc(uint32_t dst, const CUtensorMap* m, int c0, int c1, uint32_t bar, uint16_t mask) {
    asm volatile("cp.async.bulk.tensor.2d.shared::cluster.global.mbarrier::complete_tx::bytes.multicast::cluster [%0], [%1, {%3, %4}], [%2], %5;"
                 :: "r"(dst), "l"(m), "r"(bar), "r"(c0), "r"(c1), "h"(mask) : "memory");
}
__device__ __forceinline__ void bulk_mc(uint32_t dst, const void* src, uint32_t bytes, uint32_t bar, uint16_t mask) {
    asm volatile("cp.async.bulk.shared::cluster.global.mbarrier::complete_tx::bytes.multicast::cluster [%0], [%1], %2, [%3], %4;"
                 :: "r"(dst), "l"(src), "r"(bytes), "r"(bar), "h"(mask) : "memory");
}
__device__ __forceinline__ void bulk_ld(uint32_t dst, const void* src, uint32_t bytes, uint32_t bar) {
    asm volatile("cp.async.bulk.shared::cluster.global.mbarrier::complete_tx::bytes [%0], [%1], %2, [%3];"
                 :: "r"(dst), "l"(src), "r"(bytes), "r"(bar) : "memory");
}
__device__ __forceinline__ uint32_t gtick() { uint64_t c; asm volatile("mov.u64 %0, %%globaltimer;" : "=l"(c)); return (uint32_t)c >> 5; }
__device__ __forceinline__ uint32_t gtick_dep(uint32_t zero) {
    uint32_t c;
    asm volatile("{\n.reg .pred p;\nsetp.eq.u32 p, %1, 0;\nmov.u32 %0, 0;\n@p mov.u32 %0, %%globaltimer_lo;\n}" : "=r"(c) : "r"(zero));
    return c >> 5;
}
__device__ __forceinline__ uint32_t ld_relaxed1(const void* p) {
    uint32_t v; asm volatile("ld.relaxed.gpu.global.u32 %0, [%1];" : "=r"(v) : "l"(p) : "memory"); return v;
}
__device__ __forceinline__ bool any_nan(float a, float b) {
    uint32_t r;
    asm volatile("{\n.reg .pred p;\nsetp.nan.f32 p, %1, %2;\nvote.sync.any.pred p, p, 0xffffffff;\nselp.u32 %0, 1, 0, p;\n}" : "=r"(r) : "f"(a), "f"(b));
    return r;
}
__device__ __forceinline__ bool bar_sync_any_nan(float a, float b) {
    uint32_t r;
    asm volatile("{\n.reg .pred p;\nsetp.nan.f32 p, %1, %2;\nbarrier.cta.red.or.aligned.pred p, 6, 256, p;\nselp.u32 %0, 1, 0, p;\n}"
                 : "=r"(r) : "f"(a), "f"(b) : "memory");
    return r;
}
__device__ __forceinline__ void bar_arrive(int id, int n) { asm volatile("bar.arrive %0, %1;" :: "r"(id), "r"(n) : "memory"); }
__device__ __forceinline__ uint32_t clk() { uint64_t c; asm volatile("mov.u64 %0, %%clock64;" : "=l"(c)); return (uint32_t)c; }
__device__ __forceinline__ void tma2d_store(const CUtensorMap* m, int c0, int c1, uint32_t src) {
    asm volatile("cp.async.bulk.tensor.2d.global.shared::cta.bulk_group [%0, {%1, %2}], [%3];"
                 :: "l"(m), "r"(c0), "r"(c1), "r"(src) : "memory");
}
__device__ __forceinline__ void bar_sync(int id, int n) { asm volatile("bar.sync %0, %1;" :: "r"(id), "r"(n) : "memory"); }
__device__ __forceinline__ void fence_async() { asm volatile("fence.proxy.async.shared::cta;" ::: "memory"); }
__device__ __forceinline__ void cluster_sync() {
    asm volatile("barrier.cluster.arrive.release.aligned;\nbarrier.cluster.wait.acquire.aligned;" ::: "memory");
}
__device__ __forceinline__ void ldsm4(uint32_t* r, uint32_t a) {
    asm volatile("ldmatrix.sync.aligned.m8n8.x4.shared.b16 {%0,%1,%2,%3}, [%4];"
                 : "=r"(r[0]), "=r"(r[1]), "=r"(r[2]), "=r"(r[3]) : "r"(a) : "memory");
}
__device__ __forceinline__ void ldsm4t(uint32_t* r, uint32_t a) {
    asm volatile("ldmatrix.sync.aligned.m8n8.x4.trans.shared.b16 {%0,%1,%2,%3}, [%4];"
                 : "=r"(r[0]), "=r"(r[1]), "=r"(r[2]), "=r"(r[3]) : "r"(a) : "memory");
}
__device__ __forceinline__ void stsm4(uint32_t a, uint32_t r0, uint32_t r1, uint32_t r2, uint32_t r3) {
    asm volatile("stmatrix.sync.aligned.m8n8.x4.shared.b16 [%0], {%1,%2,%3,%4};" :: "r"(a), "r"(r0), "r"(r1), "r"(r2), "r"(r3) : "memory");
}
__device__ __forceinline__ void stsm4f(uint32_t a, const float* v) {
    asm volatile("{\n.reg .b32 a, b, c, d;\nmov.b32 a, %1;\nmov.b32 b, %2;\nmov.b32 c, %3;\nmov.b32 d, %4;\n"
                 "stmatrix.sync.aligned.m8n8.x4.shared.b16 [%0], {a, b, c, d};\n}" :: "r"(a), "f"(v[0]), "f"(v[1]), "f"(v[2]), "f"(v[3]) : "memory");
}
__device__ __forceinline__ void ldsm4f(float* v, uint32_t a) {
    uint32_t r[4];
    ldsm4(r, a);
#pragma unroll
    for (int i = 0; i < 4; i++) v[i] = __uint_as_float(r[i]);
}
__device__ __forceinline__ void stsm4t(uint32_t a, uint32_t r0, uint32_t r1, uint32_t r2, uint32_t r3) {
    asm volatile("stmatrix.sync.aligned.m8n8.x4.trans.shared.b16 [%0], {%1,%2,%3,%4};" :: "r"(a), "r"(r0), "r"(r1), "r"(r2), "r"(r3) : "memory");
}
__device__ __forceinline__ void stsm2(uint32_t a, uint32_t r0, uint32_t r1) {
    asm volatile("stmatrix.sync.aligned.m8n8.x2.shared.b16 [%0], {%1,%2};" :: "r"(a), "r"(r0), "r"(r1) : "memory");
}
__device__ __forceinline__ void stsm2t(uint32_t a, uint32_t r0, uint32_t r1) {
    asm volatile("stmatrix.sync.aligned.m8n8.x2.trans.shared.b16 [%0], {%1,%2};" :: "r"(a), "r"(r0), "r"(r1) : "memory");
}
__device__ __forceinline__ uint32_t movm(uint32_t a) {
    uint32_t d; asm volatile("movmatrix.sync.aligned.m8n8.trans.b16 %0, %1;" : "=r"(d) : "r"(a)); return d;
}
__device__ __forceinline__ void mma16(float* d, uint32_t a0, uint32_t a1, uint32_t a2, uint32_t a3, uint32_t b0, uint32_t b1) {
    asm volatile("mma.sync.aligned.m16n8k16.row.col.f32.bf16.bf16.f32 {%0,%1,%2,%3}, {%4,%5,%6,%7}, {%8,%9}, {%0,%1,%2,%3};"
                 : "+f"(d[0]), "+f"(d[1]), "+f"(d[2]), "+f"(d[3]) : "r"(a0), "r"(a1), "r"(a2), "r"(a3), "r"(b0), "r"(b1));
}
__device__ __forceinline__ void mma8(float* d, uint32_t a0, uint32_t a1, uint32_t b0) {
    asm volatile("mma.sync.aligned.m16n8k8.row.col.f32.bf16.bf16.f32 {%0,%1,%2,%3}, {%4,%5}, {%6}, {%0,%1,%2,%3};"
                 : "+f"(d[0]), "+f"(d[1]), "+f"(d[2]), "+f"(d[3]) : "r"(a0), "r"(a1), "r"(b0));
}
__device__ __forceinline__ uint32_t pack2(float lo, float hi) {
    uint32_t r; asm("cvt.rn.bf16x2.f32 %0, %1, %2;" : "=r"(r) : "f"(hi), "f"(lo)); return r;
}
__device__ __forceinline__ float bf_lo(uint32_t v) { return __uint_as_float(v << 16); }
__device__ __forceinline__ float bf_hi(uint32_t v) { return __uint_as_float(v & 0xFFFF0000u); }
__device__ __forceinline__ float ex2(float x) { float y; asm("ex2.approx.ftz.f32 %0, %1;" : "=f"(y) : "f"(x)); return y; }
__device__ __forceinline__ float rcp(float x) { float y; asm("rcp.approx.ftz.f32 %0, %1;" : "=f"(y) : "f"(x)); return y; }
__device__ __forceinline__ void sts4f(uint32_t a, float x, float y, float z, float w) {
    asm volatile("st.shared.v4.f32 [%0], {%1,%2,%3,%4};" :: "r"(a), "f"(x), "f"(y), "f"(z), "f"(w) : "memory");
}
__device__ __forceinline__ void sts1u(uint32_t a, uint32_t v) { asm volatile("st.shared.u32 [%0], %1;" :: "r"(a), "r"(v) : "memory"); }
__device__ __forceinline__ void sts4u(uint32_t a, uint4 v) {
    asm volatile("st.shared.v4.u32 [%0], {%1,%2,%3,%4};" :: "r"(a), "r"(v.x), "r"(v.y), "r"(v.z), "r"(v.w) : "memory");
}
__device__ __forceinline__ float4 lds4f(uint32_t a) {
    float4 v; asm volatile("ld.shared.v4.f32 {%0,%1,%2,%3}, [%4];" : "=f"(v.x), "=f"(v.y), "=f"(v.z), "=f"(v.w) : "r"(a) : "memory"); return v;
}
__device__ __forceinline__ float2 lds2f(uint32_t a) {
    float2 v; asm volatile("ld.shared.v2.f32 {%0,%1}, [%2];" : "=f"(v.x), "=f"(v.y) : "r"(a) : "memory"); return v;
}
__device__ __forceinline__ uint4 lds4u(uint32_t a) {
    uint4 v; asm volatile("ld.shared.v4.u32 {%0,%1,%2,%3}, [%4];" : "=r"(v.x), "=r"(v.y), "=r"(v.z), "=r"(v.w) : "r"(a) : "memory"); return v;
}
__device__ __forceinline__ uint32_t lds1u(uint32_t a) {
    uint32_t v; asm volatile("ld.shared.u32 %0, [%1];" : "=r"(v) : "r"(a) : "memory"); return v;
}
__device__ __forceinline__ uint2 lds2u(uint32_t a) {
    uint2 v; asm volatile("ld.shared.v2.u32 {%0,%1}, [%2];" : "=r"(v.x), "=r"(v.y) : "r"(a) : "memory"); return v;
}
__device__ __forceinline__ void st_async4(uint32_t a, uint32_t bar, float x, float y, float z, float w) {
    asm volatile("st.async.shared::cluster.mbarrier::complete_tx::bytes.v4.f32 [%0], {%1,%2,%3,%4}, [%5];"
                 :: "r"(a), "f"(x), "f"(y), "f"(z), "f"(w), "r"(bar) : "memory");
}
__device__ __forceinline__ void st_async2(uint32_t a, uint32_t bar, float x, float y) {
    asm volatile("st.async.shared::cluster.mbarrier::complete_tx::bytes.v2.f32 [%0], {%1,%2}, [%3];"
                 :: "r"(a), "f"(x), "f"(y), "r"(bar) : "memory");
}
template <int OFF>
__device__ __forceinline__ void st_async1f(uint32_t a, uint32_t bar, float x) {
    asm volatile("st.async.shared::cluster.mbarrier::complete_tx::bytes.f32 [%0 + %3], %1, [%2];" :: "r"(a), "f"(x), "r"(bar), "n"(OFF) : "memory");
}
__device__ __forceinline__ uint32_t late_zero() {
    uint64_t c;
    asm volatile("mov.u64 %0, %%clock64;" : "=l"(c));
    return c >> 63;
}
__device__ __forceinline__ void st_async1(uint32_t a, uint32_t bar, uint32_t x) {
    asm volatile("st.async.shared::cluster.mbarrier::complete_tx::bytes.b32 [%0], %1, [%2];" :: "r"(a), "r"(x), "r"(bar) : "memory");
}
__device__ __forceinline__ uint4 ld_relaxed4(const uint4* p) {
    uint4 v;
    asm volatile("ld.relaxed.gpu.global.v4.u32 {%0,%1,%2,%3}, [%4];" : "=r"(v.x), "=r"(v.y), "=r"(v.z), "=r"(v.w) : "l"(p) : "memory");
    return v;
}
__device__ __forceinline__ void st_relaxed4(uint4* p, uint4 v) {
    asm volatile("st.relaxed.gpu.global.v4.u32 [%0], {%1,%2,%3,%4};" :: "l"(p), "r"(v.x), "r"(v.y), "r"(v.z), "r"(v.w) : "memory");
}
__device__ __forceinline__ void count_up(int idx) {
    asm volatile("red.release.gpu.global.add.u32 [%0], 1;" :: "l"(&g_cnt[idx * 8]) : "memory");
}
__device__ __forceinline__ void st_pred1(void* p, uint32_t v, bool on) {
    asm volatile("{\n.reg .pred p;\nsetp.ne.u32 p, %2, 0;\n@p st.relaxed.gpu.global.u32 [%0], %1;\n}" :: "l"(p), "r"(v), "r"((uint32_t)on) : "memory");
}
__device__ __forceinline__ void st_pred4(void* p, uint4 v, bool on) {
    asm volatile("{\n.reg .pred p;\nsetp.ne.u32 p, %5, 0;\n@p st.global.v4.u32 [%0], {%1,%2,%3,%4};\n}"
                 :: "l"(p), "r"(v.x), "r"(v.y), "r"(v.z), "r"(v.w), "r"((uint32_t)on) : "memory");
}
__device__ __forceinline__ void st_relaxed1(void* p, uint32_t v) {
    asm volatile("st.relaxed.gpu.global.u32 [%0], %1;" :: "l"(p), "r"(v) : "memory");
}
__device__ __forceinline__ uint32_t umax4(uint4 v) { return max(max(v.x, v.y), max(v.z, v.w)); }
__device__ __forceinline__ void wg_fence() { asm volatile("wgmma.fence.sync.aligned;" ::: "memory"); }
__device__ __forceinline__ void wg_commit() { asm volatile("wgmma.commit_group.sync.aligned;" ::: "memory"); }
template <int N> __device__ __forceinline__ void wg_wait() { asm volatile("wgmma.wait_group.sync.aligned %0;" :: "n"(N) : "memory"); }
template <int N> __device__ __forceinline__ void reg_fence(float* d) {
#pragma unroll
    for (int i = 0; i < N; i++) asm volatile("" : "+f"(d[i]) :: "memory");
}
#define ACC16(d) "+f"(d[0]), "+f"(d[1]), "+f"(d[2]), "+f"(d[3]), "+f"(d[4]), "+f"(d[5]), "+f"(d[6]), "+f"(d[7]), \
                 "+f"(d[8]), "+f"(d[9]), "+f"(d[10]), "+f"(d[11]), "+f"(d[12]), "+f"(d[13]), "+f"(d[14]), "+f"(d[15])
#define DESC_HI_SW128 "0x40000040"
#define OUT16(d) "=f"(d[0]), "=f"(d[1]), "=f"(d[2]), "=f"(d[3]), "=f"(d[4]), "=f"(d[5]), "=f"(d[6]), "=f"(d[7]), \
                 "=f"(d[8]), "=f"(d[9]), "=f"(d[10]), "=f"(d[11]), "=f"(d[12]), "=f"(d[13]), "=f"(d[14]), "=f"(d[15])
template <int ACCUM, int BOFF>
__device__ __forceinline__ void wg32_rs(float* d, const uint32_t* a, uint64_t dsw) {
    if (ACCUM)
        asm volatile("{\n.reg .b64 db;\nadd.s64 db, %20, %21;\n"
                     "wgmma.mma_async.sync.aligned.m64n32k16.f32.bf16.bf16 {%0,%1,%2,%3,%4,%5,%6,%7,%8,%9,%10,%11,%12,%13,%14,%15}, "
                     "{%16,%17,%18,%19}, db, 1, 1, 1, 0;\n}"
                     : ACC16(d) : "r"(a[0]), "r"(a[1]), "r"(a[2]), "r"(a[3]), "l"(dsw), "n"(BOFF));
    else
        asm volatile("{\n.reg .b64 db;\nadd.s64 db, %20, %21;\n"
                     "wgmma.mma_async.sync.aligned.m64n32k16.f32.bf16.bf16 {%0,%1,%2,%3,%4,%5,%6,%7,%8,%9,%10,%11,%12,%13,%14,%15}, "
                     "{%16,%17,%18,%19}, db, 0, 1, 1, 0;\n}"
                     : OUT16(d) : "r"(a[0]), "r"(a[1]), "r"(a[2]), "r"(a[3]), "l"(dsw), "n"(BOFF));
}
template <int ACCUM, int AOFF, int BOFF>
__device__ __forceinline__ void wg32_ss(float* d, uint64_t dsw) {
    if (ACCUM)
        asm volatile("{\n.reg .b64 da, db;\nadd.s64 da, %16, %17;\nadd.s64 db, %16, %18;\n"
                     "wgmma.mma_async.sync.aligned.m64n32k16.f32.bf16.bf16 {%0,%1,%2,%3,%4,%5,%6,%7,%8,%9,%10,%11,%12,%13,%14,%15}, "
                     "da, db, 1, 1, 1, 1, 0;\n}"
                     : ACC16(d) : "l"(dsw), "n"(AOFF), "n"(BOFF));
    else
        asm volatile("{\n.reg .b64 da, db;\nadd.s64 da, %16, %17;\nadd.s64 db, %16, %18;\n"
                     "wgmma.mma_async.sync.aligned.m64n32k16.f32.bf16.bf16 {%0,%1,%2,%3,%4,%5,%6,%7,%8,%9,%10,%11,%12,%13,%14,%15}, "
                     "da, db, 0, 1, 1, 1, 0;\n}"
                     : OUT16(d) : "l"(dsw), "n"(AOFF), "n"(BOFF));
}
template <int ACCUM, int AOFF, int BOFF>
__device__ __forceinline__ void wg8_ss(float* d, uint64_t dsw, uint64_t dns) {
    if (!ACCUM)
        asm volatile("{\n.reg .b64 da, db;\nadd.s64 da, %4, %6;\nadd.s64 db, %5, %7;\n"
                     "wgmma.mma_async.sync.aligned.m64n8k16.f32.bf16.bf16 {%0,%1,%2,%3}, da, db, 0, 1, 1, 1, 0;\n}"
                     : "=f"(d[0]), "=f"(d[1]), "=f"(d[2]), "=f"(d[3]) : "l"(dsw), "l"(dns), "n"(AOFF), "n"(BOFF));
    else
        asm volatile("{\n.reg .b64 da, db;\nadd.s64 da, %4, %6;\nadd.s64 db, %5, %7;\n"
                     "wgmma.mma_async.sync.aligned.m64n8k16.f32.bf16.bf16 {%0,%1,%2,%3}, da, db, 1, 1, 1, 1, 0;\n}"
                     : "+f"(d[0]), "+f"(d[1]), "+f"(d[2]), "+f"(d[3]) : "l"(dsw), "l"(dns), "n"(AOFF), "n"(BOFF));
}
template <int I0, int I1, class F>
__device__ __forceinline__ void static_for(F&& f) {
    if constexpr (I0 < I1) { f(std::integral_constant<int, I0>{}); static_for<I0 + 1, I1>(f); }
}
template <int I0, int I1, int AOFF, int BOFF>
__device__ __forceinline__ void wg8_chain(float* d, uint64_t dsw, uint64_t dns) {
    wg_fence();
    static_for<I0, I1>([&](auto i) { wg8_ss<i.value != 0, AOFF + i.value * 128, BOFF + i.value * 16>(d, dsw, dns); });
    wg_commit();
}

__device__ __forceinline__ void ln_row(const uint4* v, int row, int lane) {
    float f[32];
#pragma unroll
    for (int j = 0; j < 4; j++) {
        f[j * 8 + 0] = bf_lo(v[j].x); f[j * 8 + 1] = bf_hi(v[j].x); f[j * 8 + 2] = bf_lo(v[j].y); f[j * 8 + 3] = bf_hi(v[j].y);
        f[j * 8 + 4] = bf_lo(v[j].z); f[j * 8 + 5] = bf_hi(v[j].z); f[j * 8 + 6] = bf_lo(v[j].w); f[j * 8 + 7] = bf_hi(v[j].w);
    }
    float s = 0.f;
#pragma unroll
    for (int i = 0; i < 32; i++) s += f[i];
#pragma unroll
    for (int o = 16; o; o >>= 1) s += __shfl_xor_sync(~0u, s, o);
    const float mean = s * (1.f / DM);
    float q = 0.f;
#pragma unroll
    for (int i = 0; i < 32; i++) { f[i] -= mean; q += f[i] * f[i]; }
#pragma unroll
    for (int o = 16; o; o >>= 1) q += __shfl_xor_sync(~0u, q, o);
    const float r = 1.f / sqrtf(q * (1.f / DM) + 1e-5f);
    uint4* dst = reinterpret_cast<uint4*>(g_xn + (size_t)row * DM);
    uint4* dst1 = g_xc + (row >> 5) * 4096 + (lane >> 3) * 256 + (row & 31) * 8 + ((lane & 7) ^ (row & 7));
#pragma unroll
    for (int j = 0; j < 4; j++) {
        const uint4 o = make_uint4(pack2(f[j * 8] * r, f[j * 8 + 1] * r), pack2(f[j * 8 + 2] * r, f[j * 8 + 3] * r),
                                   pack2(f[j * 8 + 4] * r, f[j * 8 + 5] * r), pack2(f[j * 8 + 6] * r, f[j * 8 + 7] * r));
        dst[j * 32 + lane] = o;
        dst1[(j & 1) * 2048 + (j >> 1) * 1024] = o;
    }
}
__device__ __forceinline__ void reset_exchange(const __nv_bfloat16* __restrict__ mem0) {
    const int gi = blockIdx.x * 256 + threadIdx.x;
    const uint4 poison = make_uint4(~0u, ~0u, ~0u, ~0u);
    if (gi < 1024) {
        uint4 m = reinterpret_cast<const uint4*>(mem0)[(gi & 7) * 128 + (gi >> 3)];
        if (m.x == ~0u) m.x = 0x7FFF7FFFu;
        if (m.y == ~0u) m.y = 0x7FFF7FFFu;
        if (m.z == ~0u) m.z = 0x7FFF7FFFu;
        if (m.w == ~0u) m.w = 0x7FFF7FFFu;
        g_xmem[0][gi] = m;
    } else if (gi < 4096) {
        (&g_xmem[0][0])[gi] = poison;
    } else if (gi < 4096 + 16384) {
        (&g_xo[0][0])[gi - 4096] = poison;
    } else if (gi < 4096 + 16384 + 24 * FSTR) {
        reinterpret_cast<uint4*>(&g_flag[0][0])[gi - 4096 - 16384] = poison;
    } else if (gi >= 24576 - CNT_NUM) {
        g_cnt[(24575 - gi) * 8] = 0;
    }
}

#define ONKQ 45
constexpr int ONKV = 128 - 2 * ONKQ;
constexpr uint32_t SB0 = 1024;
constexpr uint32_t C_WS = 0, C_XN = 65536, C_MB = 98304, C_WO = 114688, C_SMEM = 232448;
constexpr uint32_t C_BAR = C_SMEM - 384, C_CAL = C_BAR + 192;
constexpr uint32_t C_SLOTQ = C_WO + ONKQ * 2048, C_QX = C_SLOTQ + 8192, C_KX = C_QX + 4096,
                   C_XSL = C_KX + 4096, C_OL = C_SLOTQ + 4096;
constexpr uint32_t C_SLOTV = C_WO + ONKV * 2048, C_V = C_SLOTV + 8192, C_PL = C_V + 20480, C_SL = C_PL + 4096;
constexpr uint32_t C_DUMP = C_BAR - 512;
static_assert(C_XSL + 5120 <= C_DUMP && C_SL + 2560 <= C_DUMP, "smem overflow");
enum { B_W0 = 0, B_W1, B_W2, B_WS, B_XF0, B_XF1, B_SC, B_P0, B_P1, B_XS, B_OL, B_MF0, B_MF1, B_OF, B_RT0, B_RT1, B_VF, B_MBF, B_GO, B_DUMP, B_NUM };
struct Descs { uint64_t sw[4], ns; };
constexpr uint64_t DSW = 0x4000004000010000ull, DNS = 0x0000001000080000ull;
template <int V> using ic = std::integral_constant<int, V>;
constexpr float SM_SCALE = 0.08838834764831845f * 1.4426950408889634f;

#define TSD(i) do {} while (0)
#define TS_FLUSH(w)
#define TSX(i, c)
#define TS(i)
#define NOFILL 0
#define DLY1 2230
#define DLY2 2450
#define SWAP16 0
#define SSFIRST 1
#define EARLYB 0
#define CANARY ~0u
#define L2POS 10
#define PFX 1
#define C0FIRST 0
#define WOLATE 0
#define QK1 10
#define RFPOS 6
#define STPOS 12
#define OHEAD 8
#define OTAIL 3
#define DLYS 450
#define DLYB 1
#define VLEAD 4

#define VEARLY 8
#define QSPLIT 20
__device__ __forceinline__ bool elect() {
    uint32_t r;
    asm volatile("{\n.reg .pred p;\nelect.sync _|p, 0xffffffff;\nselp.u32 %0, 1, 0, p;\n}" : "=r"(r));
    return r;
}
__device__ __forceinline__ int uni(int v) { return __shfl_sync(~0u, v, 0); }
__device__ __forceinline__ void calibrate(uint32_t cal, float keep) {
    const uint32_t t0 = gtick();
    uint32_t t, it = 0;
    do { t = gtick(); spin_guard(it); } while (__any_sync(~0u, t == t0));
    const uint32_t c = clk();
    const uint4 p = lds4u(cal);
    const float cpt = 256.f * fminf(fmaxf(__fdividef((float)(c - p.y), (float)((t - p.x) & 0x7FFFFFF)), 16.f), 128.f);
    __syncwarp();
    sts4u(cal, make_uint4(t, c, (uint32_t)(keep > 0.f ? fmaf(keep, (float)p.z - cpt, cpt) : cpt), 0));
}
struct Stamps { uint32_t v[6]; };
__device__ __forceinline__ void load_stamps2(Stamps& t, const uint32_t* f, uint32_t l16, bool on = true) {
    const char* p = reinterpret_cast<const char*>(f) + (l16 >> 2) * FSTR;
    asm volatile("{\n.reg .pred p;\nsetp.ne.u32 p, %7, 0;\nmov.u32 %0, 63;\nmov.u32 %1, 63;\nmov.u32 %2, 63;\nmov.u32 %3, 63;\nmov.u32 %4, 63;\nmov.u32 %5, 63;\n"
                 "@p ld.relaxed.gpu.global.v2.u32 {%0, %1}, [%6];\n@p ld.relaxed.gpu.global.v2.u32 {%2, %3}, [%6 + %8];\n"
                 "@p ld.relaxed.gpu.global.v2.u32 {%4, %5}, [%6 + %9];\n}"
                 : "=&r"(t.v[0]), "=&r"(t.v[1]), "=&r"(t.v[2]), "=&r"(t.v[3]), "=&r"(t.v[4]), "=&r"(t.v[5])
                 : "l"(p), "r"((uint32_t)on), "n"(128 * FSTR), "n"(256 * FSTR) : "memory");
}
template <int N>
__device__ __forceinline__ uint32_t stamps_missing(const uint32_t* v, int s) {
    uint32_t x = 0;
#pragma unroll
    for (int i = 0; i < N; i++) x |= v[i] ^ s;
    return x & 63;
}
template <int N>
__device__ __forceinline__ uint32_t latest_stamp(const uint32_t* v, const uint4 cal) {
    int late = (int)(v[0] - (cal.x << 6));
#pragma unroll
    for (int i = 1; i < N; i++) late = max(late, (int)(v[i] - (cal.x << 6)));
    return cal.y + (((late >> 6) * (int)cal.z) >> 8);
}
__device__ __forceinline__ void wait_clock(uint32_t target, uint32_t range = 65536) {
    while (__any_sync(~0u, target - clk() < range)) {}
}

template <int BYTES>
__device__ __forceinline__ bool incomplete(uint32_t buf, uint32_t l16) {
    uint32_t m = 0;
#pragma unroll 1
    for (int o = 0; o < BYTES; o += 256) m = max(m, umax4(lds4u(buf + o + (l16 & 255))));
    return __any_sync(~0u, m == ~0u);
}
__device__ __forceinline__ void refetch(uint32_t buf, const uint4* src, uint32_t bytes, uint32_t b, int w4, int barid, uint32_t& tries) {
    spin_guard(tries);
    bar_sync(barid, 128);
    if (w4 == 0 && elect()) { mbar_expect(b, bytes); bulk_ld(buf, src, bytes, b); }
    __syncwarp();
    mbar_wait(b, 0);
    bar_sync(barid, 128);
    if (w4 == 0 && elect()) mbar_arrive(b);
    __syncwarp();
}

__device__ __forceinline__ void load_box(const CUtensorMap* tA, const CUtensorMap* tB, int cl, int rank, uint32_t dst, int j, int q, uint32_t b) {
    const bool isb = (q ^ (q >> 1)) & 1;
    tma2d(dst + q * 16384, isb ? tB : tA, cl * 256 + (rank >= 4 ? (rank - 4) * 128 + isb * 64 : rank * 64), (q >> 1) * 512 + j * 128, b);
}

template <bool ISV, int WG>
__device__ __forceinline__ void chain_main(const CUtensorMap* tWo, const uint32_t sb, const int cl, const int rank, const Descs& D,
                                           const uint32_t (&wk)[24][4], const uint32_t (&wv)[24][4], uint32_t a_adr) {
    const int tid = threadIdx.x;
    uint32_t l16 = __shfl_sync(~0u, (tid & 31) * 16, tid & 31);
    int w4 = uni((tid >> 5) & 3);
    const int role = ISV ? 2 : (rank & 1), hh = ISV ? rank - 4 : rank >> 1, head = 2 * cl + hh;
    const uint32_t bar = sb + C_BAR;
    constexpr int ONK = ISV ? ONKV : ONKQ;
    const int ostart = (hh * 128 + role * ONKQ);

    if (NOFILL) { for (uint32_t o = C_WO + ONK * 2048 + tid * 16; o < C_BAR; o += 4096) sts4u(sb + o, make_uint4(0, 0, 0, 0)); bar_sync(6, 256); }
    constexpr uint32_t SLOT = ISV ? C_SLOTV : C_SLOTQ;
    constexpr int WS_A = (SB0 + C_WS + WG * 32768) >> 4, WO_A = (SB0 + C_WO) >> 4, MB_A = (SB0 + C_MB) >> 4;
#define XN_A(ks) (int)(((SB0 + C_XN + WG * 16384) >> 4) + ((ks) >> 2) * 256 + ((ks) & 3) * 2)
    const uint32_t slot = (sb + SLOT + w4 * 512), mbw = sb + C_MB + WG * 8192;
    const uint32_t sb_v = (mapa(sb, 4 + hh));
    const uint32_t sb_x = uni(mapa(sb, 2 * hh + (WG ? 1 : (~w4 & 1))));
    const uint32_t sb_o = (mapa(sb, w4));
    const uint32_t u_off = (ISV ? (head * 128 + w4 * 32) * 16 : (cl * 4 + rank) * 256 + (w4 & 1) * 128);
    const uint32_t v_row = (sb + C_V + (2 * WG + (w4 >> 1)) * 512), v_b = ((w4 & 1) * 64);
    const uint32_t u_flag = (blockIdx.x * FSTR);
    const uint32_t f_half = (w4 & 1) * role * (ONKV * 128), f_sb = uni(mapa(sb, rank + (w4 & 1) * (4 + hh - rank)));
    const uint32_t f_src = uni((ostart + (w4 & 1) * (2 - role) * ONKQ) * 256 + f_half), f_dst = uni(f_sb + C_MB + f_half);
    const uint32_t m_dst = (sb + C_MB + role * 8192), m_bar = (bar + (B_MF0 + role) * 8);
    uint32_t target;
    Stamps st1;
    uint4 cal;
    int s = -1;
    uint32_t pf[4][4];
    float xk[16], xv[16];
    float xsc[4];
    uint4 oxp[4];

    auto send_planes = [&](auto n, uint32_t a, int b, const float* v, bool hold) {
        const uint32_t dump = sb + C_DUMP + (l16 >> 2), to = a + (l16 >> 2), ad = hold ? dump : to;
        const uint32_t mb = hold ? (dump & 0xFF000000u) | (SB0 + C_BAR + B_DUMP * 8) : (to & 0xFF000000u) | (SB0 + C_BAR + b * 8);
        static_for<0, n.value>([&](auto i) { st_async1f<i.value * 128>(ad, mb, v[i.value]); });
    };
    auto send_scores = [&]() {
        bar_sync(12, 256);
        if (!NOFILL) send_planes(ic<4>{}, sb_x + C_XSL + role * 2560 + (1 + w4) * 512, B_XS, xsc, s < 0);
    };
    auto store_ox = [&](int ss) {
        char* orow = reinterpret_cast<char*>(g_ox) + (ss * (32 * HD * 2) + (u_off >> 3) + (l16 >> 6) * (HD * 2) + (l16 & 48));
#pragma unroll
        for (int i = 0; i < 4; i++) st_pred4(orow + i * (8 * HD * 2), oxp[i], ss >= 0);
    };
    auto load_tokens = [&](int seg, int wina, int g) {
        const int khalf = ISV ? 1 - wina : wina;
        if (!NOFILL && elect()) {
            mbar_expect(bar + (B_XF0 + g) * 8, 16384);
            bulk_ld(sb + C_XN + g * 16384, g_xc + (seg * 4 + khalf * 2 + g) * 1024, 16384, bar + (B_XF0 + g) * 8);
        }
        __syncwarp();
    };
    auto prefetch = [&]() {
#pragma unroll
        for (int i = 0; i < 4; i++) ldsm4t(pf[i], a_adr + C_WS + (i & 1) * 16384 + (i >> 1) * 2048);
    };
    constexpr int HA = ISV ? 0 : 1, NK1 = ISV ? 0 : QK1;
    auto products = [&](auto give, auto half, auto init, auto i0, auto i1, const uint64_t d) {
        static_for<i0.value, i1.value>([&](auto i) {
            constexpr int ks = half.value * 16 + i.value, acc = !(init.value && i.value == i0.value);
            if constexpr (ks >= 24) wg32_ss<acc, WS_A + give.value * 1024 + (ks - 24) * 128, XN_A(i.value)>(give.value ? xv : xk, d);
            else if constexpr (give.value) wg32_rs<acc, XN_A(i.value)>(xv, wv[ks], d);
            else wg32_rs<acc, XN_A(i.value)>(xk, wk[ks], d);
        });
    };
    auto stream_a = [&](const uint64_t dk, const uint64_t dv, auto mid) {
        if (NOFILL) { mid(); return; }
        constexpr int F = (WG == 0 && SSFIRST) ? 8 : 0;
        wg_fence();
        products(ic<0>{}, ic<HA>{}, ic<1>{}, ic<F>{}, ic<F + 8>{}, dk);
        products(ic<1>{}, ic<HA>{}, ic<1>{}, ic<F>{}, ic<F + 8>{}, dv);
        products(ic<1>{}, ic<HA>{}, ic<0>{}, ic<8 - F>{}, ic<16 - F>{}, dv);
        mid();
        products(ic<0>{}, ic<HA>{}, ic<0>{}, ic<8 - F>{}, ic<16 - F>{}, dk);
        wg_commit();
    };
    auto token_softmax = [&]() {
        const int hi = w4 - 2, lane = l16 >> 4;
        const uint32_t src = sb + C_XSL + hi * 256 + (l16 & 255) + (l16 >> 8) * 2560;
        const int d0 = 16 * role + 8 * hi + (lane >> 2) - 2 * (lane & 3);
        mbar_wait(bar + B_XS * 8, s & 1);
        float e[10];
        float m = -INFINITY;
#pragma unroll
        for (int i = 0; i < 5; i++) {
            __syncwarp();
            float a[4];
            ldsm4f(a, src + i * 512);
            e[2 * i] = (i == 0 || d0 >= 8 * (i - 1)) ? a[0] + a[2] : -INFINITY;
            e[2 * i + 1] = (i == 0 || d0 > 8 * (i - 1)) ? a[1] + a[3] : -INFINITY;
            m = fmaxf(m, fmaxf(e[2 * i], e[2 * i + 1]));
        }
        m = fmaxf(m, __shfl_xor_sync(~0u, m, 1));
        m = fmaxf(m, __shfl_xor_sync(~0u, m, 2));
        m *= -SM_SCALE;
        float l = 0.f;
#pragma unroll
        for (int i = 0; i < 10; i++) { e[i] = ex2(fmaf(e[i], SM_SCALE, m)); l += e[i]; }
        l += __shfl_xor_sync(~0u, l, 1);
        l += __shfl_xor_sync(~0u, l, 2);
        l = rcp(l);
        const uint32_t pd = sb_v + C_PL + (s & 1) * 2048 + role * 768 + hi * 128 + (l16 >> 2), pb = sb_v + C_BAR + (B_P0 + (s & 1)) * 8;
        st_async1(pd, pb, pack2(e[0] * l, e[1] * l));
        st_async1(pd + 256, pb, pack2(e[2] * l, e[3] * l));
        st_async1(pd + 512, pb, pack2(e[4] * l, e[5] * l));
        if (role) {
            st_async1(pd + 768, pb, pack2(e[6] * l, e[7] * l));
            st_async1(pd + 1024, pb, pack2(e[8] * l, e[9] * l));
        }
        if (hi == 0 && l16 == 0) mbar_expect(bar + B_XS * 8, 3072 + role * 2048);
        __syncwarp();
    };

    auto windows = [&]() {
        asm volatile("" : "+r"(l16), "+r"(w4));
        const uint64_t* const dd = D.sw;
        TS(5);
        if constexpr (WG == 1) {
            TS(6);
            if (ISV) bar_sync(3, 256); else send_scores();
            uint32_t missing;
            stream_a(dd[0], dd[1], [&]() {
                if (ISV) return;
                __syncwarp();
                const uint32_t zero = late_zero();
                uint4 cz = cal;
                cz.x += zero;
                missing = stamps_missing<6>(st1.v, s + zero);
                target = latest_stamp<6>(st1.v, cz) + DLY1;
                asm volatile("" : "+r"(missing), "+r"(target));
            });
            if (!NOFILL) bar_arrive(7, 256);
            if (ISV) {
                if (!NOFILL) store_ox(s - 1);
                st_relaxed4(reinterpret_cast<uint4*>(reinterpret_cast<char*>(&g_xo[(s + 2) & 3][0]) + (u_off + l16)), make_uint4(~0u, ~0u, ~0u, ~0u));
            }
            auto fetch_o = [&]() {
            if (!ISV && w4 < 2 && s >= 0) {
                const char* src = reinterpret_cast<const char*>(&g_xo[s & 3][0]) + f_src;
                if (__builtin_expect(__any_sync(~0u, missing), 0)) {
                    uint32_t it = 0;
                    do { load_stamps2(st1, g_flag[0], l16); spin_guard(it); } while (__any_sync(~0u, stamps_missing<6>(st1.v, s)));
                    target = latest_stamp<6>(st1.v, lds4u(sb + C_CAL)) + DLY1;
                }
                mbar_wait(bar + B_VF * 8, s & 1);
                TS(10);
                wait_clock(target);
                if (elect()) bulk_ld(f_dst, src, ONKQ * 256 - w4 * (ONKQ * 256 - ONKV * 128), f_sb + C_BAR + B_OF * 8);
                __syncwarp();
                TS(8);
            }
            };
            if (!EARLYB) fetch_o();
            if (!NOFILL) {
                wg_wait<0>();
                reg_fence<16>(xk); reg_fence<16>(xv);
                if (w4 == 3) { bar_sync(2, 128); load_tokens(s + 1, 0, 1); }
                else bar_arrive(2, 128);
            }
            if (EARLYB) fetch_o();
            TS(7);
        } else {
            if (!NOFILL) {
                mbar_wait(bar + B_XF0 * 8, 0);
                bar_sync(7, 256);
            }
            TS(6);
            stream_a(dd[0], dd[1], []() {});
        }
        if constexpr (WG == 0) {
            if (s >= 0) {
                const uint32_t dst = sb_o + C_OL + rank * 512;
                uint32_t can = sb + C_MB + l16 * 8 + (l16 >> 2), can2 = can + (l16 < (ONK * 2 - 64) * 16 ? 8192 : 0);
                asm volatile("" : "+r"(can), "+r"(can2));
                float co[4];
                TS(7);
                uint32_t tries = 0;
                mbar_wait(bar + B_OF * 8, s & 1);
                TS(8);
                const uint32_t c0 = lds1u(can), c1 = lds1u(can + 4096), c2 = lds1u(can2);
                __syncwarp();
                wg8_chain<0, OHEAD, WO_A, MB_A>(co, D.sw[0], D.ns);
                __syncwarp();
                {
                    const uint32_t z = late_zero();
                    if (__builtin_expect(__any_sync(~0u, max(max(c0 | z, c1 | z), c2) == CANARY), 0)) {
                        wg_wait<0>();
                        do refetch(sb + C_MB, &g_xo[s & 3][ostart * 16], ONK * 256, bar + B_RT0 * 8, w4, 1, tries);
                        while (__any_sync(~0u, max(max(lds1u(can), lds1u(can + 4096)), lds1u(can2)) == CANARY));
                        wg8_chain<0, OHEAD, WO_A, MB_A>(co, DSW, DNS);
                    }
                }
                wg_wait<1>();
                if (l16 == 0) mbar_arrive(bar + B_GO * 8);
                wg8_chain<OHEAD, ONK - OTAIL, WO_A, MB_A>(co, D.sw[0], D.ns);
                static_for<ONK - OTAIL, ONK>([&](auto i) { wg8_ss<1, WO_A + i.value * 128, MB_A + i.value * 16>(co, D.sw[0], D.ns); });
                wg_commit();
                wg_wait<1>();
                bar_arrive(5, 256);
                wg_wait<0>();
                reg_fence<4>(co);
                const bool nan = co[0] != co[0] || co[1] != co[1];
                send_planes(ic<4>{}, dst, B_OL, co, nan);
                if (__builtin_expect(__any_sync(~0u, nan), 0)) {
                    while (incomplete<ONK * 256>(sb + C_MB, l16)) {
                        refetch(sb + C_MB, &g_xo[s & 3][ostart * 16], ONK * 256, bar + B_RT0 * 8, w4, 1, tries);
                        co[0] = co[1] = co[2] = co[3] = 0.f;
#pragma unroll 1
                        for (int i = 0; i < ONK; i++) {
                            wg_fence();
                            wg8_ss<1, WO_A, MB_A>(co, DSW + i * 128, DNS + i * 16);
                            wg_commit();
                            wg_wait<0>();
                        }
                        reg_fence<4>(co);
                    }
                    send_planes(ic<4>{}, dst, B_OL, co, !nan);
                }
                TS(9);
                if (l16 < 48 && w4 == 3) mbar_expect(bar + B_MF0 * 8 + (l16 >> 1), l16 == 32 ? ONK * 256 : 8192);
            } else {
                wg_wait<0>();
                if (l16 == 0) mbar_arrive(bar + B_GO * 8);
                bar_arrive(5, 256);
            }
            if (l16 < 32) mbar_arrive_cluster(mapa(bar + B_MBF * 8, 2 * hh + (l16 >> 4)));
            __syncwarp();
            if (!NOFILL) { reg_fence<16>(xk); reg_fence<16>(xv); }
        } else {
            if (w4 < 2) {
                if (w4 == 1) {
                    mbar_wait(bar + B_GO * 8, (s + 1) & 1);
                    load_tokens(s + 1, 0, 0);
                    if (PFX && ISV && s + 3 < NSEG && elect())
                        asm volatile("cp.async.bulk.prefetch.L2.global [%0], 8192;" :: "l"(g_xc + (s + 3) * 4096 + ((cl & 3) * 2 + hh) * 512) : "memory");
                    __syncwarp();
                } else if (!ISV) {
                    calibrate(sb + C_CAL, 0.75f);
                }
                if (!ISV) st_relaxed1(reinterpret_cast<char*>(&g_xmem[(s + 3) & 3][0]) + (u_off + (l16 >> 2)), ~0u);
            } else if (!NOFILL && s >= 0) {
                if (ISV && w4 == 2 && (s & 3) == 1 && s > 1 && l16 == 0) count_up(CNT_OX + (s >> 2) - 1);
                __syncwarp();
                if (!ISV) token_softmax();
                TSX(9, w4 == 2);
            }
            if (!NOFILL) mbar_wait(bar + B_XF1 * 8, 1);
            bar_sync(5, 256);
        }
        asm volatile("" : "+r"(l16), "+r"(w4));
        TSX(11, w4 == 0 && (WG || ISV));
        uint32_t v_dst = ISV ? v_row + ((s + 1) & 1) * 10240 + ((l16 & 384) << 4) + ((l16 & 96) << 2) + ((l16 & 112) ^ v_b)
                             : sb + C_QX + WG * 4096 + w4 * 1024 + l16;
        uint32_t v_dst2 = v_dst ^ 32;
        if (WG == 0) {
            v_dst = __shfl_sync(~0u, v_dst, l16 >> 4);
            if (ISV) v_dst2 = __shfl_sync(~0u, v_dst2, l16 >> 4);
        }
        constexpr int NR = SWAP16 ? 2 : 4;
        constexpr uint32_t OUT = SWAP16 ? WG * 4096 : 0, IN = SWAP16 ? (WG ^ 1) * 4096 : 0;
        auto give = [&]() {
#pragma unroll
            for (int j = 0; j < NR; j++) {
                if (SWAP16) stsm4(slot + OUT + l16 + j * 2048, pack2(xv[8 * j], xv[8 * j + 1]), pack2(xv[8 * j + 2], xv[8 * j + 3]),
                                  pack2(xv[8 * j + 4], xv[8 * j + 5]), pack2(xv[8 * j + 6], xv[8 * j + 7]));
                else stsm4f(slot + l16 + j * 2048, xv + 4 * j);
            }
        };
        auto take = [&](uint32_t (*r)[4]) {
#pragma unroll
            for (int j = 0; j < NR; j++) ldsm4(r[j], slot + IN + l16 + j * 2048);
        };
        auto store_tokens = [&](const uint32_t (*r)[4]) {
            uint32_t lo[4], hi[4];
#pragma unroll
            for (int j = 0; j < 4; j++) {
                if (SWAP16) {
                    const uint32_t a = r[j >> 1][(j & 1) * 2], b = r[j >> 1][(j & 1) * 2 + 1];
                    lo[j] = pack2(xk[4 * j] + bf_lo(a), xk[4 * j + 1] + bf_hi(a));
                    hi[j] = pack2(xk[4 * j + 2] + bf_lo(b), xk[4 * j + 3] + bf_hi(b));
                } else {
                    lo[j] = pack2(xk[4 * j] + __uint_as_float(r[j % NR][0]), xk[4 * j + 1] + __uint_as_float(r[j % NR][1]));
                    hi[j] = pack2(xk[4 * j + 2] + __uint_as_float(r[j % NR][2]), xk[4 * j + 3] + __uint_as_float(r[j % NR][3]));
                }
            }
            if (!ISV) {
                stsm4t(v_dst, lo[0], lo[1], lo[2], lo[3]);
                stsm4t(v_dst + 512, hi[0], hi[1], hi[2], hi[3]);
            } else {
                stsm4(v_dst, lo[0], lo[1], lo[2], lo[3]);
                stsm4(v_dst2, hi[0], hi[1], hi[2], hi[3]);
            }
        };
        if constexpr (WG == 1) {
            if (!NOFILL) {
                wg_fence();
                products(ic<1>{}, ic<1 - HA>{}, ic<0>{}, ic<0>{}, ic<16>{}, dd[3]);
                products(ic<0>{}, ic<1 - HA>{}, ic<0>{}, ic<0>{}, ic<NK1>{}, dd[2]);
                wg_commit();
                if (ISV) {
                    bar_arrive(7, 256);
                } else {
                    mbar_wait(bar + B_MBF * 8, (s + 1) & 1);
                    bar_sync(7, 256);
                }
                wg_wait<0>();
                reg_fence<16>(xv); reg_fence<16>(xk);
                give();
                bar_arrive(8, 256);
            }
            TS(12);
            prefetch();
            if (!ISV && w4 == 0) {
                const uint4* src = &g_xmem[(s + 1) & 3][role * 512];
                if (NOFILL) mbar_wait(bar + B_MBF * 8, (s + 1) & 1);
                TS(3);
                wait_clock(target + DLY2, s >= 0 ? 65536 : 0);
                if (hh) { if (elect()) bulk_mc(m_dst, src, 8192, m_bar, 0x2C); }
                else if (elect()) bulk_mc(m_dst, src, 8192, m_bar, 0x13);
                __syncwarp();
                TS(4);
            }
            if (!NOFILL) {
                bar_sync(9, 256);
                uint32_t r[NR][4];
                take(r);
                bar_sync(14, 256);
                wg_fence();
                products(ic<0>{}, ic<1 - HA>{}, ic<0>{}, ic<NK1>{}, ic<16>{}, dd[2]);
                wg_commit();
                wg_wait<0>();
                reg_fence<16>(xk);
                TS(13);
                store_tokens(r);
                bar_arrive(10, 256);
                if (w4 != 3) bar_arrive(13, 128);
            }
        } else {
            uint32_t r[NR][4];
            if (!NOFILL) mbar_wait(bar + B_XF0 * 8, 1);
            if (!ISV && w4 < 2 && s >= 0) {
                char* gd = reinterpret_cast<char*>(&g_xmem[(s + 1) & 3][0]) + (u_off + (l16 >> 2));
                const uint32_t src = sb + C_OL + w4 * 256 + l16 + (l16 & 256);
                mbar_wait(bar + B_OL * 8, s & 1);
                TSD(3);
                float a[3][4];
#pragma unroll
                for (int i = 0; i < 3; i++) ldsm4f(a[i], src + i * 1024);
                st_relaxed1(gd, movm(pack2((a[0][0] + a[0][2]) + (a[1][0] + a[1][2]) + (a[2][0] + a[2][2]),
                                           (a[0][1] + a[0][3]) + (a[1][1] + a[1][3]) + (a[2][1] + a[2][3]))));
                TS(11);
                if (w4 == 0 && l16 == 0) mbar_expect(bar + B_OL * 8, 3072);
                __syncwarp();
            }
            if (!NOFILL) {
                bar_sync(7, 256);
                TS(12);
                wg_fence();
                products(ic<1>{}, ic<1 - HA>{}, ic<0>{}, ic<0>{}, ic<16>{}, dd[3]);
                wg_commit();
                products(ic<0>{}, ic<1 - HA>{}, ic<0>{}, ic<0>{}, ic<6>{}, dd[2]);
                wg_commit();
                bar_sync(8, 256);
                take(r);
                wg_wait<1>();
                reg_fence<16>(xv);
                give();
                bar_arrive(9, 256);
                products(ic<0>{}, ic<1 - HA>{}, ic<0>{}, ic<6>{}, ic<16>{}, dd[2]);
                wg_commit();
                bar_arrive(14, 256);
                wg_wait<0>();
                reg_fence<16>(xk);
            }
            TS(13);
            if (!NOFILL) store_tokens(r);
            prefetch();
        }
    };

    if (tid == 0) TL(1, 2);
    if (w4 == 0) load_tokens(0, 1, WG);
    if (WG == 0) {
        if (WOLATE && !NOFILL) mbar_wait(bar + B_XF0 * 8, 0);
        if (elect()) {
#pragma unroll 1
            for (int i = w4; i < ONK; i += 4) tma2d(sb + C_WO + i * 2048, tWo, cl * 64, (ostart + i) * 16, bar + B_OF * 8);
        }
        __syncwarp();
    }
    mbar_wait(bar + B_WS * 8, 0);
    if (WG == 1 && !NOFILL) mbar_wait(bar + B_XF1 * 8, 0);
    if (WG == 0) bar_arrive(ISV ? 3 : 12, 256);
    xsc[0] = xsc[1] = xsc[2] = xsc[3] = 0.f;
    load_stamps2(st1, g_flag[0], l16, false);
    cal = make_uint4(0, 0, 0, 0);
    oxp[0] = oxp[1] = oxp[2] = oxp[3] = make_uint4(0, 0, 0, 0);

#pragma unroll 1
    while (true) {
        windows();
        s++;

        asm volatile("" : "+r"(l16), "+r"(a_adr), "+r"(w4));
        TS_FLUSH(WG);
        TS(0);
        float ck[4], cv[4], dk[4], dv[4];
        uint32_t b[3][4], tries = 0;
        const uint32_t kl = sb + C_KX + ((l16 & 384) << 2) + (l16 & 112);
        auto load_b = [&](auto kp) { ldsm4(b[kp.value % 3], mbw + l16 + ((kp.value & 3) ? (kp.value >> 2) * 3 + (kp.value & 3) - 1 : 12 + (kp.value >> 2)) * 512); };
        auto kpair = [&](auto kp_) {
            constexpr int kp = kp_.value, grp = kp >> 2, ph = kp & 3;
            if constexpr (kp > 0 && kp < 14) load_b(ic<kp + 2>{});
            const uint32_t* bb = b[kp % 3];
            if constexpr (ph != 0) {
                constexpr int q = (grp * 3 + ph - 1) * 2;
                static_for<(ph == 1 ? 0 : ph), ph + 1>([&](auto i) {
                    if constexpr (grp < 3) ldsm4t(pf[i.value], a_adr + C_WS + (i.value & 1) * 16384 + (grp * 2 + 2 + (i.value >> 1)) * 2048);
                });
                __syncwarp();
                mma16(cv, wv[q][0], wv[q][1], wv[q][2], wv[q][3], bb[0], bb[1]);
                mma16(ck, wk[q][0], wk[q][1], wk[q][2], wk[q][3], bb[0], bb[1]);
                mma16(dv, wv[q + 1][0], wv[q + 1][1], wv[q + 1][2], wv[q + 1][3], bb[2], bb[3]);
                mma16(dk, wk[q + 1][0], wk[q + 1][1], wk[q + 1][2], wk[q + 1][3], bb[2], bb[3]);
            } else {
                if constexpr (kp == 0) {
#pragma unroll
                    for (int i = 0; i < 4; i++) ck[i] = cv[i] = dk[i] = dv[i] = 0.f;
                }
                mma16(ck, pf[0][0], pf[0][1], pf[0][2], pf[0][3], bb[0], bb[1]);
                mma16(cv, pf[1][0], pf[1][1], pf[1][2], pf[1][3], bb[0], bb[1]);
                mma16(dk, pf[2][0], pf[2][1], pf[2][2], pf[2][3], bb[2], bb[3]);
                mma16(dv, pf[3][0], pf[3][1], pf[3][2], pf[3][3], bb[2], bb[3]);
            }
        };
        auto hand_over = [&]() {
#pragma unroll
            for (int i = 0; i < 4; i++) { cv[i] += dv[i]; ck[i] += dk[i]; }
            if (ISV) {
                stsm4f(slot + WG * 2048 + l16, cv);
            } else {
                const float *q = WG ? cv : ck, *k = WG ? ck : cv;
                stsm4t(slot + WG * 2048 + l16, pack2(q[0], q[1]), pack2(q[2], q[3]), pack2(k[0], k[1]), pack2(k[2], k[3]));
            }
        };
        auto repair = [&]() {
            bar_sync(6, 256);
            while (incomplete<8192>(mbw, l16)) {
                refetch(mbw, &g_xmem[s & 3][WG * 512], 8192, bar + (B_RT0 + WG) * 8, w4, 1 + WG, tries);
                prefetch();
                static_for<0, 3>(load_b);
                static_for<0, 16>(kpair);
                hand_over();
            }
            bar_sync(6, 256);
        };
        {
            const uint32_t can = mbw + l16 * 8 + (l16 >> 2);
            uint32_t* const flag = &g_flag[0][u_flag + WG + l16];
            for (;; tries |= 1) {
                asm volatile("" : "+r"(tries));
                if (__builtin_expect(tries, 0)) {
                    refetch(mbw, &g_xmem[s & 3][WG * 512], 8192, bar + (B_RT0 + WG) * 8, w4, 1 + WG, tries);
                }
                mbar_wait(bar + (B_MF0 + WG) * 8, s & 1);
                TS(1);
                static_for<0, 3>(load_b);
                const uint32_t c0 = lds1u(can), c1 = lds1u(can + 4096);
                const uint32_t v = ((gtick() - (ISV ? VLEAD : 0)) << 6) | s;
                kpair(ic<0>{});
                const bool early = __any_sync(~0u, max(c0, c1) == CANARY);
                st_pred1(flag, v, w4 * 512 + l16 == 1536 && !early);
                if (__builtin_expect(!early, 1)) break;
            }
            static_for<1, RFPOS>(kpair);
            if (WG == 0 && !NOFILL) bar_sync(10, 256);
            if (WG == 1 && !NOFILL && w4 == 3) {
                bar_sync(13, 128);
                if (s < NSEG - 1) load_tokens(s + 1, 1, 1);
            }
            static_for<RFPOS, 13>(kpair);
        }
        auto finish_projections = [&]() {
            static_for<13, 16>(kpair);
            hand_over();
            TS(2);
            return bar_sync_any_nan(cv[0], cv[1]);
        };
        if constexpr (!ISV) {
            const uint32_t qa = sb + C_SLOTQ + ((l16 >> 1) & 128) + ((l16 & 128) << 3) + (l16 & 112);
            const uint32_t ma = sb + C_SLOTQ + 256 + l16 + (l16 & 256);
            const uint32_t qx = sb + C_QX + l16 + (l16 & 256);
            auto ldsm_sum = [&](uint32_t* r, uint32_t a) {
                uint32_t t[4];
                ldsm4(r, a); ldsm4(t, a + 2048);
#pragma unroll
                for (int i = 0; i < 4; i++) asm("add.rn.bf16x2 %0, %0, %1;" : "+r"(r[i]) : "r"(t[i]));
            };
            auto tile = [&](float* d, const uint32_t (*q)[4], const uint32_t (*k)[4]) {
                d[0] = d[1] = d[2] = d[3] = 0.f;
#pragma unroll
                for (int i = 0; i < 4; i++) mma16(d, q[i][0], q[i][1], q[i][2], q[i][3], k[i >> 1][(i & 1) * 2], k[i >> 1][(i & 1) * 2 + 1]);
            };
            auto send = [&](int ti, const float* d, bool hold) {
                send_planes(ic<4>{}, sb_x + C_XSL + role * 2560 + ti * 512, B_XS, d, hold);
            };
            if constexpr (WG == 0) {
                auto scores = [&](auto again) {
                    bool nan = false;
                    if (w4 < 2) {
                        uint32_t k0[2][4], k1[2][4], q0[4], q1[4];
                        const uint32_t ka = kl + w4 * 256, dst = sb_v + C_SL + role * 1024 + w4 * 512;
                        ldsm4(k0[0], ka); ldsm4(k0[1], ka + 2048);
                        ldsm4(k1[0], ka + 128); ldsm4(k1[1], ka + 128 + 2048);
                        __syncwarp();
                        if (!again.value) nan = finish_projections();
                        TS(3);
                        ldsm_sum(q0, qa); ldsm_sum(q1, qa + 512);
                        float s0[4] = {0.f, 0.f, 0.f, 0.f}, s1[4] = {0.f, 0.f, 0.f, 0.f}, s2[4] = {0.f, 0.f, 0.f, 0.f}, s3[4] = {0.f, 0.f, 0.f, 0.f};
                        mma16(s0, q0[0], q0[1], q0[2], q0[3], k0[0][0], k0[0][1]);
                        mma16(s1, q0[0], q0[1], q0[2], q0[3], k0[1][0], k0[1][1]);
                        mma16(s2, q0[0], q0[1], q0[2], q0[3], k1[0][0], k1[0][1]);
                        mma16(s3, q0[0], q0[1], q0[2], q0[3], k1[1][0], k1[1][1]);
                        mma16(s0, q1[0], q1[1], q1[2], q1[3], k0[0][2], k0[0][3]);
                        mma16(s1, q1[0], q1[1], q1[2], q1[3], k0[1][2], k0[1][3]);
                        mma16(s2, q1[0], q1[1], q1[2], q1[3], k1[0][2], k1[0][3]);
                        mma16(s3, q1[0], q1[1], q1[2], q1[3], k1[1][2], k1[1][3]);
                        const float out[4] = {s0[0] + s1[2], s0[1] + s1[3], s2[0] + s3[2], s2[1] + s3[3]};
                        send_planes(ic<4>{}, dst, B_SC, out, nan);
                        if (!again.value) bar_arrive(12, 256);
                        TS(4);
                    } else if (w4 == 2) {
                        uint32_t q0[4], q1[4], km[2][4], q[4][4];
                        const uint32_t dst = sb_v + C_SL + 2048 + role * 256;
                        if (!again.value) nan = finish_projections();
                        ldsm_sum(q0, qa); ldsm_sum(km[0], ma); ldsm_sum(km[1], ma + 1024); ldsm_sum(q1, qa + 512);
                        __syncwarp();
#pragma unroll
                        for (int i = 0; i < 4; i++) ldsm4(q[i], qx + 256 + i * 1024);
                        float s0[4] = {0.f, 0.f, 0.f, 0.f}, s1[4] = {0.f, 0.f, 0.f, 0.f}, d0[4];
                        mma16(s0, q0[0], q0[1], q0[2], q0[3], km[0][0], km[0][1]);
                        mma16(s1, q0[0], q0[1], q0[2], q0[3], km[1][0], km[1][1]);
                        mma16(s0, q1[0], q1[1], q1[2], q1[3], km[0][2], km[0][3]);
                        mma16(s1, q1[0], q1[1], q1[2], q1[3], km[1][2], km[1][3]);
                        const float out[2] = {s0[0] + s1[2], s0[1] + s1[3]};
                        send_planes(ic<2>{}, dst, B_SC, out, nan);
                        if (!NOFILL) tile(d0, q, km);
                        if (!again.value) bar_sync(12, 256);
                        if (!NOFILL) send(0, d0, nan);
                    } else {
                        if (!again.value) {
                            nan = finish_projections();
                            if (s < NSEG - 1) load_tokens(s + 1, 1, 0);
                        }
                        uint32_t q[4][4], k0[2][4], k1[2][4], km[2][4];
                        float d0[4], d1[4], d2[4];
                        if (!NOFILL) {
#pragma unroll
                            for (int i = 0; i < 4; i++) ldsm4(q[i], qx + i * 1024);
                            ldsm4(k0[0], kl); ldsm4(k0[1], kl + 2048);
                            ldsm4(k1[0], kl + 128); ldsm4(k1[1], kl + 128 + 2048);
                            tile(d1, q, k0); tile(d2, q, k1);
                            ldsm_sum(km[0], ma); ldsm_sum(km[1], ma + 1024);
                            tile(d0, q, km);
                        }
                        if (!again.value) bar_sync(12, 256);
                        if (!NOFILL) { send(0, d0, nan); send(1, d1, nan); send(2, d2, nan); }
                    }
                    return nan;
                };
                if (__builtin_expect(__any_sync(~0u, scores(ic<0>{})), 0)) { repair(); scores(ic<1>{}); bar_arrive(12, 256); }
                if (__builtin_expect(s == NSEG - 1, 0)) break;
            } else {
                const bool nan = finish_projections();
                load_stamps2(st1, g_flag[0], l16, w4 < 2);
                if (!NOFILL) mbar_wait(bar + B_XF1 * 8, s == NSEG - 1);
                cal = lds4u(sb + C_CAL);
                if (!NOFILL) {
                    uint32_t q[4][4], k0[2][4];
                    float d1[4] = {0.f, 0.f, 0.f, 0.f};
#pragma unroll
                    for (int i = 0; i < 4; i++) { ldsm4(q[i], qx + 256 + i * 1024); xsc[i] = 0.f; }
                    ldsm4(k0[0], kl + w4 * 128); ldsm4(k0[1], kl + w4 * 128 + 2048);
#pragma unroll
                    for (int i = 0; i < 4; i++) mma16((i & 1) ? d1 : xsc, q[i][0], q[i][1], q[i][2], q[i][3], k0[i >> 1][(i & 1) * 2], k0[i >> 1][(i & 1) * 2 + 1]);
#pragma unroll
                    for (int i = 0; i < 4; i++) xsc[i] += d1[i];
                }
                if (__builtin_expect(__any_sync(~0u, nan), 0)) {
                    bar_sync(12, 256);
                    repair();
                    load_stamps2(st1, g_flag[0], l16, false);
                    cal = lds4u(sb + C_CAL);
                }
                if (__builtin_expect(s == NSEG - 1, 0)) {
                    asm volatile("" : "+r"(l16));
                    send_scores();
                    if (w4 >= 2 && !NOFILL) token_softmax();
                    break;
                }
            }
        } else {
            const uint32_t lane_b = sb + C_V + w4 * 512 + ((l16 & 384) << 4) + (l16 & 112);
            auto load_vx = [&](uint32_t (*vx)[4], int ss) {
#pragma unroll
                for (int j = 0; j < 4; j++) ldsm4(vx[j], ((lane_b + (ss & 1) * 10240) ^ (j * 32)) + j * 128);
            };
            auto load_vm = [&](uint32_t* vm, int ss) { ldsm4(vm, sb + C_V + (ss & 1) * 10240 + w4 * 512 + 8192 + (l16 ^ ((l16 >> 2) & 96))); };
            auto token_output = [&](int ss) {
                uint32_t vx[4][4], vm[4];
                const uint32_t pl = sb + C_PL + (ss & 1) * 2048 + l16;
                auto lds_frag = [&](uint32_t a) { uint32_t r[4]; ldsm4(r, a); return make_uint4(r[0], r[1], r[2], r[3]); };
                load_vm(vm, ss);
                load_vx(vx, ss);
                mbar_wait(bar + (B_P0 + (ss & 1)) * 8, (ss >> 1) & 1);
                uint32_t dep = 0;
#pragma unroll
                for (int mh = 1; mh >= 0; mh--) {
                    uint2 pm;
                    asm volatile("ldmatrix.sync.aligned.m8n8.x2.shared.b16 {%0,%1}, [%2];" : "=r"(pm.x), "=r"(pm.y) : "r"(pl + mh * 768 + dep) : "memory");
                    const uint4 p0 = lds_frag(pl + mh * 768 + 256);
                    float o[4][4];
#pragma unroll
                    for (int j = 0; j < 4; j++) { o[j][0] = o[j][1] = o[j][2] = o[j][3] = 0.f; mma8(o[j], pm.x, pm.y, vm[j]); }
#pragma unroll
                    for (int j = 0; j < 4; j++) mma16(o[j], p0.x, p0.y, p0.z, p0.w, vx[j][0], vx[j][1]);
                    if (mh) {
                        const uint4 p1 = lds_frag(pl + 1536);
#pragma unroll
                        for (int j = 0; j < 4; j++) mma16(o[j], p1.x, p1.y, p1.z, p1.w, vx[j][2], vx[j][3]);
                    }
                    oxp[2 * mh] = make_uint4(pack2(o[0][0], o[0][1]), pack2(o[1][0], o[1][1]), pack2(o[2][0], o[2][1]), pack2(o[3][0], o[3][1]));
                    oxp[2 * mh + 1] = make_uint4(pack2(o[0][2], o[0][3]), pack2(o[1][2], o[1][3]), pack2(o[2][2], o[2][3]), pack2(o[3][2], o[3][3]));
                    asm volatile("" : "+r"(oxp[2 * mh].x), "+r"(oxp[2 * mh].y), "+r"(oxp[2 * mh].z), "+r"(oxp[2 * mh].w),
                                 "+r"(oxp[2 * mh + 1].x), "+r"(oxp[2 * mh + 1].y), "+r"(oxp[2 * mh + 1].z), "+r"(oxp[2 * mh + 1].w));
                    dep = oxp[2].x == ~0u ? 16 : 0;
                }
            };
            const uint32_t vd = v_row + (s & 1) * 10240 + 8192 + ((l16 & 96) << 2) + ((l16 & 112) ^ v_b ^ ((l16 & 128) >> 2));
            uint32_t vx[4][4], vm[4];
            if (WG == 0) { load_vx(vx, s); __syncwarp(); }
            if (__builtin_expect(__any_sync(~0u, finish_projections()), 0)) { repair(); if (WG == 0) load_vx(vx, s); }
            float r[4];
            ldsm4f(r, slot + (WG ^ 1) * 2048 + l16);
            stsm2(vd, pack2(ck[0] + r[0], ck[1] + r[1]), pack2(ck[2] + r[2], ck[3] + r[3]));
            TSX(3, WG == 0 && w4 == 0);
            if (WG == 1) {
                bar_arrive(11, 256);
                if (w4 == 3 && l16 < 32) mbar_arrive_cluster(mapa(bar + B_VF * 8, 2 * hh + (l16 >> 4)));
                if (w4 == 2 && s < NSEG - 1) load_tokens(s + 1, 1, 0);
                if (!NOFILL) {
                    token_output(s - 1);
                    if (w4 == 1 && l16 == 0 && s > 0) mbar_expect(bar + (B_P0 + ((s - 1) & 1)) * 8, 2048);
                    mbar_wait(bar + B_XF1 * 8, s == NSEG - 1);
                }
            }
            if (WG == 0) bar_sync(11, 256);
            if (__builtin_expect(s == NSEG - 1, 0)) {
                bar_sync(6, 256);
                if (WG == 1) {
                    if (!NOFILL) {
                        store_ox(s - 1);
                        token_output(s);
                        store_ox(s);
                    }
                    bar_sync(2, 128);
                    if (w4 == 0 && l16 == 0) {
                        if (NOFILL) for (int i = 0; i < 15; i++) count_up(CNT_OX + i);
                        count_up(CNT_OX + 15);
                    }
                    __syncwarp();
                }
                mbar_wait(bar + B_SC * 8, s & 1);
                break;
            }
            if constexpr (WG == 0) {
                load_vm(vm, s);
                const uint32_t oo = u_off + ((l16 & 48) << 3) + ((l16 >> 2) & 112);
                char* dst = reinterpret_cast<char*>(&g_xo[s & 3][0]) + oo;
                mbar_wait(bar + B_SC * 8, s & 1);
                TS(4);
                float a0[4], b0[4], a1[4], b1[4], a2[4];
                ldsm4f(a0, sb + C_SL + l16); ldsm4f(b0, sb + C_SL + 1024 + l16);
                ldsm4f(a1, sb + C_SL + 512 + l16); ldsm4f(b1, sb + C_SL + 1536 + l16);
                ldsm4f(a2, sb + C_SL + 2048 + l16);
                const float e[10] = {a0[0] + b0[0], a0[1] + b0[1], a0[2] + b0[2], a0[3] + b0[3], a1[0] + b1[0], a1[1] + b1[1], a1[2] + b1[2], a1[3] + b1[3],
                                     a2[0] + a2[2], a2[1] + a2[3]};
                float m = fmaxf(fmaxf(fmaxf(e[0], e[1]), fmaxf(e[2], e[3])), fmaxf(fmaxf(e[4], e[5]), fmaxf(e[6], e[7])));
                m = fmaxf(m, fmaxf(e[8], e[9]));
                m = fmaxf(fmaxf(m, __shfl_xor_sync(~0u, m, 1)), fmaxf(__shfl_xor_sync(~0u, m, 2), __shfl_xor_sync(~0u, m, 3)));
                m *= -SM_SCALE;
                float x[10];
#pragma unroll
                for (int i = 0; i < 10; i++) x[i] = ex2(fmaf(e[i], SM_SCALE, m));
                float o[4][4];
                const uint32_t p0 = pack2(x[0], x[1]), p1 = pack2(x[2], x[3]), j0 = __float_as_uint(x[1]), j1 = __float_as_uint(x[3]);
#pragma unroll
                for (int j = 0; j < 4; j++) { o[j][0] = o[j][1] = o[j][2] = o[j][3] = 0.f; mma16(o[j], p0, j0, p1, j1, vx[j][0], vx[j][1]); }
                const uint32_t p2 = pack2(x[4], x[5]), p3 = pack2(x[6], x[7]), j2 = __float_as_uint(x[5]), j3 = __float_as_uint(x[7]);
#pragma unroll
                for (int j = 0; j < 4; j++) mma16(o[j], p2, j2, p3, j3, vx[j][2], vx[j][3]);
                const uint32_t p4 = pack2(x[8], x[9]), j4 = __float_as_uint(x[9]);
                float l = (((x[0] + x[1]) + (x[2] + x[3])) + ((x[4] + x[5]) + (x[6] + x[7]))) + (x[8] + x[9]);
                l = (l + __shfl_xor_sync(~0u, l, 1)) + (__shfl_xor_sync(~0u, l, 2) + __shfl_xor_sync(~0u, l, 3));
#pragma unroll
                for (int j = 0; j < 4; j++) mma8(o[j], p4, j4, vm[j]);
                l = rcp(l);
                st_relaxed4(reinterpret_cast<uint4*>(dst), make_uint4(pack2(o[0][0] * l, o[0][1] * l), pack2(o[1][0] * l, o[1][1] * l),
                                                                      pack2(o[2][0] * l, o[2][1] * l), pack2(o[3][0] * l, o[3][1] * l)));
                bar_arrive(3, 256);
                if (w4 == 0 && l16 == 0) mbar_expect(bar + B_SC * 8, 2560);
            }
        }
    }
}

__global__ void __cluster_dims__(6, 1, 1) __launch_bounds__(256, 1)
chain_kernel(const __grid_constant__ CUtensorMap tq, const __grid_constant__ CUtensorMap tk, const __grid_constant__ CUtensorMap tv,
             const __grid_constant__ CUtensorMap two, const __grid_constant__ Descs D, const __grid_constant__ Descs DV,
             const __nv_bfloat16* __restrict__ x, const __nv_bfloat16* __restrict__ mem0) {
    extern __shared__ __align__(1024) uint8_t smem[];
    const uint32_t sb = smem_u32(smem);
    const int rank = blockIdx.x % 6, cl = blockIdx.x / 6, role = rank >= 4 ? 2 : rank & 1;
    const int tid = threadIdx.x, lane = tid & 31, gw = blockIdx.x * 8 + uni(tid >> 5);
    const CUtensorMap *tA = role == 2 ? &tv : &tq, *tB = role == 2 ? &tv : &tk;
    uint4 cur[4], nxt[4];
#pragma unroll
    for (int j = 0; j < 4; j++) {
        cur[j] = reinterpret_cast<const uint4*>(x)[gw * 128 + j * 32 + lane];
        nxt[j] = reinterpret_cast<const uint4*>(x)[(gw + 768) * 128 + j * 32 + lane];
    }
    if (gw < 512 && lane < 16) asm volatile("prefetch.global.L2 [%0];" :: "l"(x + (gw + 1536) * DM + lane * 64));
    if ((gw & 7) == 0) {
        if (tid == 0) { TL(1, 0); TLSM(1); }
        if ((sb & 0xFFFFFF) != SB0 || mapa(sb, 5) != (SB0 | 0x5000000u)) sts1u(1, 0);
        const uint32_t b = sb + C_BAR + lane * 8;
        uint32_t tx = 0;
        if (lane <= B_WS) tx = 65536;
        if (lane == B_MF0 || lane == B_MF1) tx = 8192;
        if (lane == B_OF) tx = (role == 2 ? ONKV : ONKQ) * (256 + 2048);
        if (lane == B_SC) tx = 2560;
        if (lane == B_P0 || lane == B_P1) tx = 2048;
        if (lane == B_XS || lane == B_OL) tx = (lane == B_XS && role) ? 5120 : 3072;
        if (lane < B_NUM) mbar_init(b, lane == B_MBF ? 12 : (lane == B_GO ? 4 : 1));
        if (tx) mbar_expect(b, tx);
        asm volatile("fence.mbarrier_init.release.cluster;" ::: "memory");
        fence_async();
        __syncwarp();
#pragma unroll 1
        for (int i = 0; i < 12; i++)
            if (elect()) load_box(tA, tB, cl, rank, sb + (i >> 2) * 65536, i >> 2, i & 3, sb + C_BAR + (i >> 2) * 8);
    }
    reset_exchange(mem0);
    __syncthreads();
    asm volatile("barrier.cluster.arrive.relaxed.aligned;" ::: "memory");
    const int warp = gw & 7, wg = warp >> 2, kr = (lane & 7) + ((lane >> 4) << 3);
    const uint32_t a_adr = __shfl_sync(~0u, sb + wg * 32768 + kr * 128 + ((((warp & 3) * 2 + ((lane >> 3) & 1)) ^ (kr & 7)) << 4), lane);
    uint32_t wk[24][4], wv[24][4], goal = 0;
    auto to_regs = [&](auto j) {
        mbar_wait(sb + C_BAR + (B_W0 + j.value) * 8, 0);
#pragma unroll
        for (int i = 0; i < 8; i++) {
            ldsm4t(wk[j.value * 8 + i], a_adr + j.value * 65536 + i * 2048);
            ldsm4t(wv[j.value * 8 + i], a_adr + j.value * 65536 + 16384 + i * 2048);
        }
    };
    auto first_chunk = [&]() {
        to_regs(ic<0>{});
        __syncthreads();
        if (wg == 0 && elect()) load_box(tA, tB, cl, rank, sb + C_WS, 3, warp, sb + C_BAR + B_WS * 8);
        __syncwarp();
        if (tid == 0) TL(1, 6);
    };
    if (warp == 4) calibrate(sb + C_CAL, 0.f);
    if (C0FIRST) first_chunk();
#pragma unroll 1
    for (int row = gw; row < SEQ; row += 768) {
        uint4 v[4];
#pragma unroll
        for (int j = 0; j < 4; j++) {
            v[j] = cur[j]; cur[j] = nxt[j];
            if (row + 1536 < SEQ) nxt[j] = reinterpret_cast<const uint4*>(x)[(row + 1536) * 128 + j * 32 + lane];
        }
        ln_row(v, row, lane);
    }
    if (tid == 0) TL(1, 5);
    if (C0FIRST) __syncthreads(); else first_chunk();
    if (warp == 5 && elect()) {
        __threadfence();
        goal = (atomicAdd(&g_epoch, 1u) / 96 + 1) * 96;
        asm volatile("griddepcontrol.launch_dependents;" ::: "memory");
        TL(1, 4);
    }
    __syncwarp();
    to_regs(ic<1>{});
    to_regs(ic<2>{});
    if (warp == 5) {
        goal = __reduce_max_sync(~0u, goal);
        uint32_t v, it = 0;
        do {
            asm volatile("ld.acquire.gpu.global.u32 %0, [%1];" : "=r"(v) : "l"(&g_epoch) : "memory");
            spin_guard(it);
        } while (__any_sync(~0u, (int)(v - goal) < 0));
    }
    if (warp == 4) calibrate(sb + C_CAL, 0.f);
    asm volatile("barrier.cluster.wait.aligned;" ::: "memory");
    __syncthreads();
    asm volatile("fence.proxy.async.global;" ::: "memory");
    if (role == 2) {
        if (wg == 0) chain_main<true, 0>(&two, sb, cl, rank, DV, wk, wv, a_adr);
        else chain_main<true, 1>(&two, sb, cl, rank, DV, wk, wv, a_adr);
    } else {
        if (wg == 0) chain_main<false, 0>(&two, sb, cl, rank, D, wk, wv, a_adr);
        else chain_main<false, 1>(&two, sb, cl, rank, D, wk, wv, a_adr);
    }
    __syncwarp();
    cluster_sync();
    if (threadIdx.x == 0) TL(1, 1);
}

__device__ __forceinline__ void wg256(float* d, uint32_t da, uint32_t db, uint32_t accum) {
    asm volatile("{\n.reg .b64 da, db;\n.reg .pred p;\nsetp.ne.u32 p, %130, 0;\nmov.b64 da, {%128, " DESC_HI_SW128 "};\nmov.b64 db, {%129, " DESC_HI_SW128 "};\n"
                 "wgmma.mma_async.sync.aligned.m64n256k16.f32.bf16.bf16 {"
                 "%0,%1,%2,%3,%4,%5,%6,%7,%8,%9,%10,%11,%12,%13,%14,%15,%16,%17,%18,%19,%20,%21,%22,%23,%24,%25,%26,%27,%28,%29,%30,%31,"
                 "%32,%33,%34,%35,%36,%37,%38,%39,%40,%41,%42,%43,%44,%45,%46,%47,%48,%49,%50,%51,%52,%53,%54,%55,%56,%57,%58,%59,%60,%61,%62,%63,"
                 "%64,%65,%66,%67,%68,%69,%70,%71,%72,%73,%74,%75,%76,%77,%78,%79,%80,%81,%82,%83,%84,%85,%86,%87,%88,%89,%90,%91,%92,%93,%94,%95,"
                 "%96,%97,%98,%99,%100,%101,%102,%103,%104,%105,%106,%107,%108,%109,%110,%111,%112,%113,%114,%115,%116,%117,%118,%119,%120,%121,%122,%123,%124,%125,%126,%127"
                 "}, da, db, p, 1, 1, 0, 1;\n}"
                 : ACC16(d), ACC16((d + 16)), ACC16((d + 32)), ACC16((d + 48)), ACC16((d + 64)), ACC16((d + 80)), ACC16((d + 96)), ACC16((d + 112))
                 : "r"(da), "r"(db), "r"(accum));
}
__device__ __forceinline__ void wg128(float* d, uint32_t da, uint32_t db, uint32_t accum) {
    asm volatile("{\n.reg .b64 da, db;\n.reg .pred p;\nsetp.ne.u32 p, %66, 0;\nmov.b64 da, {%64, " DESC_HI_SW128 "};\nmov.b64 db, {%65, " DESC_HI_SW128 "};\n"
                 "wgmma.mma_async.sync.aligned.m64n128k16.f32.bf16.bf16 {"
                 "%0,%1,%2,%3,%4,%5,%6,%7,%8,%9,%10,%11,%12,%13,%14,%15,%16,%17,%18,%19,%20,%21,%22,%23,%24,%25,%26,%27,%28,%29,%30,%31,"
                 "%32,%33,%34,%35,%36,%37,%38,%39,%40,%41,%42,%43,%44,%45,%46,%47,%48,%49,%50,%51,%52,%53,%54,%55,%56,%57,%58,%59,%60,%61,%62,%63"
                 "}, da, db, p, 1, 1, 0, 1;\n}"
                 : ACC16(d), ACC16((d + 16)), ACC16((d + 32)), ACC16((d + 48))
                 : "r"(da), "r"(db), "r"(accum));
}
__device__ __forceinline__ float sigmoidf_(float v) { return rcp(1.f + ex2(-1.4426950408889634f * v)); }
__device__ __forceinline__ void wait_count(int idx, uint32_t n) {
    uint32_t v, it = 0;
    while (true) {
        asm volatile("ld.acquire.gpu.global.u32 %0, [%1];" : "=r"(v) : "l"(&g_cnt[idx * 8]) : "memory");
        if (v >= n) break;
        __nanosleep(100);
        spin_guard(it);
    }
    asm volatile("fence.proxy.async.global;" ::: "memory");
}

constexpr int G_STAGES = 4, G_PAIRS = 18;
constexpr uint32_t G_STAGE = 49152, G_EPI = G_STAGES * G_STAGE, G_BAR = G_EPI + 32768, G_SMEM = G_BAR + 256;
__device__ __forceinline__ int glu_job(int p, int j) {
    if (j < 12) return j * G_PAIRS + p;
    if (p < 14) return j == 12 ? 224 + p : (j == 13 ? 242 + p : -1);
    return j < 14 ? 216 + (j - 12) * 4 + (p - 14) : (j == 14 ? 224 + p : -1);
}

__global__ void __cluster_dims__(2, 1, 1) __launch_bounds__(384, 1)
glu_kernel(const __grid_constant__ CUtensorMap tXn, const __grid_constant__ CUtensorMap tG, const __grid_constant__ CUtensorMap tU,
           const __grid_constant__ CUtensorMap tHst, const __grid_constant__ CUtensorMap tHld, const __grid_constant__ CUtensorMap tD,
           const __grid_constant__ CUtensorMap tYst) {
    extern __shared__ __align__(1024) uint8_t smem[];
    const uint32_t sb = smem_u32(smem);
    const uint32_t full = sb + G_BAR, empty = full + 64;
    const int tid = threadIdx.x, lane = tid & 31;
    const int warp = uni(tid >> 5), wg = warp >> 2;
    const int rank = blockIdx.x & 1, pair = blockIdx.x >> 1;
    asm volatile("griddepcontrol.launch_dependents;" ::: "memory");
    if (tid == 0) {
        TL(2, 0); TLSM(2);
        for (int i = 0; i < G_STAGES; i++) { mbar_init(full + i * 8, 1); mbar_init(empty + i * 8, 16); }
        asm volatile("fence.mbarrier_init.release.cluster;" ::: "memory");
        fence_async();
    }
    __syncthreads();
    cluster_sync();
    if (wg == 0) {
        asm volatile("setmaxnreg.dec.sync.aligned.u32 40;");
        if (warp == 0) {
            if (lane == 0) {
                uint32_t st = 0, ph = 1;
                asm volatile("fence.acq_rel.gpu;\nfence.proxy.async.global;" ::: "memory");
                for (int j = 0, job; (job = glu_job(pair, j)) >= 0; j++) {
                    const bool dn = job >= 224;
                    const int mp = dn ? (job - 224) >> 2 : job / 28, nt = dn ? job & 3 : job % 28, rb = mp * 2 + rank;
                    const CUtensorMap* tA = dn ? &tHld : &tXn;
                    const CUtensorMap* tB = dn ? &tD : (rank ? &tU : &tG);
                    const int bcol = dn ? nt * 256 + rank * 128 : nt * 128, nkb = dn ? FF / 64 : DM / 64;
                    if (j == 12) TL(2, 2);
                    if (dn) wait_count(CNT_H + rb, 56);
                    for (int kb = 0; kb < nkb; kb++) {
                        mbar_wait(empty + st * 8, ph);
                        const uint32_t base = sb + st * G_STAGE;
                        mbar_expect(full + st * 8, G_STAGE);
                        tma2d(base, tA, kb * 64, rb * 128, full + st * 8);
                        tma2d_mc(base + 16384 + rank * 16384, tB, bcol, kb * 64, full + st * 8, 3);
                        tma2d_mc(base + 16384 + rank * 16384 + 8192, tB, bcol + 64, kb * 64, full + st * 8, 3);
                        if (++st == G_STAGES) { st = 0; ph ^= 1; }
                    }
                }
            }
        } else if (warp < 3) {
            const int cw = warp - 1;
            const uint32_t epi = sb + G_EPI + cw * 16384;
            bar_arrive(3 + cw, 160);
            for (int j = 0, job; (job = glu_job(pair, j)) >= 0; j++) {
                const bool dn = job >= 224;
                const int mp = dn ? (job - 224) >> 2 : job / 28, nt = dn ? job & 3 : job % 28, rb = mp * 2 + rank;
                for (int hp = 0; hp <= (int)dn; hp++) {
                    bar_sync(1 + cw, 160);
                    if (lane == 0) {
                        const int col = dn ? nt * 256 + hp * 128 : nt * 128;
                        tma2d_store(dn ? &tYst : &tHst, col, rb * 128 + cw * 64, epi);
                        tma2d_store(dn ? &tYst : &tHst, col + 64, rb * 128 + cw * 64, epi + 8192);
                        asm volatile("cp.async.bulk.commit_group;\ncp.async.bulk.wait_group.read 0;" ::: "memory");
                    }
                    __syncwarp();
                    bar_arrive(3 + cw, 160);
                    if (lane == 0) {
                        asm volatile("cp.async.bulk.wait_group 0;\nfence.proxy.async.global;" ::: "memory");
                        count_up(dn ? CNT_Y + rb * 8 + nt * 2 + hp : CNT_H + rb);
                    }
                    __syncwarp();
                }
            }
        }
        cluster_sync();
    } else {
        asm volatile("setmaxnreg.inc.sync.aligned.u32 232;");
        const int cw = wg - 1, w4 = warp & 3;
        const uint32_t empty_dst = mapa(empty, lane & 1);
        const int er = w4 * 16 + (lane & 15), ec = lane >> 4;
        const uint32_t epi = sb + G_EPI + cw * 16384 + er * 128;
        uint32_t st = 0, ph = 0;
        float acc[128];
        auto put = [&](const uint32_t* o) {
            bar_sync(3 + cw, 160);
#pragma unroll
            for (int q = 0; q < 8; q++) stsm4(epi + (q >> 2) * 8192 + (((2 * (q & 3) + ec) ^ (er & 7)) << 4), o[q * 4], o[q * 4 + 1], o[q * 4 + 2], o[q * 4 + 3]);
            fence_async();
            bar_arrive(1 + cw, 160);
        };
        for (int j = 0, job; (job = glu_job(pair, j)) >= 0; j++) {
            const bool dn = job >= 224;
            const int nkb = dn ? FF / 64 : DM / 64;
            uint32_t prev = 0;
#pragma unroll 1
            for (int kb = 0; kb < nkb; kb++) {
                mbar_wait(full + st * 8, ph);
                const uint32_t base = sb + st * G_STAGE;
                const uint32_t da = (((base + cw * 8192) & 0x3FFFF) >> 4) | (1u << 16);
                const uint32_t db = (((base + 16384) & 0x3FFFF) >> 4) | (512u << 16);
                wg_fence();
#pragma unroll
                for (int k = 0; k < 4; k++) wg256(acc, da + k * 2, db + k * 128, (kb | k) != 0);
                wg_commit();
                if (kb > 0) {
                    wg_wait<1>();
                    if (lane < 2) mbar_arrive_cluster(empty_dst + prev * 8);
                }
                prev = st;
                if (++st == G_STAGES) { st = 0; ph ^= 1; }
            }
            wg_wait<0>();
            reg_fence<128>(acc);
            if (lane < 2) mbar_arrive_cluster(empty_dst + prev * 8);
            uint32_t o[32];
            if (!dn) {
#pragma unroll
                for (int i = 0; i < 32; i++) o[i] = pack2(sigmoidf_(acc[2 * i]) * acc[64 + 2 * i], sigmoidf_(acc[2 * i + 1]) * acc[65 + 2 * i]);
                put(o);
            } else {
#pragma unroll
                for (int hp = 0; hp < 2; hp++) {
#pragma unroll
                    for (int i = 0; i < 32; i++) {
                        const float a = acc[hp * 64 + 2 * i], b = acc[hp * 64 + 2 * i + 1];
                        o[i] = pack2(sigmoidf_(a) * a, sigmoidf_(b) * b);
                    }
                    put(o);
                }
            }
        }
        bar_sync(3 + cw, 160);
        if (tid == 128) TL(2, 1);
        cluster_sync();
    }
}

constexpr int O_STAGES = 7;
constexpr uint32_t O_STAGE = 32768, O_BAR = O_STAGES * O_STAGE, O_SMEM = O_BAR + 256;

__global__ void __cluster_dims__(2, 1, 1) __launch_bounds__(384, 1)
out_kernel(const __grid_constant__ CUtensorMap tOx, const __grid_constant__ CUtensorMap tWo, const __grid_constant__ CUtensorMap tX,
           const __grid_constant__ CUtensorMap tY, const __grid_constant__ CUtensorMap tOut) {
    extern __shared__ __align__(1024) uint8_t smem[];
    const uint32_t sb = smem_u32(smem);
    const uint32_t full = sb + O_BAR, empty = full + 64;
    const int tid = threadIdx.x, lane = tid & 31;
    const int warp = uni(tid >> 5), wg = warp >> 2;
    const int rank = blockIdx.x & 1, nt = (blockIdx.x >> 1) & 7, rb = (blockIdx.x >> 4) * 2 + rank;
    constexpr int NKB = HD / 64;
    if (warp == 0) {
        if (tid == 0) { TL(3, 0); TLSM(3); }
        if (lane < O_STAGES) { mbar_init(full + lane * 8, 1); mbar_init(empty + lane * 8, 16); mbar_expect(full + lane * 8, O_STAGE); }
        asm volatile("fence.mbarrier_init.release.cluster;" ::: "memory");
        fence_async();
    }
    if (tid == 32) wait_count(CNT_OX + rb, 32);
    __syncwarp();
    asm volatile("barrier.cluster.arrive.relaxed.aligned;" ::: "memory");
    __syncthreads();
    if (warp == 1) {
        if (elect()) {
            TL(3, 2);
            asm volatile("fence.proxy.async.global;" ::: "memory");
            for (int kb = 0; kb < O_STAGES; kb++) tma2d(sb + kb * O_STAGE, &tOx, kb * 64, rb * 128, full + kb * 8);
        }
        __syncwarp();
    }
    asm volatile("barrier.cluster.wait.aligned;" ::: "memory");
    if (wg == 0) {
        if (warp == 0 && elect()) {
            asm volatile("fence.proxy.async.global;" ::: "memory");
            for (int kb = 0; kb < O_STAGES; kb++)
                tma2d_mc(sb + kb * O_STAGE + 16384 + rank * 8192, &tWo, nt * 128 + rank * 64, kb * 64, full + kb * 8, 3);
            uint32_t st = 0, ph = 0;
            for (int kb = O_STAGES; kb < NKB + 2; kb++) {
                const uint32_t base = sb + st * O_STAGE;
                mbar_wait(empty + st * 8, ph);
                mbar_expect(full + st * 8, O_STAGE);
                if (kb < NKB) {
                    tma2d(base, &tOx, kb * 64, rb * 128, full + st * 8);
                    tma2d_mc(base + 16384 + rank * 8192, &tWo, nt * 128 + rank * 64, kb * 64, full + st * 8, 3);
                } else {
                    if (kb == NKB) wait_count(CNT_Y + rb * 8 + nt, 2);
                    tma2d(base, &tX, nt * 128 + (kb - NKB) * 64, rb * 128, full + st * 8);
                    tma2d(base + 16384, &tY, nt * 128 + (kb - NKB) * 64, rb * 128, full + st * 8);
                }
                if (++st == O_STAGES) { st = 0; ph ^= 1; }
            }
        }
        __syncwarp();
    } else {
        const int cw = wg - 1, w4 = warp & 3;
        const uint32_t empty_dst = mapa(empty, lane & 1);
        const int er = cw * 64 + w4 * 16 + (lane & 15), ec = lane >> 4;
        uint32_t st = 0, ph = 0, prev = 0;
        float acc[64];
#pragma unroll 1
        for (int kb = 0; kb < NKB; kb++) {
            mbar_wait(full + st * 8, ph);
            const uint32_t base = sb + st * O_STAGE;
            const uint32_t da = (((base + cw * 8192) & 0x3FFFF) >> 4) | (1u << 16);
            const uint32_t db = (((base + 16384) & 0x3FFFF) >> 4) | (512u << 16);
            wg_fence();
#pragma unroll
            for (int k = 0; k < 4; k++) wg128(acc, da + k * 2, db + k * 128, (kb | k) != 0);
            wg_commit();
            wg_wait<1>();
            if (lane < 2 && kb > 0 && kb <= NKB + 2 - O_STAGES) mbar_arrive_cluster(empty_dst + prev * 8);
            prev = st;
            if (++st == O_STAGES) { st = 0; ph ^= 1; }
        }
        wg_wait<0>();
        reg_fence<64>(acc);
#pragma unroll
        for (int bx = 0; bx < 2; bx++) {
            mbar_wait(full + st * 8, ph);
            const uint32_t base = sb + st * O_STAGE;
#pragma unroll
            for (int j = 0; j < 4; j++) {
                uint32_t xv[4], yv[4];
                const uint32_t ad = base + er * 128 + (((2 * j + ec) ^ (er & 7)) << 4);
                ldsm4(xv, ad); ldsm4(yv, ad + 16384);
                const float* a = acc + bx * 32 + j * 8;
#pragma unroll
                for (int i = 0; i < 4; i++)
                    xv[i] = pack2(fmaf(a[2 * i], bf_lo(yv[i]), bf_lo(xv[i])), fmaf(a[2 * i + 1], bf_hi(yv[i]), bf_hi(xv[i])));
                stsm4(ad, xv[0], xv[1], xv[2], xv[3]);
            }
            fence_async();
            bar_sync(1 + cw, 128);
            if ((tid & 127) == 0) {
                tma2d_store(&tOut, nt * 128 + bx * 64, rb * 128 + cw * 64, base + cw * 8192);
                asm volatile("cp.async.bulk.commit_group;" ::: "memory");
            }
            if (++st == O_STAGES) { st = 0; ph ^= 1; }
        }
        if ((tid & 127) == 0) asm volatile("cp.async.bulk.wait_group.read 0;" ::: "memory");
        if (tid == 128) TL(3, 1);
        __syncwarp();
    }
    asm volatile("barrier.cluster.arrive.relaxed.aligned;\nbarrier.cluster.wait.aligned;" ::: "memory");
}

typedef CUresult (*EncodeFn)(CUtensorMap*, CUtensorMapDataType, cuuint32_t, void*, const cuuint64_t*, const cuuint64_t*, const cuuint32_t*,
                             const cuuint32_t*, CUtensorMapInterleave, CUtensorMapSwizzle, CUtensorMapL2promotion, CUtensorMapFloatOOBfill);

CUtensorMap make_map(EncodeFn enc, const void* p, int rows, int cols, int box_rows) {
    CUtensorMap m;
    cuuint64_t dims[2] = {(cuuint64_t)cols, (cuuint64_t)rows}, strides[1] = {(cuuint64_t)cols * 2};
    cuuint32_t box[2] = {64, (cuuint32_t)box_rows}, es[2] = {1, 1};
    enc(&m, CU_TENSOR_MAP_DATA_TYPE_BFLOAT16, 2, const_cast<void*>(p), dims, strides, box, es, CU_TENSOR_MAP_INTERLEAVE_NONE,
        CU_TENSOR_MAP_SWIZZLE_128B, CU_TENSOR_MAP_L2_PROMOTION_L2_128B, CU_TENSOR_MAP_FLOAT_OOB_FILL_NONE);
    return m;
}

}

#define PDL 7
extern "C" void kernel_launch(void* const* d_in, const int* in_sizes, int n_in, void* d_out, int out_size) {
    const __nv_bfloat16* x = (const __nv_bfloat16*)d_in[0];
    const __nv_bfloat16* mem0 = (const __nv_bfloat16*)d_in[1];
    void* fn = nullptr;
    cudaDriverEntryPointQueryResult qr;
    cudaGetDriverEntryPoint("cuTensorMapEncodeTiled", &fn, cudaEnableDefault, &qr);
    EncodeFn enc = (EncodeFn)fn;
    void *xn, *ox, *h, *y;
    cudaGetSymbolAddress(&xn, g_xn); cudaGetSymbolAddress(&ox, g_ox); cudaGetSymbolAddress(&h, g_h); cudaGetSymbolAddress(&y, g_y);

    const CUtensorMap tq = make_map(enc, d_in[2], DM, HD, 128), tk = make_map(enc, d_in[3], DM, HD, 128), tv = make_map(enc, d_in[4], DM, HD, 128);
    const CUtensorMap two16 = make_map(enc, d_in[5], HD, DM, 16);
    const CUtensorMap txn128 = make_map(enc, xn, SEQ, DM, 128), tg = make_map(enc, d_in[8], DM, FF, 64), tu = make_map(enc, d_in[9], DM, FF, 64);
    const CUtensorMap th64 = make_map(enc, h, SEQ, FF, 64), th128 = make_map(enc, h, SEQ, FF, 128), td = make_map(enc, d_in[10], FF, DM, 64);
    const CUtensorMap ty64 = make_map(enc, y, SEQ, DM, 64), ty128 = make_map(enc, y, SEQ, DM, 128), tx128 = make_map(enc, x, SEQ, DM, 128);
    const CUtensorMap tox = make_map(enc, ox, SEQ, HD, 128), two64 = make_map(enc, d_in[5], HD, DM, 64), tout = make_map(enc, d_out, SEQ, DM, 64);

    cudaFuncSetAttribute(chain_kernel, cudaFuncAttributeMaxDynamicSharedMemorySize, C_SMEM);
    cudaFuncSetAttribute(glu_kernel, cudaFuncAttributeMaxDynamicSharedMemorySize, G_SMEM);
    cudaFuncSetAttribute(out_kernel, cudaFuncAttributeMaxDynamicSharedMemorySize, O_SMEM);

    Descs D;
    for (int i = 0; i < 4; i++) D.sw[i] = DSW;
    D.ns = DNS;
    cudaStream_t st = cudaStreamPerThread;
    cudaLaunchAttribute at;
    at.id = cudaLaunchAttributeProgrammaticStreamSerialization;
    at.val.programmaticStreamSerializationAllowed = 1;
    cudaLaunchConfig_t cfg = {};
    cfg.stream = st; cfg.attrs = &at; cfg.numAttrs = 0;
    cfg.gridDim = dim3(96); cfg.blockDim = dim3(256); cfg.dynamicSmemBytes = C_SMEM;
    cudaLaunchKernelEx(&cfg, chain_kernel, tq, tk, tv, two16, D, D, x, mem0);
    cfg.gridDim = dim3(2 * G_PAIRS); cfg.blockDim = dim3(384); cfg.dynamicSmemBytes = G_SMEM; cfg.numAttrs = (PDL >> 1) & 1;
    cudaLaunchKernelEx(&cfg, glu_kernel, txn128, tg, tu, th64, th128, td, ty64);
    cfg.gridDim = dim3(128); cfg.dynamicSmemBytes = O_SMEM; cfg.numAttrs = (PDL >> 2) & 1;
    cudaLaunchKernelEx(&cfg, out_kernel, tox, two64, tx128, ty128, tout);
}
```

```cpp
#include <cuda_runtime.h>
#include <cuda_bf16.h>
#include <cuda.h>
#include <stdint.h>
#include <type_traits>

namespace {

constexpr int SEQ = 2048, DM = 1024, HD = 4096, FF = 3584, NSEG = 64;

__device__ __align__(1024) __nv_bfloat16 g_xn[SEQ * DM];
__device__ __align__(1024) uint4 g_xc[SEQ * DM / 8];
__device__ __align__(1024) __nv_bfloat16 g_ox[SEQ * HD];
__device__ __align__(1024) __nv_bfloat16 g_h[SEQ * FF];
__device__ __align__(1024) __nv_bfloat16 g_y[SEQ * DM];
__device__ __align__(1024) uint4 g_xmem[4][1024];
__device__ __align__(1024) uint4 g_xo[4][4096];
#define FSTR 8
__device__ __align__(1024) uint32_t g_flag[1][96 * FSTR];
enum { CNT_H = 0, CNT_OX = 16, CNT_Y = 32, CNT_NUM = 160 };
__device__ __align__(1024) uint32_t g_cnt[CNT_NUM * 8];
__device__ __align__(128) uint32_t g_epoch;
#define TL(k, i)
#define TLSM(k)

__device__ __forceinline__ uint32_t smem_u32(const void* p) { return (uint32_t)__cvta_generic_to_shared(p); }
__device__ __forceinline__ uint32_t mapa(uint32_t a, uint32_t r) {
    uint32_t o; asm("mapa.shared::cluster.u32 %0, %1, %2;" : "=r"(o) : "r"(a), "r"(r)); return o;
}
__device__ __forceinline__ void mbar_init(uint32_t a, uint32_t cnt) {
    asm volatile("mbarrier.init.shared.b64 [%0], %1;" :: "r"(a), "r"(cnt) : "memory");
}
__device__ __forceinline__ void mbar_expect(uint32_t a, uint32_t bytes) {
    asm volatile("mbarrier.arrive.expect_tx.shared.b64 _, [%0], %1;" :: "r"(a), "r"(bytes) : "memory");
}
__device__ __forceinline__ void mbar_arrive_cluster(uint32_t a) {
    asm volatile("mbarrier.arrive.shared::cluster.b64 _, [%0];" :: "r"(a) : "memory");
}
__device__ __forceinline__ void spin_guard(uint32_t& it) {
    asm volatile("{\n.reg .pred p;\nadd.u32 %0, %0, 1;\nsetp.gt.u32 p, %0, 0x400000;\n@p st.shared.u32 [%0], %0;\n}" : "+r"(it));
}
__device__ __forceinline__ void mbar_wait(uint32_t a, uint32_t par) {
    asm volatile("{\n.reg .pred p;\nWL:\nmbarrier.try_wait.parity.shared::cta.b64 p, [%0], %1;\n@!p bra WL;\n}" :: "r"(a), "r"(par) : "memory");
}
__device__ __forceinline__ void mbar_arrive(uint32_t a) { asm volatile("mbarrier.arrive.shared.b64 _, [%0];" :: "r"(a) : "memory"); }
__device__ __forceinline__ void tma2d(uint32_t dst, const CUtensorMap* m, int c0, int c1, uint32_t bar) {
    asm volatile("cp.async.bulk.tensor.2d.shared::cluster.global.mbarrier::complete_tx::bytes [%0], [%1, {%3, %4}], [%2];"
                 :: "r"(dst), "l"(m), "r"(bar), "r"(c0), "r"(c1) : "memory");
}
__device__ __forceinline__ void tma2d_mc(uint32_t dst, const CUtensorMap* m, int c0, int c1, uint32_t bar, uint16_t mask) {
    asm volatile("cp.async.bulk.tensor.2d.shared::cluster.global.mbarrier::complete_tx::bytes.multicast::cluster [%0], [%1, {%3, %4}], [%2], %5;"
                 :: "r"(dst), "l"(m), "r"(bar), "r"(c0), "r"(c1), "h"(mask) : "memory");
}
__device__ __forceinline__ void bulk_mc(uint32_t dst, const void* src, uint32_t bytes, uint32_t bar, uint16_t mask) {
    asm volatile("cp.async.bulk.shared::cluster.global.mbarrier::complete_tx::bytes.multicast::cluster [%0], [%1], %2, [%3], %4;"
                 :: "r"(dst), "l"(src), "r"(bytes), "r"(bar), "h"(mask) : "memory");
}
__device__ __forceinline__ void bulk_ld(uint32_t dst, const void* src, uint32_t bytes, uint32_t bar) {
    asm volatile("cp.async.bulk.shared::cluster.global.mbarrier::complete_tx::bytes [%0], [%1], %2, [%3];"
                 :: "r"(dst), "l"(src), "r"(bytes), "r"(bar) : "memory");
}
__device__ __forceinline__ uint32_t gtick() { uint64_t c; asm volatile("mov.u64 %0, %%globaltimer;" : "=l"(c)); return (uint32_t)c >> 5; }
__device__ __forceinline__ uint32_t gtick_dep(uint32_t zero) {
    uint32_t c;
    asm volatile("{\n.reg .pred p;\nsetp.eq.u32 p, %1, 0;\nmov.u32 %0, 0;\n@p mov.u32 %0, %%globaltimer_lo;\n}" : "=r"(c) : "r"(zero));
    return c >> 5;
}
__device__ __forceinline__ uint32_t ld_relaxed1(const void* p) {
    uint32_t v; asm volatile("ld.relaxed.gpu.global.u32 %0, [%1];" : "=r"(v) : "l"(p) : "memory"); return v;
}
__device__ __forceinline__ bool any_nan(float a, float b) {
    uint32_t r;
    asm volatile("{\n.reg .pred p;\nsetp.nan.f32 p, %1, %2;\nvote.sync.any.pred p, p, 0xffffffff;\nselp.u32 %0, 1, 0, p;\n}" : "=r"(r) : "f"(a), "f"(b));
    return r;
}
__device__ __forceinline__ bool bar_sync_any_nan(float a, float b) {
    uint32_t r;
    asm volatile("{\n.reg .pred p;\nsetp.nan.f32 p, %1, %2;\nbarrier.cta.red.or.aligned.pred p, 6, 256, p;\nselp.u32 %0, 1, 0, p;\n}"
                 : "=r"(r) : "f"(a), "f"(b) : "memory");
    return r;
}
__device__ __forceinline__ void bar_arrive(int id, int n) { asm volatile("bar.arrive %0, %1;" :: "r"(id), "r"(n) : "memory"); }
__device__ __forceinline__ uint32_t clk() { uint64_t c; asm volatile("mov.u64 %0, %%clock64;" : "=l"(c)); return (uint32_t)c; }
__device__ __forceinline__ void tma2d_store(const CUtensorMap* m, int c0, int c1, uint32_t src) {
    asm volatile("cp.async.bulk.tensor.2d.global.shared::cta.bulk_group [%0, {%1, %2}], [%3];"
                 :: "l"(m), "r"(c0), "r"(c1), "r"(src) : "memory");
}
__device__ __forceinline__ void bar_sync(int id, int n) { asm volatile("bar.sync %0, %1;" :: "r"(id), "r"(n) : "memory"); }
__device__ __forceinline__ void fence_async() { asm volatile("fence.proxy.async.shared::cta;" ::: "memory"); }
__device__ __forceinline__ void cluster_sync() {
    asm volatile("barrier.cluster.arrive.release.aligned;\nbarrier.cluster.wait.acquire.aligned;" ::: "memory");
}
__device__ __forceinline__ void ldsm4(uint32_t* r, uint32_t a) {
    asm volatile("ldmatrix.sync.aligned.m8n8.x4.shared.b16 {%0,%1,%2,%3}, [%4];"
                 : "=r"(r[0]), "=r"(r[1]), "=r"(r[2]), "=r"(r[3]) : "r"(a) : "memory");
}
__device__ __forceinline__ void ldsm4t(uint32_t* r, uint32_t a) {
    asm volatile("ldmatrix.sync.aligned.m8n8.x4.trans.shared.b16 {%0,%1,%2,%3}, [%4];"
                 : "=r"(r[0]), "=r"(r[1]), "=r"(r[2]), "=r"(r[3]) : "r"(a) : "memory");
}
__device__ __forceinline__ void stsm4(uint32_t a, uint32_t r0, uint32_t r1, uint32_t r2, uint32_t r3) {
    asm volatile("stmatrix.sync.aligned.m8n8.x4.shared.b16 [%0], {%1,%2,%3,%4};" :: "r"(a), "r"(r0), "r"(r1), "r"(r2), "r"(r3) : "memory");
}
__device__ __forceinline__ void stsm4f(uint32_t a, const float* v) {
    asm volatile("{\n.reg .b32 a, b, c, d;\nmov.b32 a, %1;\nmov.b32 b, %2;\nmov.b32 c, %3;\nmov.b32 d, %4;\n"
                 "stmatrix.sync.aligned.m8n8.x4.shared.b16 [%0], {a, b, c, d};\n}" :: "r"(a), "f"(v[0]), "f"(v[1]), "f"(v[2]), "f"(v[3]) : "memory");
}
__device__ __forceinline__ void ldsm4f(float* v, uint32_t a) {
    uint32_t r[4];
    ldsm4(r, a);
#pragma unroll
    for (int i = 0; i < 4; i++) v[i] = __uint_as_float(r[i]);
}
__device__ __forceinline__ void stsm4t(uint32_t a, uint32_t r0, uint32_t r1, uint32_t r2, uint32_t r3) {
    asm volatile("stmatrix.sync.aligned.m8n8.x4.trans.shared.b16 [%0], {%1,%2,%3,%4};" :: "r"(a), "r"(r0), "r"(r1), "r"(r2), "r"(r3) : "memory");
}
__device__ __forceinline__ void stsm2(uint32_t a, uint32_t r0, uint32_t r1) {
    asm volatile("stmatrix.sync.aligned.m8n8.x2.shared.b16 [%0], {%1,%2};" :: "r"(a), "r"(r0), "r"(r1) : "memory");
}
__device__ __forceinline__ void stsm2t(uint32_t a, uint32_t r0, uint32_t r1) {
    asm volatile("stmatrix.sync.aligned.m8n8.x2.trans.shared.b16 [%0], {%1,%2};" :: "r"(a), "r"(r0), "r"(r1) : "memory");
}
__device__ __forceinline__ uint32_t movm(uint32_t a) {
    uint32_t d; asm volatile("movmatrix.sync.aligned.m8n8.trans.b16 %0, %1;" : "=r"(d) : "r"(a)); return d;
}
__device__ __forceinline__ void mma16(float* d, uint32_t a0, uint32_t a1, uint32_t a2, uint32_t a3, uint32_t b0, uint32_t b1) {
    asm volatile("mma.sync.aligned.m16n8k16.row.col.f32.bf16.bf16.f32 {%0,%1,%2,%3}, {%4,%5,%6,%7}, {%8,%9}, {%0,%1,%2,%3};"
                 : "+f"(d[0]), "+f"(d[1]), "+f"(d[2]), "+f"(d[3]) : "r"(a0), "r"(a1), "r"(a2), "r"(a3), "r"(b0), "r"(b1));
}
__device__ __forceinline__ void mma8(float* d, uint32_t a0, uint32_t a1, uint32_t b0) {
    asm volatile("mma.sync.aligned.m16n8k8.row.col.f32.bf16.bf16.f32 {%0,%1,%2,%3}, {%4,%5}, {%6}, {%0,%1,%2,%3};"
                 : "+f"(d[0]), "+f"(d[1]), "+f"(d[2]), "+f"(d[3]) : "r"(a0), "r"(a1), "r"(b0));
}
__device__ __forceinline__ uint32_t pack2(float lo, float hi) {
    uint32_t r; asm("cvt.rn.bf16x2.f32 %0, %1, %2;" : "=r"(r) : "f"(hi), "f"(lo)); return r;
}
__device__ __forceinline__ float bf_lo(uint32_t v) { return __uint_as_float(v << 16); }
__device__ __forceinline__ float bf_hi(uint32_t v) { return __uint_as_float(v & 0xFFFF0000u); }
__device__ __forceinline__ float ex2(float x) { float y; asm("ex2.approx.ftz.f32 %0, %1;" : "=f"(y) : "f"(x)); return y; }
__device__ __forceinline__ float rcp(float x) { float y; asm("rcp.approx.ftz.f32 %0, %1;" : "=f"(y) : "f"(x)); return y; }
__device__ __forceinline__ void sts4f(uint32_t a, float x, float y, float z, float w) {
    asm volatile("st.shared.v4.f32 [%0], {%1,%2,%3,%4};" :: "r"(a), "f"(x), "f"(y), "f"(z), "f"(w) : "memory");
}
__device__ __forceinline__ void sts1u(uint32_t a, uint32_t v) { asm volatile("st.shared.u32 [%0], %1;" :: "r"(a), "r"(v) : "memory"); }
__device__ __forceinline__ void sts4u(uint32_t a, uint4 v) {
    asm volatile("st.shared.v4.u32 [%0], {%1,%2,%3,%4};" :: "r"(a), "r"(v.x), "r"(v.y), "r"(v.z), "r"(v.w) : "memory");
}
__device__ __forceinline__ float4 lds4f(uint32_t a) {
    float4 v; asm volatile("ld.shared.v4.f32 {%0,%1,%2,%3}, [%4];" : "=f"(v.x), "=f"(v.y), "=f"(v.z), "=f"(v.w) : "r"(a) : "memory"); return v;
}
__device__ __forceinline__ float2 lds2f(uint32_t a) {
    float2 v; asm volatile("ld.shared.v2.f32 {%0,%1}, [%2];" : "=f"(v.x), "=f"(v.y) : "r"(a) : "memory"); return v;
}
__device__ __forceinline__ uint4 lds4u(uint32_t a) {
    uint4 v; asm volatile("ld.shared.v4.u32 {%0,%1,%2,%3}, [%4];" : "=r"(v.x), "=r"(v.y), "=r"(v.z), "=r"(v.w) : "r"(a) : "memory"); return v;
}
__device__ __forceinline__ uint32_t lds1u(uint32_t a) {
    uint32_t v; asm volatile("ld.shared.u32 %0, [%1];" : "=r"(v) : "r"(a) : "memory"); return v;
}
__device__ __forceinline__ uint2 lds2u(uint32_t a) {
    uint2 v; asm volatile("ld.shared.v2.u32 {%0,%1}, [%2];" : "=r"(v.x), "=r"(v.y) : "r"(a) : "memory"); return v;
}
__device__ __forceinline__ void st_async4(uint32_t a, uint32_t bar, float x, float y, float z, float w) {
    asm volatile("st.async.shared::cluster.mbarrier::complete_tx::bytes.v4.f32 [%0], {%1,%2,%3,%4}, [%5];"
                 :: "r"(a), "f"(x), "f"(y), "f"(z), "f"(w), "r"(bar) : "memory");
}
__device__ __forceinline__ void st_async2(uint32_t a, uint32_t bar, float x, float y) {
    asm volatile("st.async.shared::cluster.mbarrier::complete_tx::bytes.v2.f32 [%0], {%1,%2}, [%3];"
                 :: "r"(a), "f"(x), "f"(y), "r"(bar) : "memory");
}
template <int OFF>
__device__ __forceinline__ void st_async1f(uint32_t a, uint32_t bar, float x) {
    asm volatile("st.async.shared::cluster.mbarrier::complete_tx::bytes.f32 [%0 + %3], %1, [%2];" :: "r"(a), "f"(x), "r"(bar), "n"(OFF) : "memory");
}
__device__ __forceinline__ uint32_t late_zero() {
    uint64_t c;
    asm volatile("mov.u64 %0, %%clock64;" : "=l"(c));
    return c >> 63;
}
__device__ __forceinline__ void st_async1(uint32_t a, uint32_t bar, uint32_t x) {
    asm volatile("st.async.shared::cluster.mbarrier::complete_tx::bytes.b32 [%0], %1, [%2];" :: "r"(a), "r"(x), "r"(bar) : "memory");
}
__device__ __forceinline__ uint4 ld_relaxed4(const uint4* p) {
    uint4 v;
    asm volatile("ld.relaxed.gpu.global.v4.u32 {%0,%1,%2,%3}, [%4];" : "=r"(v.x), "=r"(v.y), "=r"(v.z), "=r"(v.w) : "l"(p) : "memory");
    return v;
}
__device__ __forceinline__ void st_relaxed4(uint4* p, uint4 v) {
    asm volatile("st.relaxed.gpu.global.v4.u32 [%0], {%1,%2,%3,%4};" :: "l"(p), "r"(v.x), "r"(v.y), "r"(v.z), "r"(v.w) : "memory");
}
__device__ __forceinline__ void count_up(int idx) {
    asm volatile("red.release.gpu.global.add.u32 [%0], 1;" :: "l"(&g_cnt[idx * 8]) : "memory");
}
__device__ __forceinline__ void st_pred1(void* p, uint32_t v, bool on) {
    asm volatile("{\n.reg .pred p;\nsetp.ne.u32 p, %2, 0;\n@p st.relaxed.gpu.global.u32 [%0], %1;\n}" :: "l"(p), "r"(v), "r"((uint32_t)on) : "memory");
}
__device__ __forceinline__ void st_pred4(void* p, uint4 v, bool on) {
    asm volatile("{\n.reg .pred p;\nsetp.ne.u32 p, %5, 0;\n@p st.global.v4.u32 [%0], {%1,%2,%3,%4};\n}"
                 :: "l"(p), "r"(v.x), "r"(v.y), "r"(v.z), "r"(v.w), "r"((uint32_t)on) : "memory");
}
__device__ __forceinline__ void st_relaxed1(void* p, uint32_t v) {
    asm volatile("st.relaxed.gpu.global.u32 [%0], %1;" :: "l"(p), "r"(v) : "memory");
}
__device__ __forceinline__ uint32_t umax4(uint4 v) { return max(max(v.x, v.y), max(v.z, v.w)); }
__device__ __forceinline__ void wg_fence() { asm volatile("wgmma.fence.sync.aligned;" ::: "memory"); }
__device__ __forceinline__ void wg_commit() { asm volatile("wgmma.commit_group.sync.aligned;" ::: "memory"); }
template <int N> __device__ __forceinline__ void wg_wait() { asm volatile("wgmma.wait_group.sync.aligned %0;" :: "n"(N) : "memory"); }
template <int N> __device__ __forceinline__ void reg_fence(float* d) {
#pragma unroll
    for (int i = 0; i < N; i++) asm volatile("" : "+f"(d[i]) :: "memory");
}
#define ACC16(d) "+f"(d[0]), "+f"(d[1]), "+f"(d[2]), "+f"(d[3]), "+f"(d[4]), "+f"(d[5]), "+f"(d[6]), "+f"(d[7]), \
                 "+f"(d[8]), "+f"(d[9]), "+f"(d[10]), "+f"(d[11]), "+f"(d[12]), "+f"(d[13]), "+f"(d[14]), "+f"(d[15])
#define DESC_HI_SW128 "0x40000040"
#define OUT16(d) "=f"(d[0]), "=f"(d[1]), "=f"(d[2]), "=f"(d[3]), "=f"(d[4]), "=f"(d[5]), "=f"(d[6]), "=f"(d[7]), \
                 "=f"(d[8]), "=f"(d[9]), "=f"(d[10]), "=f"(d[11]), "=f"(d[12]), "=f"(d[13]), "=f"(d[14]), "=f"(d[15])
template <int ACCUM, int BOFF>
__device__ __forceinline__ void wg32_rs(float* d, const uint32_t* a, uint64_t dsw) {
    if (ACCUM)
        asm volatile("{\n.reg .b64 db;\nadd.s64 db, %20, %21;\n"
                     "wgmma.mma_async.sync.aligned.m64n32k16.f32.bf16.bf16 {%0,%1,%2,%3,%4,%5,%6,%7,%8,%9,%10,%11,%12,%13,%14,%15}, "
                     "{%16,%17,%18,%19}, db, 1, 1, 1, 0;\n}"
                     : ACC16(d) : "r"(a[0]), "r"(a[1]), "r"(a[2]), "r"(a[3]), "l"(dsw), "n"(BOFF));
    else
        asm volatile("{\n.reg .b64 db;\nadd.s64 db, %20, %21;\n"
                     "wgmma.mma_async.sync.aligned.m64n32k16.f32.bf16.bf16 {%0,%1,%2,%3,%4,%5,%6,%7,%8,%9,%10,%11,%12,%13,%14,%15}, "
                     "{%16,%17,%18,%19}, db, 0, 1, 1, 0;\n}"
                     : OUT16(d) : "r"(a[0]), "r"(a[1]), "r"(a[2]), "r"(a[3]), "l"(dsw), "n"(BOFF));
}
template <int ACCUM, int AOFF, int BOFF>
__device__ __forceinline__ void wg32_ss(float* d, uint64_t dsw) {
    if (ACCUM)
        asm volatile("{\n.reg .b64 da, db;\nadd.s64 da, %16, %17;\nadd.s64 db, %16, %18;\n"
                     "wgmma.mma_async.sync.aligned.m64n32k16.f32.bf16.bf16 {%0,%1,%2,%3,%4,%5,%6,%7,%8,%9,%10,%11,%12,%13,%14,%15}, "
                     "da, db, 1, 1, 1, 1, 0;\n}"
                     : ACC16(d) : "l"(dsw), "n"(AOFF), "n"(BOFF));
    else
        asm volatile("{\n.reg .b64 da, db;\nadd.s64 da, %16, %17;\nadd.s64 db, %16, %18;\n"
                     "wgmma.mma_async.sync.aligned.m64n32k16.f32.bf16.bf16 {%0,%1,%2,%3,%4,%5,%6,%7,%8,%9,%10,%11,%12,%13,%14,%15}, "
                     "da, db, 0, 1, 1, 1, 0;\n}"
                     : OUT16(d) : "l"(dsw), "n"(AOFF), "n"(BOFF));
}
template <int ACCUM, int AOFF, int BOFF>
__device__ __forceinline__ void wg8_ss(float* d, uint64_t dsw, uint64_t dns) {
    if (!ACCUM)
        asm volatile("{\n.reg .b64 da, db;\nadd.s64 da, %4, %6;\nadd.s64 db, %5, %7;\n"
                     "wgmma.mma_async.sync.aligned.m64n8k16.f32.bf16.bf16 {%0,%1,%2,%3}, da, db, 0, 1, 1, 1, 0;\n}"
                     : "=f"(d[0]), "=f"(d[1]), "=f"(d[2]), "=f"(d[3]) : "l"(dsw), "l"(dns), "n"(AOFF), "n"(BOFF));
    else
        asm volatile("{\n.reg .b64 da, db;\nadd.s64 da, %4, %6;\nadd.s64 db, %5, %7;\n"
                     "wgmma.mma_async.sync.aligned.m64n8k16.f32.bf16.bf16 {%0,%1,%2,%3}, da, db, 1, 1, 1, 1, 0;\n}"
                     : "+f"(d[0]), "+f"(d[1]), "+f"(d[2]), "+f"(d[3]) : "l"(dsw), "l"(dns), "n"(AOFF), "n"(BOFF));
}
template <int I0, int I1, class F>
__device__ __forceinline__ void static_for(F&& f) {
    if constexpr (I0 < I1) { f(std::integral_constant<int, I0>{}); static_for<I0 + 1, I1>(f); }
}
template <int I0, int I1, int AOFF, int BOFF>
__device__ __forceinline__ void wg8_chain(float* d, uint64_t dsw, uint64_t dns) {
    wg_fence();
    static_for<I0, I1>([&](auto i) { wg8_ss<i.value != 0, AOFF + i.value * 128, BOFF + i.value * 16>(d, dsw, dns); });
    wg_commit();
}

__device__ __forceinline__ void ln_row(const uint4* v, int row, int lane) {
    float f[32];
#pragma unroll
    for (int j = 0; j < 4; j++) {
        f[j * 8 + 0] = bf_lo(v[j].x); f[j * 8 + 1] = bf_hi(v[j].x); f[j * 8 + 2] = bf_lo(v[j].y); f[j * 8 + 3] = bf_hi(v[j].y);
        f[j * 8 + 4] = bf_lo(v[j].z); f[j * 8 + 5] = bf_hi(v[j].z); f[j * 8 + 6] = bf_lo(v[j].w); f[j * 8 + 7] = bf_hi(v[j].w);
    }
    float s = 0.f;
#pragma unroll
    for (int i = 0; i < 32; i++) s += f[i];
#pragma unroll
    for (int o = 16; o; o >>= 1) s += __shfl_xor_sync(~0u, s, o);
    const float mean = s * (1.f / DM);
    float q = 0.f;
#pragma unroll
    for (int i = 0; i < 32; i++) { f[i] -= mean; q += f[i] * f[i]; }
#pragma unroll
    for (int o = 16; o; o >>= 1) q += __shfl_xor_sync(~0u, q, o);
    const float r = 1.f / sqrtf(q * (1.f / DM) + 1e-5f);
    uint4* dst = reinterpret_cast<uint4*>(g_xn + (size_t)row * DM);
    uint4* dst1 = g_xc + (row >> 5) * 4096 + (lane >> 3) * 256 + (row & 31) * 8 + ((lane & 7) ^ (row & 7));
#pragma unroll
    for (int j = 0; j < 4; j++) {
        const uint4 o = make_uint4(pack2(f[j * 8] * r, f[j * 8 + 1] * r), pack2(f[j * 8 + 2] * r, f[j * 8 + 3] * r),
                                   pack2(f[j * 8 + 4] * r, f[j * 8 + 5] * r), pack2(f[j * 8 + 6] * r, f[j * 8 + 7] * r));
        dst[j * 32 + lane] = o;
        dst1[(j & 1) * 2048 + (j >> 1) * 1024] = o;
    }
}
__device__ __forceinline__ void reset_exchange(const __nv_bfloat16* __restrict__ mem0) {
    const int gi = blockIdx.x * 256 + threadIdx.x;
    const uint4 poison = make_uint4(~0u, ~0u, ~0u, ~0u);
    if (gi < 1024) {
        uint4 m = reinterpret_cast<const uint4*>(mem0)[(gi & 7) * 128 + (gi >> 3)];
        if (m.x == ~0u) m.x = 0x7FFF7FFFu;
        if (m.y == ~0u) m.y = 0x7FFF7FFFu;
        if (m.z == ~0u) m.z = 0x7FFF7FFFu;
        if (m.w == ~0u) m.w = 0x7FFF7FFFu;
        g_xmem[0][gi] = m;
    } else if (gi < 4096) {
        (&g_xmem[0][0])[gi] = poison;
    } else if (gi < 4096 + 16384) {
        (&g_xo[0][0])[gi - 4096] = poison;
    } else if (gi < 4096 + 16384 + 24 * FSTR) {
        reinterpret_cast<uint4*>(&g_flag[0][0])[gi - 4096 - 16384] = poison;
    } else if (gi >= 24576 - CNT_NUM) {
        g_cnt[(24575 - gi) * 8] = 0;
    }
}

#define ONKQ 45
constexpr int ONKV = 128 - 2 * ONKQ;
constexpr uint32_t SB0 = 1024;
constexpr uint32_t C_WS = 0, C_XN = 65536, C_MB = 98304, C_WO = 114688, C_SMEM = 232448;
constexpr uint32_t C_BAR = C_SMEM - 384, C_CAL = C_BAR + 192;
constexpr uint32_t C_SLOTQ = C_WO + ONKQ * 2048, C_QX = C_SLOTQ + 8192, C_KX = C_QX + 4096,
                   C_XSL = C_KX + 4096, C_OL = C_XSL + 5120;
constexpr uint32_t C_SLOTV = C_WO + ONKV * 2048, C_V = C_SLOTV + 8192, C_PL = C_V + 20480, C_SL = C_PL + 4096;
constexpr uint32_t C_DUMP = C_BAR - 512;
static_assert(C_OL + 3072 <= C_DUMP && C_SL + 2560 <= C_DUMP, "smem overflow");
enum { B_W0 = 0, B_W1, B_W2, B_WS, B_XF0, B_XF1, B_SC, B_P0, B_P1, B_XS, B_OL, B_MF0, B_MF1, B_OF, B_RT0, B_RT1, B_VF, B_MBF, B_GO, B_H1, B_A0, B_XF2, B_DUMP, B_NUM };
struct Descs { uint64_t sw[4], ns; };
constexpr uint64_t DSW = 0x4000004000010000ull, DNS = 0x0000001000080000ull;
template <int V> using ic = std::integral_constant<int, V>;
constexpr float SM_SCALE = 0.08838834764831845f * 1.4426950408889634f;

#define TSD(i) do {} while (0)
#define TS_FLUSH(w)
#define TSX(i, c)
#define TS(i)
#define NOFILL 0
#define DLY1 2230
#define DLY2 2420
#define SWAP16 0
#define SSFIRST 1
#define CANARY ~0u
#define L2POS 10
#define PFX 1
#define C0FIRST 0
#define WOLATE 0
#define TAKEV 1
#define TAKEQ 0
#define XS0 1
#define QNB 8
#define QK1 16
#define RFPOS 6
#define STPOS 12
#define OHEAD 8
#define OTAIL 3
#define DLYS 150
#define DLYB 200
#define VLEAD 3

#define VEARLY 8
#define QSPLIT 20
__device__ __forceinline__ bool elect() {
    uint32_t r;
    asm volatile("{\n.reg .pred p;\nelect.sync _|p, 0xffffffff;\nselp.u32 %0, 1, 0, p;\n}" : "=r"(r));
    return r;
}
__device__ __forceinline__ int uni(int v) { return __shfl_sync(~0u, v, 0); }
__device__ __forceinline__ void calibrate(uint32_t cal, float keep) {
    const uint32_t t0 = gtick();
    uint32_t t, it = 0;
    do { t = gtick(); spin_guard(it); } while (__any_sync(~0u, t == t0));
    const uint32_t c = clk();
    const uint4 p = lds4u(cal);
    const float cpt = 256.f * fminf(fmaxf(__fdividef((float)(c - p.y), (float)((t - p.x) & 0x7FFFFFF)), 16.f), 128.f);
    __syncwarp();
    sts4u(cal, make_uint4(t, c, (uint32_t)(keep > 0.f ? fmaf(keep, (float)p.z - cpt, cpt) : cpt), 0));
}
struct Stamps { uint32_t v[6]; };
__device__ __forceinline__ void load_stamps2(Stamps& t, const uint32_t* f, uint32_t l16, bool on = true) {
    const char* p = reinterpret_cast<const char*>(f) + (l16 >> 2) * FSTR;
    asm volatile("{\n.reg .pred p;\nsetp.ne.u32 p, %7, 0;\nmov.u32 %0, 63;\nmov.u32 %1, 63;\nmov.u32 %2, 63;\nmov.u32 %3, 63;\nmov.u32 %4, 63;\nmov.u32 %5, 63;\n"
                 "@p ld.relaxed.gpu.global.v2.u32 {%0, %1}, [%6];\n@p ld.relaxed.gpu.global.v2.u32 {%2, %3}, [%6 + %8];\n"
                 "@p ld.relaxed.gpu.global.v2.u32 {%4, %5}, [%6 + %9];\n}"
                 : "=&r"(t.v[0]), "=&r"(t.v[1]), "=&r"(t.v[2]), "=&r"(t.v[3]), "=&r"(t.v[4]), "=&r"(t.v[5])
                 : "l"(p), "r"((uint32_t)on), "n"(128 * FSTR), "n"(256 * FSTR) : "memory");
}
template <int N>
__device__ __forceinline__ uint32_t stamps_missing(const uint32_t* v, int s) {
    uint32_t x = 0;
#pragma unroll
    for (int i = 0; i < N; i++) x |= v[i] ^ s;
    return x & 63;
}
template <int N>
__device__ __forceinline__ uint32_t latest_stamp(const uint32_t* v, const uint4 cal) {
    int late = (int)(v[0] - (cal.x << 6));
#pragma unroll
    for (int i = 1; i < N; i++) late = max(late, (int)(v[i] - (cal.x << 6)));
    return cal.y + (((late >> 6) * (int)cal.z) >> 8);
}
__device__ __forceinline__ void wait_clock(uint32_t target, uint32_t range = 65536) {
    while (__any_sync(~0u, target - clk() < range)) {}
}

template <int BYTES>
__device__ __forceinline__ bool incomplete(uint32_t buf, uint32_t l16) {
    uint32_t m = 0;
#pragma unroll 1
    for (int o = 0; o < BYTES; o += 256) m = max(m, umax4(lds4u(buf + o + (l16 & 255))));
    return __any_sync(~0u, m == ~0u);
}
__device__ __forceinline__ void refetch(uint32_t buf, const uint4* src, uint32_t bytes, uint32_t b, int w4, int barid, uint32_t& tries) {
    spin_guard(tries);
    bar_sync(barid, 128);
    if (w4 == 0 && elect()) { mbar_expect(b, bytes); bulk_ld(buf, src, bytes, b); }
    __syncwarp();
    mbar_wait(b, 0);
    bar_sync(barid, 128);
    if (w4 == 0 && elect()) mbar_arrive(b);
    __syncwarp();
}

__device__ __forceinline__ void load_box(const CUtensorMap* tA, const CUtensorMap* tB, int cl, int rank, uint32_t dst, int j, int q, uint32_t b) {
    const bool isb = (q ^ (q >> 1)) & 1;
    tma2d(dst + q * 16384, isb ? tB : tA, cl * 256 + (rank >= 4 ? (rank - 4) * 128 + isb * 64 : rank * 64), (q >> 1) * 512 + j * 128, b);
}

template <bool ISV, int WG>
__device__ __forceinline__ void chain_main(const CUtensorMap* tWo, const uint32_t sb, const int cl, const int rank, const Descs& D,
                                           const uint32_t (&wk)[24][4], const uint32_t (&wv)[24][4], uint32_t a_adr) {
    const int tid = threadIdx.x;
    uint32_t l16 = __shfl_sync(~0u, (tid & 31) * 16, tid & 31);
    int w4 = uni((tid >> 5) & 3);
    const int role = ISV ? 2 : (rank & 1), hh = ISV ? rank - 4 : rank >> 1, head = 2 * cl + hh;
    const uint32_t bar = sb + C_BAR;
    constexpr int ONK = ISV ? ONKV : ONKQ;
    const int ostart = (hh * 128 + role * ONKQ);

    if (NOFILL) { for (uint32_t o = C_WO + ONK * 2048 + tid * 16; o < C_BAR; o += 4096) sts4u(sb + o, make_uint4(0, 0, 0, 0)); bar_sync(6, 256); }
    constexpr uint32_t SLOT = ISV ? C_SLOTV : C_SLOTQ;
    constexpr int WS_A = (SB0 + C_WS + WG * 32768) >> 4, WO_A = (SB0 + C_WO) >> 4, MB_A = (SB0 + C_MB) >> 4;
#define XN_A(ks) (int)(((SB0 + C_XN + WG * 16384) >> 4) + ((ks) >> 2) * 256 + ((ks) & 3) * 2)
    const uint32_t slot = (sb + SLOT + w4 * 512), mbw = sb + C_MB + WG * 8192;
    const uint32_t sb_v = (mapa(sb, 4 + hh));
    const uint32_t sb_x = uni(mapa(sb, 2 * hh + (WG ? 1 : (~w4 & 1))));
    const uint32_t sb_o = (mapa(sb, w4));
    const uint32_t u_off = (ISV ? (head * 128 + w4 * 32) * 16 : (cl * 4 + rank) * 256 + (w4 & 1) * 128);
    const uint32_t v_row = (sb + C_V + (2 * WG + (w4 >> 1)) * 512), v_b = ((w4 & 1) * 64);
    const uint32_t u_flag = (blockIdx.x * FSTR);
    const uint32_t f_half = (w4 & 1) * role * (ONKV * 128), f_sb = uni(mapa(sb, rank + (w4 & 1) * (4 + hh - rank)));
    const uint32_t f_src = uni((ostart + (w4 & 1) * (2 - role) * ONKQ) * 256 + f_half), f_dst = uni(f_sb + C_MB + f_half);
    const uint32_t m_dst = (sb + C_MB + role * 8192), m_bar = (bar + (B_MF0 + role) * 8);
    uint32_t target;
    Stamps st1;
    uint4 cal;
    int s = -1;
    uint32_t pf[4][4];
    float xk[16], xv[16];
    float xsc[4];
    uint4 oxp[4];

    auto send_planes = [&](auto n, uint32_t a, int b, const float* v, bool hold) {
        const uint32_t dump = sb + C_DUMP + (l16 >> 2), to = a + (l16 >> 2), ad = hold ? dump : to;
        const uint32_t mb = hold ? (dump & 0xFF000000u) | (SB0 + C_BAR + B_DUMP * 8) : (to & 0xFF000000u) | (SB0 + C_BAR + b * 8);
        static_for<0, n.value>([&](auto i) { st_async1f<i.value * 128>(ad, mb, v[i.value]); });
    };
    auto send_scores = [&]() {
        bar_sync(12, 256);
        if (!NOFILL) send_planes(ic<4>{}, sb_x + C_XSL + role * 2560 + (1 + w4) * 512, B_XS, xsc, s < 0);
    };
    auto store_ox = [&](int ss) {
        char* orow = reinterpret_cast<char*>(g_ox) + (ss * (32 * HD * 2) + (u_off >> 3) + (l16 >> 6) * (HD * 2) + (l16 & 48));
#pragma unroll
        for (int i = 0; i < 4; i++) st_pred4(orow + i * (8 * HD * 2), oxp[i], ss >= 0);
    };
    auto load_blocks = [&](int seg, int wina, int g, uint32_t off, uint32_t bytes, int b) {
        const int khalf = ISV ? 1 - wina : wina;
        if (!NOFILL && elect()) {
            mbar_expect(bar + b * 8, bytes);
            bulk_ld(sb + C_XN + g * 16384 + off, g_xc + (seg * 4 + khalf * 2 + g) * 1024 + off / 16, bytes, bar + b * 8);
        }
        __syncwarp();
    };
    auto load_tokens = [&](int seg, int wina, int g) { load_blocks(seg, wina, g, 0, 16384, B_XF0 + g); };
    auto prefetch = [&]() {
#pragma unroll
        for (int i = 0; i < 4; i++) ldsm4t(pf[i], a_adr + C_WS + (i & 1) * 16384 + (i >> 1) * 2048);
    };
    constexpr int HA = ISV ? 0 : 1, NB = (ISV || NOFILL) ? 0 : QNB, NK1 = ISV ? 0 : QK1;
    constexpr bool TAKE1 = ISV ? TAKEV : (TAKEQ || QK1 == 16);
    auto products = [&](auto give, auto half, auto init, auto i0, auto i1, const uint64_t d) {
        static_for<i0.value, i1.value>([&](auto i) {
            constexpr int ks = half.value * 16 + i.value, acc = !(init.value && i.value == i0.value);
            if constexpr (ks >= 24) wg32_ss<acc, WS_A + give.value * 1024 + (ks - 24) * 128, XN_A(i.value)>(give.value ? xv : xk, d);
            else if constexpr (give.value) wg32_rs<acc, XN_A(i.value)>(xv, wv[ks], d);
            else wg32_rs<acc, XN_A(i.value)>(xk, wk[ks], d);
        });
    };
    auto stream_a = [&](const uint64_t dk, const uint64_t dv, auto mid) {
        if (NOFILL) { mid(); return; }
        constexpr int F = (WG == 0 && SSFIRST) ? 8 : 0;
        wg_fence();
        products(ic<0>{}, ic<HA>{}, ic<1>{}, ic<F>{}, ic<F + 8>{}, dk);
        products(ic<1>{}, ic<HA>{}, ic<1>{}, ic<F>{}, ic<F + 8>{}, dv);
        if (NB && WG == 1) wg_commit();
        products(ic<1>{}, ic<HA>{}, ic<0>{}, ic<8 - F>{}, ic<16 - F>{}, dv);
        if (NB && WG == 1) {
            wg_commit();
            wg_wait<1>();
            if (l16 == 0) mbar_arrive(bar + B_H1 * 8);
        }
        mid();
        products(ic<0>{}, ic<HA>{}, ic<0>{}, ic<8 - F>{}, ic<16 - F>{}, dk);
        wg_commit();
    };
    auto token_scores = [&](float* e) {
        const int hi = w4 - 2, lane = l16 >> 4;
        const uint32_t src = sb + C_XSL + hi * 256 + (l16 & 255) + (l16 >> 8) * 2560;
        const int d0 = 16 * role + 8 * hi + (lane >> 2) - 2 * (lane & 3);
        mbar_wait(bar + B_XS * 8, s & 1);
#pragma unroll
        for (int i = 0; i < 5; i++) {
            if (i == 3) __syncwarp();
            float a[4];
            ldsm4f(a, src + i * 512);
            e[2 * i] = (i == 0 || d0 >= 8 * (i - 1)) ? a[0] + a[2] : -INFINITY;
            e[2 * i + 1] = (i == 0 || d0 > 8 * (i - 1)) ? a[1] + a[3] : -INFINITY;
        }
        reg_fence<10>(e);
    };
    auto token_softmax = [&](float* e) {
        const int hi = w4 - 2;
        float m = -INFINITY;
#pragma unroll
        for (int i = 0; i < 5; i++) m = fmaxf(m, fmaxf(e[2 * i], e[2 * i + 1]));
        m = fmaxf(m, __shfl_xor_sync(~0u, m, 1));
        m = fmaxf(m, __shfl_xor_sync(~0u, m, 2));
        m *= -SM_SCALE;
        float l = 0.f;
#pragma unroll
        for (int i = 0; i < 10; i++) { e[i] = ex2(fmaf(e[i], SM_SCALE, m)); l += e[i]; }
        l += __shfl_xor_sync(~0u, l, 1);
        l += __shfl_xor_sync(~0u, l, 2);
        l = rcp(l);
        const uint32_t pd = sb_v + C_PL + (s & 1) * 2048 + role * 768 + hi * 128 + (l16 >> 2), pb = sb_v + C_BAR + (B_P0 + (s & 1)) * 8;
        st_async1(pd, pb, pack2(e[0] * l, e[1] * l));
        st_async1(pd + 256, pb, pack2(e[2] * l, e[3] * l));
        st_async1(pd + 512, pb, pack2(e[4] * l, e[5] * l));
        if (role) {
            st_async1(pd + 768, pb, pack2(e[6] * l, e[7] * l));
            st_async1(pd + 1024, pb, pack2(e[8] * l, e[9] * l));
        }
        if (hi == 0 && l16 == 0) mbar_expect(bar + B_XS * 8, 3072 + role * 2048);
        __syncwarp();
    };

    auto windows = [&]() {
        asm volatile("" : "+r"(l16), "+r"(w4));
        const uint64_t* const dd = D.sw;
        TS(5);
        float xe[10];
        if constexpr (WG == 1) {
            TS(6);
            if (ISV) bar_sync(3, 256); else send_scores();
            uint32_t missing;
            stream_a(dd[0], dd[1], [&]() {
                if (ISV) return;
                __syncwarp();
                const uint32_t zero = late_zero();
                uint4 cz = cal;
                cz.x += zero;
                missing = stamps_missing<6>(st1.v, s + zero);
                target = latest_stamp<6>(st1.v, cz) + DLY1;
                asm volatile("" : "+r"(missing), "+r"(target));
            });
            if (!NOFILL) bar_arrive(7, 256);
            if (ISV) {
                if (!NOFILL) store_ox(s - 1);
                st_relaxed4(reinterpret_cast<uint4*>(reinterpret_cast<char*>(&g_xo[(s + 2) & 3][0]) + (u_off + l16)), make_uint4(~0u, ~0u, ~0u, ~0u));
            }
            auto fetch_o = [&]() {
            if (!ISV && w4 < 2 && s >= 0) {
                const char* src = reinterpret_cast<const char*>(&g_xo[s & 3][0]) + f_src;
                if (__builtin_expect(__any_sync(~0u, missing), 0)) {
                    uint32_t it = 0;
                    do { load_stamps2(st1, g_flag[0], l16); spin_guard(it); } while (__any_sync(~0u, stamps_missing<6>(st1.v, s)));
                    target = latest_stamp<6>(st1.v, lds4u(sb + C_CAL)) + DLY1;
                }
                mbar_wait(bar + B_VF * 8, s & 1);
                TS(10);
                wait_clock(target);
                if (elect()) bulk_ld(f_dst, src, ONKQ * 256 - w4 * (ONKQ * 256 - ONKV * 128), f_sb + C_BAR + B_OF * 8);
                __syncwarp();
                TS(8);
            }
            };
            fetch_o();
            if (!NOFILL) {
                wg_wait<0>();
                reg_fence<16>(xk); reg_fence<16>(xv);
                if (w4 == 1) {
                    bar_sync(2, 128);
                    wait_clock(clk() + (ISV ? DLYS : DLYB));
                    load_blocks(s + 1, 0, 1, NB ? 8192 : 0, NB ? 8192 : 16384, B_XF1);
                } else {
                    bar_arrive(2, 128);
                }
                if (!ISV) {
#pragma unroll
                    for (int i = 0; i < 10; i++) xe[i] = 0.f;
                    if (w4 >= 2 && s >= 0) token_scores(xe);
                }
                if (NB) {
                    mbar_wait(bar + B_XF2 * 8, (s + 1) & 1);
                    mbar_wait(bar + B_A0 * 8, (s + 1) & 1);
                    wg_fence();
                    products(ic<1>{}, ic<1 - HA>{}, ic<0>{}, ic<0>{}, ic<NB>{}, dd[3]);
                    wg_commit();
                }
            }
            TS(7);
        } else {
            if (!NOFILL) {
                mbar_wait(bar + B_XF0 * 8, 0);
                if (NB && w4 == 3) { mbar_wait(bar + B_H1 * 8, (s + 1) & 1); load_blocks(s + 1, 0, 1, 0, 8192, B_XF2); }
                bar_sync(7, 256);
            }
            TS(6);
            stream_a(dd[0], dd[1], []() {});
            if (NB && l16 == 0) mbar_arrive(bar + B_A0 * 8);
        }
        if constexpr (WG == 0) {
            if (s >= 0) {
                const uint32_t dst = sb_o + C_OL + rank * 512;
                uint32_t can = sb + C_MB + l16 * 8 + (l16 >> 2), can2 = can + (l16 < (ONK * 2 - 64) * 16 ? 8192 : 0);
                asm volatile("" : "+r"(can), "+r"(can2));
                float co[4];
                TS(7);
                uint32_t tries = 0;
                mbar_wait(bar + B_OF * 8, s & 1);
                TS(8);
                const uint32_t c0 = lds1u(can), c1 = lds1u(can + 4096), c2 = lds1u(can2);
                __syncwarp();
                wg8_chain<0, OHEAD, WO_A, MB_A>(co, D.sw[0], D.ns);
                __syncwarp();
                {
                    const uint32_t z = late_zero();
                    if (__builtin_expect(__any_sync(~0u, max(max(c0 | z, c1 | z), c2) == CANARY), 0)) {
                        wg_wait<0>();
                        do refetch(sb + C_MB, &g_xo[s & 3][ostart * 16], ONK * 256, bar + B_RT0 * 8, w4, 1, tries);
                        while (__any_sync(~0u, max(max(lds1u(can), lds1u(can + 4096)), lds1u(can2)) == CANARY));
                        wg8_chain<0, OHEAD, WO_A, MB_A>(co, DSW, DNS);
                    }
                }
                wg_wait<1>();
                if (l16 == 0) mbar_arrive(bar + B_GO * 8);
                wg8_chain<OHEAD, ONK - OTAIL, WO_A, MB_A>(co, D.sw[0], D.ns);
                static_for<ONK - OTAIL, ONK>([&](auto i) { wg8_ss<1, WO_A + i.value * 128, MB_A + i.value * 16>(co, D.sw[0], D.ns); });
                wg_commit();
                wg_wait<1>();
                bar_arrive(5, 256);
                wg_wait<0>();
                reg_fence<4>(co);
                const bool nan = co[0] != co[0] || co[1] != co[1];
                send_planes(ic<4>{}, dst, B_OL, co, nan);
                if (__builtin_expect(__any_sync(~0u, nan), 0)) {
                    while (incomplete<ONK * 256>(sb + C_MB, l16)) {
                        refetch(sb + C_MB, &g_xo[s & 3][ostart * 16], ONK * 256, bar + B_RT0 * 8, w4, 1, tries);
                        co[0] = co[1] = co[2] = co[3] = 0.f;
#pragma unroll 1
                        for (int i = 0; i < ONK; i++) {
                            wg_fence();
                            wg8_ss<1, WO_A, MB_A>(co, DSW + i * 128, DNS + i * 16);
                            wg_commit();
                            wg_wait<0>();
                        }
                        reg_fence<4>(co);
                    }
                    send_planes(ic<4>{}, dst, B_OL, co, !nan);
                }
                TS(9);
                if (l16 < 48 && w4 == 3) mbar_expect(bar + B_MF0 * 8 + (l16 >> 1), l16 == 32 ? ONK * 256 : 8192);
            } else {
                wg_wait<0>();
                if (l16 == 0) mbar_arrive(bar + B_GO * 8);
                bar_arrive(5, 256);
            }
            if (l16 < 32) mbar_arrive_cluster(mapa(bar + B_MBF * 8, 2 * hh + (l16 >> 4)));
            __syncwarp();
            if (!NOFILL) { reg_fence<16>(xk); reg_fence<16>(xv); }
        } else {
            if (w4 < 2) {
                if (w4 == 1) {
                    mbar_wait(bar + B_GO * 8, (s + 1) & 1);
                    load_tokens(s + 1, 0, 0);
                    if (PFX && ISV && s + 3 < NSEG && elect())
                        asm volatile("cp.async.bulk.prefetch.L2.global [%0], 8192;" :: "l"(g_xc + (s + 3) * 4096 + ((cl & 3) * 2 + hh) * 512) : "memory");
                    __syncwarp();
                } else if (!ISV) {
                    calibrate(sb + C_CAL, 0.75f);
                }
                if (!ISV) st_relaxed1(reinterpret_cast<char*>(&g_xmem[(s + 3) & 3][0]) + (u_off + (l16 >> 2)), ~0u);
            } else if (!NOFILL && s >= 0) {
                if (ISV && w4 == 2 && (s & 3) == 1 && s > 1 && l16 == 0) count_up(CNT_OX + (s >> 2) - 1);
                __syncwarp();
                if (!ISV) token_softmax(xe);
                TSX(9, w4 == 2);
            }
            if (!NOFILL) mbar_wait(bar + B_XF1 * 8, 1);
            bar_sync(5, 256);
        }
        asm volatile("" : "+r"(l16), "+r"(w4));
        TSX(11, w4 == 0 && (WG || ISV));
        uint32_t v_dst = ISV ? v_row + ((s + 1) & 1) * 10240 + ((l16 & 384) << 4) + ((l16 & 96) << 2) + ((l16 & 112) ^ v_b)
                             : sb + C_QX + WG * 4096 + w4 * 1024 + l16;
        uint32_t v_dst2 = v_dst ^ 32;
        if (WG == 0) {
            v_dst = __shfl_sync(~0u, v_dst, l16 >> 4);
            if (ISV) v_dst2 = __shfl_sync(~0u, v_dst2, l16 >> 4);
        }
        constexpr int NR = SWAP16 ? 2 : 4;
        constexpr uint32_t OUT = SWAP16 ? WG * 4096 : 0, IN = SWAP16 ? (WG ^ 1) * 4096 : 0;
        auto give = [&]() {
#pragma unroll
            for (int j = 0; j < NR; j++) {
                if (SWAP16) stsm4(slot + OUT + l16 + j * 2048, pack2(xv[8 * j], xv[8 * j + 1]), pack2(xv[8 * j + 2], xv[8 * j + 3]),
                                  pack2(xv[8 * j + 4], xv[8 * j + 5]), pack2(xv[8 * j + 6], xv[8 * j + 7]));
                else stsm4f(slot + l16 + j * 2048, xv + 4 * j);
            }
        };
        auto take = [&](uint32_t (*r)[4]) {
#pragma unroll
            for (int j = 0; j < NR; j++) ldsm4(r[j], slot + IN + l16 + j * 2048);
        };
        auto store_tokens = [&](const uint32_t (*r)[4]) {
            uint32_t lo[4], hi[4];
#pragma unroll
            for (int j = 0; j < 4; j++) {
                if (SWAP16) {
                    const uint32_t a = r[j >> 1][(j & 1) * 2], b = r[j >> 1][(j & 1) * 2 + 1];
                    lo[j] = pack2(xk[4 * j] + bf_lo(a), xk[4 * j + 1] + bf_hi(a));
                    hi[j] = pack2(xk[4 * j + 2] + bf_lo(b), xk[4 * j + 3] + bf_hi(b));
                } else {
                    lo[j] = pack2(xk[4 * j] + __uint_as_float(r[j % NR][0]), xk[4 * j + 1] + __uint_as_float(r[j % NR][1]));
                    hi[j] = pack2(xk[4 * j + 2] + __uint_as_float(r[j % NR][2]), xk[4 * j + 3] + __uint_as_float(r[j % NR][3]));
                }
            }
            if (!ISV) {
                stsm4t(v_dst, lo[0], lo[1], lo[2], lo[3]);
                stsm4t(v_dst + 512, hi[0], hi[1], hi[2], hi[3]);
            } else {
                stsm4(v_dst, lo[0], lo[1], lo[2], lo[3]);
                stsm4(v_dst2, hi[0], hi[1], hi[2], hi[3]);
            }
        };
        if constexpr (WG == 1) {
            if (!NOFILL) {
                wg_fence();
                products(ic<1>{}, ic<1 - HA>{}, ic<0>{}, ic<NB>{}, ic<16>{}, dd[3]);
                products(ic<0>{}, ic<1 - HA>{}, ic<0>{}, ic<0>{}, ic<NK1>{}, dd[2]);
                wg_commit();
                if (ISV) {
                    bar_arrive(7, 256);
                } else {
                    mbar_wait(bar + B_MBF * 8, (s + 1) & 1);
                    bar_sync(7, 256);
                }
                wg_wait<0>();
                reg_fence<16>(xv); reg_fence<16>(xk);
                give();
                bar_arrive(8, 256);
            }
            TS(12);
            prefetch();
            if (!ISV && w4 == 0) {
                const uint4* src = &g_xmem[(s + 1) & 3][role * 512];
                if (NOFILL) mbar_wait(bar + B_MBF * 8, (s + 1) & 1);
                TS(3);
                wait_clock(target + DLY2, s >= 0 ? 65536 : 0);
                if (hh) { if (elect()) bulk_mc(m_dst, src, 8192, m_bar, 0x2C); }
                else if (elect()) bulk_mc(m_dst, src, 8192, m_bar, 0x13);
                __syncwarp();
                TS(4);
            }
            if (!NOFILL) {
                uint32_t r[NR][4];
                if (TAKE1) { bar_sync(9, 256); take(r); }
                if (NK1 < 16) {
                    bar_sync(14, 256);
                    wg_fence();
                    products(ic<0>{}, ic<1 - HA>{}, ic<0>{}, ic<NK1>{}, ic<16>{}, dd[2]);
                    wg_commit();
                    if (!TAKE1) { __syncwarp(); take(r); }
                    wg_wait<0>();
                    reg_fence<16>(xk);
                }
                TS(13);
                store_tokens(r);
                bar_arrive(10, 256);
                if (w4 != 3) bar_arrive(13, 128);
            }
        } else {
            uint32_t r[NR][4];
            if (!NOFILL) mbar_wait(bar + B_XF0 * 8, 1);
            if (!ISV && w4 < 2 && s >= 0) {
                char* gd = reinterpret_cast<char*>(&g_xmem[(s + 1) & 3][0]) + (u_off + (l16 >> 2));
                const uint32_t src = sb + C_OL + w4 * 256 + l16 + (l16 & 256);
                mbar_wait(bar + B_OL * 8, s & 1);
                TSD(3);
                float a[3][4];
#pragma unroll
                for (int i = 0; i < 3; i++) ldsm4f(a[i], src + i * 1024);
                st_relaxed1(gd, movm(pack2((a[0][0] + a[0][2]) + (a[1][0] + a[1][2]) + (a[2][0] + a[2][2]),
                                           (a[0][1] + a[0][3]) + (a[1][1] + a[1][3]) + (a[2][1] + a[2][3]))));
                TS(11);
                if (w4 == 0 && l16 == 0) mbar_expect(bar + B_OL * 8, 3072);
                __syncwarp();
            }
            if (!NOFILL) {
                bar_sync(7, 256);
                TS(12);
                wg_fence();
                products(ic<1>{}, ic<1 - HA>{}, ic<0>{}, ic<0>{}, ic<16>{}, dd[3]);
                wg_commit();
                products(ic<0>{}, ic<1 - HA>{}, ic<0>{}, ic<0>{}, ic<6>{}, dd[2]);
                wg_commit();
                bar_sync(8, 256);
                take(r);
                wg_wait<1>();
                reg_fence<16>(xv);
                give();
                if (TAKE1) bar_arrive(9, 256);
                products(ic<0>{}, ic<1 - HA>{}, ic<0>{}, ic<6>{}, ic<16>{}, dd[2]);
                wg_commit();
                if (NK1 < 16) bar_arrive(14, 256);
                wg_wait<0>();
                reg_fence<16>(xk);
            }
            TS(13);
            if (!NOFILL) store_tokens(r);
            prefetch();
        }
    };

    if (tid == 0) TL(1, 2);
    if (w4 == 0) load_tokens(0, 1, WG);
    if (WG == 0) {
        if (WOLATE && !NOFILL) mbar_wait(bar + B_XF0 * 8, 0);
        if (elect()) {
#pragma unroll 1
            for (int i = w4; i < ONK; i += 4) tma2d(sb + C_WO + i * 2048, tWo, cl * 64, (ostart + i) * 16, bar + B_OF * 8);
        }
        __syncwarp();
    }
    mbar_wait(bar + B_WS * 8, 0);
    if (WG == 1 && !NOFILL) mbar_wait(bar + B_XF1 * 8, 0);
    if (WG == 0) bar_arrive(ISV ? 3 : 12, 256);
    xsc[0] = xsc[1] = xsc[2] = xsc[3] = 0.f;
    load_stamps2(st1, g_flag[0], l16, false);
    cal = make_uint4(0, 0, 0, 0);
    oxp[0] = oxp[1] = oxp[2] = oxp[3] = make_uint4(0, 0, 0, 0);

#pragma unroll 1
    while (true) {
        windows();
        s++;

        asm volatile("" : "+r"(l16), "+r"(a_adr), "+r"(w4));
        TS_FLUSH(WG);
        TS(0);
        float ck[4], cv[4], dk[4], dv[4];
        uint32_t b[3][4], tries = 0;
        const uint32_t kl = sb + C_KX + ((l16 & 384) << 2) + (l16 & 112);
        auto load_b = [&](auto kp) { ldsm4(b[kp.value % 3], mbw + l16 + ((kp.value & 3) ? (kp.value >> 2) * 3 + (kp.value & 3) - 1 : 12 + (kp.value >> 2)) * 512); };
        auto kpair = [&](auto kp_) {
            constexpr int kp = kp_.value, grp = kp >> 2, ph = kp & 3;
            if constexpr (kp > 0 && kp < 14) load_b(ic<kp + 2>{});
            const uint32_t* bb = b[kp % 3];
            if constexpr (ph != 0) {
                constexpr int q = (grp * 3 + ph - 1) * 2;
                static_for<(ph == 1 ? 0 : ph), ph + 1>([&](auto i) {
                    if constexpr (grp < 3) ldsm4t(pf[i.value], a_adr + C_WS + (i.value & 1) * 16384 + (grp * 2 + 2 + (i.value >> 1)) * 2048);
                });
                __syncwarp();
                mma16(cv, wv[q][0], wv[q][1], wv[q][2], wv[q][3], bb[0], bb[1]);
                mma16(ck, wk[q][0], wk[q][1], wk[q][2], wk[q][3], bb[0], bb[1]);
                mma16(dv, wv[q + 1][0], wv[q + 1][1], wv[q + 1][2], wv[q + 1][3], bb[2], bb[3]);
                mma16(dk, wk[q + 1][0], wk[q + 1][1], wk[q + 1][2], wk[q + 1][3], bb[2], bb[3]);
            } else {
                if constexpr (kp == 0) {
#pragma unroll
                    for (int i = 0; i < 4; i++) ck[i] = cv[i] = dk[i] = dv[i] = 0.f;
                }
                mma16(ck, pf[0][0], pf[0][1], pf[0][2], pf[0][3], bb[0], bb[1]);
                mma16(cv, pf[1][0], pf[1][1], pf[1][2], pf[1][3], bb[0], bb[1]);
                mma16(dk, pf[2][0], pf[2][1], pf[2][2], pf[2][3], bb[2], bb[3]);
                mma16(dv, pf[3][0], pf[3][1], pf[3][2], pf[3][3], bb[2], bb[3]);
            }
        };
        auto hand_over = [&]() {
#pragma unroll
            for (int i = 0; i < 4; i++) { cv[i] += dv[i]; ck[i] += dk[i]; }
            if (ISV) {
                stsm4f(slot + WG * 2048 + l16, cv);
            } else {
                const float *q = WG ? cv : ck, *k = WG ? ck : cv;
                stsm4t(slot + WG * 2048 + l16, pack2(q[0], q[1]), pack2(q[2], q[3]), pack2(k[0], k[1]), pack2(k[2], k[3]));
            }
        };
        auto repair = [&]() {
            bar_sync(6, 256);
            while (incomplete<8192>(mbw, l16)) {
                refetch(mbw, &g_xmem[s & 3][WG * 512], 8192, bar + (B_RT0 + WG) * 8, w4, 1 + WG, tries);
                prefetch();
                static_for<0, 3>(load_b);
                static_for<0, 16>(kpair);
                hand_over();
            }
            bar_sync(6, 256);
        };
        {
            const uint32_t can = mbw + l16 * 8 + (l16 >> 2);
            uint32_t* const flag = &g_flag[0][u_flag + WG + l16];
            for (;; tries |= 1) {
                asm volatile("" : "+r"(tries));
                if (__builtin_expect(tries, 0)) {
                    refetch(mbw, &g_xmem[s & 3][WG * 512], 8192, bar + (B_RT0 + WG) * 8, w4, 1 + WG, tries);
                }
                mbar_wait(bar + (B_MF0 + WG) * 8, s & 1);
                TS(1);
                static_for<0, 3>(load_b);
                const uint32_t c0 = lds1u(can), c1 = lds1u(can + 4096);
                const uint32_t v = ((gtick() - (ISV ? VLEAD : 0)) << 6) | s;
                kpair(ic<0>{});
                const bool early = __any_sync(~0u, max(c0, c1) == CANARY);
                st_pred1(flag, v, w4 * 512 + l16 == 1536 && !early);
                if (__builtin_expect(!early, 1)) break;
            }
            static_for<1, RFPOS>(kpair);
            if (WG == 0 && !NOFILL) bar_sync(10, 256);
            if (WG == 1 && !NOFILL && w4 == 3) {
                bar_sync(13, 128);
                if (s < NSEG - 1) load_tokens(s + 1, 1, 1);
            }
            static_for<RFPOS, 13>(kpair);
        }
        auto finish_projections = [&]() {
            static_for<13, 16>(kpair);
            hand_over();
            TS(2);
            return bar_sync_any_nan(cv[0], cv[1]);
        };
        if constexpr (!ISV) {
            const uint32_t qa = sb + C_SLOTQ + ((l16 >> 1) & 128) + ((l16 & 128) << 3) + (l16 & 112);
            const uint32_t ma = sb + C_SLOTQ + 256 + l16 + (l16 & 256);
            const uint32_t qx = sb + C_QX + l16 + (l16 & 256);
            auto ldsm_sum = [&](uint32_t* r, uint32_t a) {
                uint32_t t[4];
                ldsm4(r, a); ldsm4(t, a + 2048);
#pragma unroll
                for (int i = 0; i < 4; i++) asm("add.rn.bf16x2 %0, %0, %1;" : "+r"(r[i]) : "r"(t[i]));
            };
            auto tile = [&](float* d, const uint32_t (*q)[4], const uint32_t (*k)[4]) {
                d[0] = d[1] = d[2] = d[3] = 0.f;
#pragma unroll
                for (int i = 0; i < 4; i++) mma16(d, q[i][0], q[i][1], q[i][2], q[i][3], k[i >> 1][(i & 1) * 2], k[i >> 1][(i & 1) * 2 + 1]);
            };
            auto send = [&](int ti, const float* d, bool hold) {
                send_planes(ic<4>{}, sb_x + C_XSL + role * 2560 + ti * 512, B_XS, d, hold);
            };
            if constexpr (WG == 0) {
                auto scores = [&](auto again) {
                    bool nan = false;
                    if (w4 < 2) {
                        uint32_t k0[2][4], k1[2][4], q0[4], q1[4];
                        const uint32_t ka = kl + w4 * 256, dst = sb_v + C_SL + role * 1024 + w4 * 512;
                        ldsm4(k0[0], ka); ldsm4(k0[1], ka + 2048);
                        ldsm4(k1[0], ka + 128); ldsm4(k1[1], ka + 128 + 2048);
                        __syncwarp();
                        if (!again.value) nan = finish_projections();
                        TS(3);
                        ldsm_sum(q0, qa); ldsm_sum(q1, qa + 512);
                        float s0[4] = {0.f, 0.f, 0.f, 0.f}, s1[4] = {0.f, 0.f, 0.f, 0.f}, s2[4] = {0.f, 0.f, 0.f, 0.f}, s3[4] = {0.f, 0.f, 0.f, 0.f};
                        mma16(s0, q0[0], q0[1], q0[2], q0[3], k0[0][0], k0[0][1]);
                        mma16(s1, q0[0], q0[1], q0[2], q0[3], k0[1][0], k0[1][1]);
                        mma16(s2, q0[0], q0[1], q0[2], q0[3], k1[0][0], k1[0][1]);
                        mma16(s3, q0[0], q0[1], q0[2], q0[3], k1[1][0], k1[1][1]);
                        mma16(s0, q1[0], q1[1], q1[2], q1[3], k0[0][2], k0[0][3]);
                        mma16(s1, q1[0], q1[1], q1[2], q1[3], k0[1][2], k0[1][3]);
                        mma16(s2, q1[0], q1[1], q1[2], q1[3], k1[0][2], k1[0][3]);
                        mma16(s3, q1[0], q1[1], q1[2], q1[3], k1[1][2], k1[1][3]);
                        const float out[4] = {s0[0] + s1[2], s0[1] + s1[3], s2[0] + s3[2], s2[1] + s3[3]};
                        send_planes(ic<4>{}, dst, B_SC, out, nan);
                        TS(4);
                        if (XS0 && !again.value && !NOFILL && w4 == 0) {
                            uint32_t q[4][4];
                            float d1[4], d2[4];
#pragma unroll
                            for (int i = 0; i < 4; i++) ldsm4(q[i], qx + i * 1024);
                            tile(d1, q, k0); tile(d2, q, k1);
                            bar_sync(12, 256);
                            send_planes(ic<4>{}, mapa(sb, 2 * hh) + C_XSL + role * 2560 + 512, B_XS, d1, false);
                            send_planes(ic<4>{}, mapa(sb, 2 * hh) + C_XSL + role * 2560 + 1024, B_XS, d2, false);
                        } else if (!again.value) {
                            bar_arrive(12, 256);
                        }
                    } else if (w4 == 2) {
                        uint32_t q0[4], q1[4], km[2][4], q[4][4];
                        const uint32_t dst = sb_v + C_SL + 2048 + role * 256;
                        if (!again.value) nan = finish_projections();
                        ldsm_sum(q0, qa); ldsm_sum(km[0], ma); ldsm_sum(km[1], ma + 1024); ldsm_sum(q1, qa + 512);
                        __syncwarp();
#pragma unroll
                        for (int i = 0; i < 4; i++) ldsm4(q[i], qx + 256 + i * 1024);
                        float s0[4] = {0.f, 0.f, 0.f, 0.f}, s1[4] = {0.f, 0.f, 0.f, 0.f}, d0[4];
                        mma16(s0, q0[0], q0[1], q0[2], q0[3], km[0][0], km[0][1]);
                        mma16(s1, q0[0], q0[1], q0[2], q0[3], km[1][0], km[1][1]);
                        mma16(s0, q1[0], q1[1], q1[2], q1[3], km[0][2], km[0][3]);
                        mma16(s1, q1[0], q1[1], q1[2], q1[3], km[1][2], km[1][3]);
                        const float out[2] = {s0[0] + s1[2], s0[1] + s1[3]};
                        send_planes(ic<2>{}, dst, B_SC, out, nan);
                        if (!NOFILL) tile(d0, q, km);
                        if (!again.value) bar_sync(12, 256);
                        if (!NOFILL) send(0, d0, nan);
                    } else {
                        if (!again.value) {
                            nan = finish_projections();
                            if (s < NSEG - 1) load_tokens(s + 1, 1, 0);
                        }
                        uint32_t q[4][4], k0[2][4], k1[2][4], km[2][4];
                        float d0[4], d1[4], d2[4];
                        if (!NOFILL) {
#pragma unroll
                            for (int i = 0; i < 4; i++) ldsm4(q[i], qx + i * 1024);
                            if (!XS0) {
                                ldsm4(k0[0], kl); ldsm4(k0[1], kl + 2048);
                                ldsm4(k1[0], kl + 128); ldsm4(k1[1], kl + 128 + 2048);
                                tile(d1, q, k0); tile(d2, q, k1);
                            }
                            ldsm_sum(km[0], ma); ldsm_sum(km[1], ma + 1024);
                            tile(d0, q, km);
                        }
                        if (!again.value) bar_sync(12, 256);
                        if (!NOFILL) { send(0, d0, nan); if (!XS0) { send(1, d1, nan); send(2, d2, nan); } }
                    }
                    return nan;
                };
                if (__builtin_expect(__any_sync(~0u, scores(ic<0>{})), 0)) { repair(); scores(ic<1>{}); bar_arrive(12, 256); }
                if (__builtin_expect(s == NSEG - 1, 0)) break;
            } else {
                const bool nan = finish_projections();
                load_stamps2(st1, g_flag[0], l16, w4 < 2);
                if (!NOFILL) mbar_wait(bar + B_XF1 * 8, s == NSEG - 1);
                cal = lds4u(sb + C_CAL);
                if (!NOFILL) {
                    uint32_t q[4][4], k0[2][4];
                    float d1[4] = {0.f, 0.f, 0.f, 0.f};
#pragma unroll
                    for (int i = 0; i < 4; i++) { ldsm4(q[i], qx + 256 + i * 1024); xsc[i] = 0.f; }
                    ldsm4(k0[0], kl + w4 * 128); ldsm4(k0[1], kl + w4 * 128 + 2048);
#pragma unroll
                    for (int i = 0; i < 4; i++) mma16((i & 1) ? d1 : xsc, q[i][0], q[i][1], q[i][2], q[i][3], k0[i >> 1][(i & 1) * 2], k0[i >> 1][(i & 1) * 2 + 1]);
#pragma unroll
                    for (int i = 0; i < 4; i++) xsc[i] += d1[i];
                }
                if (__builtin_expect(__any_sync(~0u, nan), 0)) {
                    bar_sync(12, 256);
                    repair();
                    load_stamps2(st1, g_flag[0], l16, false);
                    cal = lds4u(sb + C_CAL);
                }
                if (__builtin_expect(s == NSEG - 1, 0)) {
                    asm volatile("" : "+r"(l16));
                    send_scores();
                    if (w4 >= 2 && !NOFILL) { float e[10]; token_scores(e); token_softmax(e); }
                    break;
                }
            }
        } else {
            const uint32_t lane_b = sb + C_V + w4 * 512 + ((l16 & 384) << 4) + (l16 & 112);
            auto load_vx = [&](uint32_t (*vx)[4], int ss) {
#pragma unroll
                for (int j = 0; j < 4; j++) ldsm4(vx[j], ((lane_b + (ss & 1) * 10240) ^ (j * 32)) + j * 128);
            };
            auto load_vm = [&](uint32_t* vm, int ss) { ldsm4(vm, sb + C_V + (ss & 1) * 10240 + w4 * 512 + 8192 + (l16 ^ ((l16 >> 2) & 96))); };
            auto token_output = [&](int ss) {
                uint32_t vx[4][4], vm[4];
                const uint32_t pl = sb + C_PL + (ss & 1) * 2048 + l16;
                auto lds_frag = [&](uint32_t a) { uint32_t r[4]; ldsm4(r, a); return make_uint4(r[0], r[1], r[2], r[3]); };
                load_vm(vm, ss);
                load_vx(vx, ss);
                mbar_wait(bar + (B_P0 + (ss & 1)) * 8, (ss >> 1) & 1);
                uint32_t dep = 0;
#pragma unroll
                for (int mh = 1; mh >= 0; mh--) {
                    uint2 pm;
                    asm volatile("ldmatrix.sync.aligned.m8n8.x2.shared.b16 {%0,%1}, [%2];" : "=r"(pm.x), "=r"(pm.y) : "r"(pl + mh * 768 + dep) : "memory");
                    const uint4 p0 = lds_frag(pl + mh * 768 + 256);
                    float o[4][4];
#pragma unroll
                    for (int j = 0; j < 4; j++) { o[j][0] = o[j][1] = o[j][2] = o[j][3] = 0.f; mma8(o[j], pm.x, pm.y, vm[j]); }
#pragma unroll
                    for (int j = 0; j < 4; j++) mma16(o[j], p0.x, p0.y, p0.z, p0.w, vx[j][0], vx[j][1]);
                    if (mh) {
                        const uint4 p1 = lds_frag(pl + 1536);
#pragma unroll
                        for (int j = 0; j < 4; j++) mma16(o[j], p1.x, p1.y, p1.z, p1.w, vx[j][2], vx[j][3]);
                    }
                    oxp[2 * mh] = make_uint4(pack2(o[0][0], o[0][1]), pack2(o[1][0], o[1][1]), pack2(o[2][0], o[2][1]), pack2(o[3][0], o[3][1]));
                    oxp[2 * mh + 1] = make_uint4(pack2(o[0][2], o[0][3]), pack2(o[1][2], o[1][3]), pack2(o[2][2], o[2][3]), pack2(o[3][2], o[3][3]));
                    asm volatile("" : "+r"(oxp[2 * mh].x), "+r"(oxp[2 * mh].y), "+r"(oxp[2 * mh].z), "+r"(oxp[2 * mh].w),
                                 "+r"(oxp[2 * mh + 1].x), "+r"(oxp[2 * mh + 1].y), "+r"(oxp[2 * mh + 1].z), "+r"(oxp[2 * mh + 1].w));
                    dep = oxp[2].x == ~0u ? 16 : 0;
                }
            };
            const uint32_t vd = v_row + (s & 1) * 10240 + 8192 + ((l16 & 96) << 2) + ((l16 & 112) ^ v_b ^ ((l16 & 128) >> 2));
            uint32_t vx[4][4], vm[4];
            if (WG == 0) { load_vx(vx, s); __syncwarp(); }
            if (__builtin_expect(__any_sync(~0u, finish_projections()), 0)) { repair(); if (WG == 0) load_vx(vx, s); }
            float r[4];
            ldsm4f(r, slot + (WG ^ 1) * 2048 + l16);
            stsm2(vd, pack2(ck[0] + r[0], ck[1] + r[1]), pack2(ck[2] + r[2], ck[3] + r[3]));
            TSX(3, WG == 0 && w4 == 0);
            if (WG == 1) {
                bar_arrive(11, 256);
                if (w4 == 3 && l16 < 32) mbar_arrive_cluster(mapa(bar + B_VF * 8, 2 * hh + (l16 >> 4)));
                if (w4 == 2 && s < NSEG - 1) load_tokens(s + 1, 1, 0);
                if (!NOFILL) {
                    token_output(s - 1);
                    if (w4 == 1 && l16 == 0 && s > 0) mbar_expect(bar + (B_P0 + ((s - 1) & 1)) * 8, 2048);
                    mbar_wait(bar + B_XF1 * 8, s == NSEG - 1);
                }
            }
            if (WG == 0) bar_sync(11, 256);
            if (__builtin_expect(s == NSEG - 1, 0)) {
                bar_sync(6, 256);
                if (WG == 1) {
                    if (!NOFILL) {
                        store_ox(s - 1);
                        token_output(s);
                        store_ox(s);
                    }
                    bar_sync(2, 128);
                    if (w4 == 0 && l16 == 0) {
                        if (NOFILL) for (int i = 0; i < 15; i++) count_up(CNT_OX + i);
                        count_up(CNT_OX + 15);
                    }
                    __syncwarp();
                }
                mbar_wait(bar + B_SC * 8, s & 1);
                break;
            }
            if constexpr (WG == 0) {
                load_vm(vm, s);
                const uint32_t oo = u_off + ((l16 & 48) << 3) + ((l16 >> 2) & 112);
                char* dst = reinterpret_cast<char*>(&g_xo[s & 3][0]) + oo;
                mbar_wait(bar + B_SC * 8, s & 1);
                TS(4);
                float a0[4], b0[4], a1[4], b1[4], a2[4];
                ldsm4f(a0, sb + C_SL + l16); ldsm4f(b0, sb + C_SL + 1024 + l16);
                ldsm4f(a1, sb + C_SL + 512 + l16); ldsm4f(b1, sb + C_SL + 1536 + l16);
                ldsm4f(a2, sb + C_SL + 2048 + l16);
                const float e[10] = {a0[0] + b0[0], a0[1] + b0[1], a0[2] + b0[2], a0[3] + b0[3], a1[0] + b1[0], a1[1] + b1[1], a1[2] + b1[2], a1[3] + b1[3],
                                     a2[0] + a2[2], a2[1] + a2[3]};
                float m = fmaxf(fmaxf(fmaxf(e[0], e[1]), fmaxf(e[2], e[3])), fmaxf(fmaxf(e[4], e[5]), fmaxf(e[6], e[7])));
                m = fmaxf(m, fmaxf(e[8], e[9]));
                m = fmaxf(fmaxf(m, __shfl_xor_sync(~0u, m, 1)), fmaxf(__shfl_xor_sync(~0u, m, 2), __shfl_xor_sync(~0u, m, 3)));
                m *= -SM_SCALE;
                float x[10];
#pragma unroll
                for (int i = 0; i < 10; i++) x[i] = ex2(fmaf(e[i], SM_SCALE, m));
                float o[4][4];
                const uint32_t p0 = pack2(x[0], x[1]), p1 = pack2(x[2], x[3]), j0 = __float_as_uint(x[1]), j1 = __float_as_uint(x[3]);
#pragma unroll
                for (int j = 0; j < 4; j++) { o[j][0] = o[j][1] = o[j][2] = o[j][3] = 0.f; mma16(o[j], p0, j0, p1, j1, vx[j][0], vx[j][1]); }
                const uint32_t p2 = pack2(x[4], x[5]), p3 = pack2(x[6], x[7]), j2 = __float_as_uint(x[5]), j3 = __float_as_uint(x[7]);
#pragma unroll
                for (int j = 0; j < 4; j++) mma16(o[j], p2, j2, p3, j3, vx[j][2], vx[j][3]);
                const uint32_t p4 = pack2(x[8], x[9]), j4 = __float_as_uint(x[9]);
                float l = (((x[0] + x[1]) + (x[2] + x[3])) + ((x[4] + x[5]) + (x[6] + x[7]))) + (x[8] + x[9]);
                l = (l + __shfl_xor_sync(~0u, l, 1)) + (__shfl_xor_sync(~0u, l, 2) + __shfl_xor_sync(~0u, l, 3));
#pragma unroll
                for (int j = 0; j < 4; j++) mma8(o[j], p4, j4, vm[j]);
                l = rcp(l);
                st_relaxed4(reinterpret_cast<uint4*>(dst), make_uint4(pack2(o[0][0] * l, o[0][1] * l), pack2(o[1][0] * l, o[1][1] * l),
                                                                      pack2(o[2][0] * l, o[2][1] * l), pack2(o[3][0] * l, o[3][1] * l)));
                bar_arrive(3, 256);
                if (w4 == 0 && l16 == 0) mbar_expect(bar + B_SC * 8, 2560);
            }
        }
    }
}

__global__ void __cluster_dims__(6, 1, 1) __launch_bounds__(256, 1)
chain_kernel(const __grid_constant__ CUtensorMap tq, const __grid_constant__ CUtensorMap tk, const __grid_constant__ CUtensorMap tv,
             const __grid_constant__ CUtensorMap two, const __grid_constant__ Descs D, const __grid_constant__ Descs DV,
             const __nv_bfloat16* __restrict__ x, const __nv_bfloat16* __restrict__ mem0) {
    extern __shared__ __align__(1024) uint8_t smem[];
    const uint32_t sb = smem_u32(smem);
    const int rank = blockIdx.x % 6, cl = blockIdx.x / 6, role = rank >= 4 ? 2 : rank & 1;
    const int tid = threadIdx.x, lane = tid & 31, gw = blockIdx.x * 8 + uni(tid >> 5);
    const CUtensorMap *tA = role == 2 ? &tv : &tq, *tB = role == 2 ? &tv : &tk;
    uint4 cur[4], nxt[4];
#pragma unroll
    for (int j = 0; j < 4; j++) {
        cur[j] = reinterpret_cast<const uint4*>(x)[gw * 128 + j * 32 + lane];
        nxt[j] = reinterpret_cast<const uint4*>(x)[(gw + 768) * 128 + j * 32 + lane];
    }
    if (gw < 512 && lane < 16) asm volatile("prefetch.global.L2 [%0];" :: "l"(x + (gw + 1536) * DM + lane * 64));
    if ((gw & 7) == 0) {
        if (tid == 0) { TL(1, 0); TLSM(1); }
        if ((sb & 0xFFFFFF) != SB0 || mapa(sb, 5) != (SB0 | 0x5000000u)) sts1u(1, 0);
        const uint32_t b = sb + C_BAR + lane * 8;
        uint32_t tx = 0;
        if (lane <= B_WS) tx = 65536;
        if (lane == B_MF0 || lane == B_MF1) tx = 8192;
        if (lane == B_OF) tx = (role == 2 ? ONKV : ONKQ) * (256 + 2048);
        if (lane == B_SC) tx = 2560;
        if (lane == B_P0 || lane == B_P1) tx = 2048;
        if (lane == B_XS || lane == B_OL) tx = (lane == B_XS && role) ? 5120 : 3072;
        if (lane < B_NUM) mbar_init(b, lane == B_MBF ? 12 : (lane >= B_GO && lane <= B_A0 ? 4 : 1));
        if (tx) mbar_expect(b, tx);
        asm volatile("fence.mbarrier_init.release.cluster;" ::: "memory");
        fence_async();
        __syncwarp();
#pragma unroll 1
        for (int i = 0; i < 12; i++)
            if (elect()) load_box(tA, tB, cl, rank, sb + (i >> 2) * 65536, i >> 2, i & 3, sb + C_BAR + (i >> 2) * 8);
    }
    reset_exchange(mem0);
    __syncthreads();
    asm volatile("barrier.cluster.arrive.relaxed.aligned;" ::: "memory");
    const int warp = gw & 7, wg = warp >> 2, kr = (lane & 7) + ((lane >> 4) << 3);
    const uint32_t a_adr = __shfl_sync(~0u, sb + wg * 32768 + kr * 128 + ((((warp & 3) * 2 + ((lane >> 3) & 1)) ^ (kr & 7)) << 4), lane);
    uint32_t wk[24][4], wv[24][4], goal = 0;
    auto to_regs = [&](auto j) {
        mbar_wait(sb + C_BAR + (B_W0 + j.value) * 8, 0);
#pragma unroll
        for (int i = 0; i < 8; i++) {
            ldsm4t(wk[j.value * 8 + i], a_adr + j.value * 65536 + i * 2048);
            ldsm4t(wv[j.value * 8 + i], a_adr + j.value * 65536 + 16384 + i * 2048);
        }
    };
    auto first_chunk = [&]() {
        to_regs(ic<0>{});
        __syncthreads();
        if (wg == 0 && elect()) load_box(tA, tB, cl, rank, sb + C_WS, 3, warp, sb + C_BAR + B_WS * 8);
        __syncwarp();
        if (tid == 0) TL(1, 6);
    };
    if (warp == 4) calibrate(sb + C_CAL, 0.f);
    if (C0FIRST) first_chunk();
#pragma unroll 1
    for (int row = gw; row < SEQ; row += 768) {
        uint4 v[4];
#pragma unroll
        for (int j = 0; j < 4; j++) {
            v[j] = cur[j]; cur[j] = nxt[j];
            if (row + 1536 < SEQ) nxt[j] = reinterpret_cast<const uint4*>(x)[(row + 1536) * 128 + j * 32 + lane];
        }
        ln_row(v, row, lane);
    }
    if (tid == 0) TL(1, 5);
    if (C0FIRST) __syncthreads(); else first_chunk();
    if (warp == 5 && elect()) {
        __threadfence();
        goal = (atomicAdd(&g_epoch, 1u) / 96 + 1) * 96;
        asm volatile("griddepcontrol.launch_dependents;" ::: "memory");
        TL(1, 4);
    }
    __syncwarp();
    to_regs(ic<1>{});
    to_regs(ic<2>{});
    if (warp == 5) {
        goal = __reduce_max_sync(~0u, goal);
        uint32_t v, it = 0;
        do {
            asm volatile("ld.acquire.gpu.global.u32 %0, [%1];" : "=r"(v) : "l"(&g_epoch) : "memory");
            spin_guard(it);
        } while (__any_sync(~0u, (int)(v - goal) < 0));
    }
    if (warp == 4) calibrate(sb + C_CAL, 0.f);
    asm volatile("barrier.cluster.wait.aligned;" ::: "memory");
    __syncthreads();
    asm volatile("fence.proxy.async.global;" ::: "memory");
    if (role == 2) {
        if (wg == 0) chain_main<true, 0>(&two, sb, cl, rank, DV, wk, wv, a_adr);
        else chain_main<true, 1>(&two, sb, cl, rank, DV, wk, wv, a_adr);
    } else {
        if (wg == 0) chain_main<false, 0>(&two, sb, cl, rank, D, wk, wv, a_adr);
        else chain_main<false, 1>(&two, sb, cl, rank, D, wk, wv, a_adr);
    }
    __syncwarp();
    cluster_sync();
    if (threadIdx.x == 0) TL(1, 1);
}

__device__ __forceinline__ void wg256(float* d, uint32_t da, uint32_t db, uint32_t accum) {
    asm volatile("{\n.reg .b64 da, db;\n.reg .pred p;\nsetp.ne.u32 p, %130, 0;\nmov.b64 da, {%128, " DESC_HI_SW128 "};\nmov.b64 db, {%129, " DESC_HI_SW128 "};\n"
                 "wgmma.mma_async.sync.aligned.m64n256k16.f32.bf16.bf16 {"
                 "%0,%1,%2,%3,%4,%5,%6,%7,%8,%9,%10,%11,%12,%13,%14,%15,%16,%17,%18,%19,%20,%21,%22,%23,%24,%25,%26,%27,%28,%29,%30,%31,"
                 "%32,%33,%34,%35,%36,%37,%38,%39,%40,%41,%42,%43,%44,%45,%46,%47,%48,%49,%50,%51,%52,%53,%54,%55,%56,%57,%58,%59,%60,%61,%62,%63,"
                 "%64,%65,%66,%67,%68,%69,%70,%71,%72,%73,%74,%75,%76,%77,%78,%79,%80,%81,%82,%83,%84,%85,%86,%87,%88,%89,%90,%91,%92,%93,%94,%95,"
                 "%96,%97,%98,%99,%100,%101,%102,%103,%104,%105,%106,%107,%108,%109,%110,%111,%112,%113,%114,%115,%116,%117,%118,%119,%120,%121,%122,%123,%124,%125,%126,%127"
                 "}, da, db, p, 1, 1, 0, 1;\n}"
                 : ACC16(d), ACC16((d + 16)), ACC16((d + 32)), ACC16((d + 48)), ACC16((d + 64)), ACC16((d + 80)), ACC16((d + 96)), ACC16((d + 112))
                 : "r"(da), "r"(db), "r"(accum));
}
__device__ __forceinline__ void wg128(float* d, uint32_t da, uint32_t db, uint32_t accum) {
    asm volatile("{\n.reg .b64 da, db;\n.reg .pred p;\nsetp.ne.u32 p, %66, 0;\nmov.b64 da, {%64, " DESC_HI_SW128 "};\nmov.b64 db, {%65, " DESC_HI_SW128 "};\n"
                 "wgmma.mma_async.sync.aligned.m64n128k16.f32.bf16.bf16 {"
                 "%0,%1,%2,%3,%4,%5,%6,%7,%8,%9,%10,%11,%12,%13,%14,%15,%16,%17,%18,%19,%20,%21,%22,%23,%24,%25,%26,%27,%28,%29,%30,%31,"
                 "%32,%33,%34,%35,%36,%37,%38,%39,%40,%41,%42,%43,%44,%45,%46,%47,%48,%49,%50,%51,%52,%53,%54,%55,%56,%57,%58,%59,%60,%61,%62,%63"
                 "}, da, db, p, 1, 1, 0, 1;\n}"
                 : ACC16(d), ACC16((d + 16)), ACC16((d + 32)), ACC16((d + 48))
                 : "r"(da), "r"(db), "r"(accum));
}
__device__ __forceinline__ float sigmoidf_(float v) { return rcp(1.f + ex2(-1.4426950408889634f * v)); }
__device__ __forceinline__ void wait_count(int idx, uint32_t n) {
    uint32_t v, it = 0;
    while (true) {
        asm volatile("ld.acquire.gpu.global.u32 %0, [%1];" : "=r"(v) : "l"(&g_cnt[idx * 8]) : "memory");
        if (v >= n) break;
        __nanosleep(100);
        spin_guard(it);
    }
    asm volatile("fence.proxy.async.global;" ::: "memory");
}

constexpr int G_STAGES = 4, G_PAIRS = 18;
constexpr uint32_t G_STAGE = 49152, G_EPI = G_STAGES * G_STAGE, G_BAR = G_EPI + 32768, G_SMEM = G_BAR + 256;
__device__ __forceinline__ int glu_job(int p, int j) {
    if (j < 12) return j * G_PAIRS + p;
    if (p < 14) return j == 12 ? 224 + p : (j == 13 ? 242 + p : -1);
    return j < 14 ? 216 + (j - 12) * 4 + (p - 14) : (j == 14 ? 224 + p : -1);
}

__global__ void __cluster_dims__(2, 1, 1) __launch_bounds__(384, 1)
glu_kernel(const __grid_constant__ CUtensorMap tXn, const __grid_constant__ CUtensorMap tG, const __grid_constant__ CUtensorMap tU,
           const __grid_constant__ CUtensorMap tHst, const __grid_constant__ CUtensorMap tHld, const __grid_constant__ CUtensorMap tD,
           const __grid_constant__ CUtensorMap tYst) {
    extern __shared__ __align__(1024) uint8_t smem[];
    const uint32_t sb = smem_u32(smem);
    const uint32_t full = sb + G_BAR, empty = full + 64;
    const int tid = threadIdx.x, lane = tid & 31;
    const int warp = uni(tid >> 5), wg = warp >> 2;
    const int rank = blockIdx.x & 1, pair = blockIdx.x >> 1;
    asm volatile("griddepcontrol.launch_dependents;" ::: "memory");
    if (tid == 0) {
        TL(2, 0); TLSM(2);
        for (int i = 0; i < G_STAGES; i++) { mbar_init(full + i * 8, 1); mbar_init(empty + i * 8, 16); }
        asm volatile("fence.mbarrier_init.release.cluster;" ::: "memory");
        fence_async();
    }
    __syncthreads();
    cluster_sync();
    if (wg == 0) {
        asm volatile("setmaxnreg.dec.sync.aligned.u32 40;");
        if (warp == 0) {
            if (lane == 0) {
                uint32_t st = 0, ph = 1;
                asm volatile("fence.acq_rel.gpu;\nfence.proxy.async.global;" ::: "memory");
                for (int j = 0, job; (job = glu_job(pair, j)) >= 0; j++) {
                    const bool dn = job >= 224;
                    const int mp = dn ? (job - 224) >> 2 : job / 28, nt = dn ? job & 3 : job % 28, rb = mp * 2 + rank;
                    const CUtensorMap* tA = dn ? &tHld : &tXn;
                    const CUtensorMap* tB = dn ? &tD : (rank ? &tU : &tG);
                    const int bcol = dn ? nt * 256 + rank * 128 : nt * 128, nkb = dn ? FF / 64 : DM / 64;
                    if (j == 12) TL(2, 2);
                    if (dn) wait_count(CNT_H + rb, 56);
                    for (int kb = 0; kb < nkb; kb++) {
                        mbar_wait(empty + st * 8, ph);
                        const uint32_t base = sb + st * G_STAGE;
                        mbar_expect(full + st * 8, G_STAGE);
                        tma2d(base, tA, kb * 64, rb * 128, full + st * 8);
                        tma2d_mc(base + 16384 + rank * 16384, tB, bcol, kb * 64, full + st * 8, 3);
                        tma2d_mc(base + 16384 + rank * 16384 + 8192, tB, bcol + 64, kb * 64, full + st * 8, 3);
                        if (++st == G_STAGES) { st = 0; ph ^= 1; }
                    }
                }
            }
        } else if (warp < 3) {
            const int cw = warp - 1;
            const uint32_t epi = sb + G_EPI + cw * 16384;
            bar_arrive(3 + cw, 160);
            for (int j = 0, job; (job = glu_job(pair, j)) >= 0; j++) {
                const bool dn = job >= 224;
                const int mp = dn ? (job - 224) >> 2 : job / 28, nt = dn ? job & 3 : job % 28, rb = mp * 2 + rank;
                for (int hp = 0; hp <= (int)dn; hp++) {
                    bar_sync(1 + cw, 160);
                    if (lane == 0) {
                        const int col = dn ? nt * 256 + hp * 128 : nt * 128;
                        tma2d_store(dn ? &tYst : &tHst, col, rb * 128 + cw * 64, epi);
                        tma2d_store(dn ? &tYst : &tHst, col + 64, rb * 128 + cw * 64, epi + 8192);
                        asm volatile("cp.async.bulk.commit_group;\ncp.async.bulk.wait_group.read 0;" ::: "memory");
                    }
                    __syncwarp();
                    bar_arrive(3 + cw, 160);
                    if (lane == 0) {
                        asm volatile("cp.async.bulk.wait_group 0;\nfence.proxy.async.global;" ::: "memory");
                        count_up(dn ? CNT_Y + rb * 8 + nt * 2 + hp : CNT_H + rb);
                    }
                    __syncwarp();
                }
            }
        }
        cluster_sync();
    } else {
        asm volatile("setmaxnreg.inc.sync.aligned.u32 232;");
        const int cw = wg - 1, w4 = warp & 3;
        const uint32_t empty_dst = mapa(empty, lane & 1);
        const int er = w4 * 16 + (lane & 15), ec = lane >> 4;
        const uint32_t epi = sb + G_EPI + cw * 16384 + er * 128;
        uint32_t st = 0, ph = 0;
        float acc[128];
        auto put = [&](const uint32_t* o) {
            bar_sync(3 + cw, 160);
#pragma unroll
            for (int q = 0; q < 8; q++) stsm4(epi + (q >> 2) * 8192 + (((2 * (q & 3) + ec) ^ (er & 7)) << 4), o[q * 4], o[q * 4 + 1], o[q * 4 + 2], o[q * 4 + 3]);
            fence_async();
            bar_arrive(1 + cw, 160);
        };
        for (int j = 0, job; (job = glu_job(pair, j)) >= 0; j++) {
            const bool dn = job >= 224;
            const int nkb = dn ? FF / 64 : DM / 64;
            uint32_t prev = 0;
#pragma unroll 1
            for (int kb = 0; kb < nkb; kb++) {
                mbar_wait(full + st * 8, ph);
                const uint32_t base = sb + st * G_STAGE;
                const uint32_t da = (((base + cw * 8192) & 0x3FFFF) >> 4) | (1u << 16);
                const uint32_t db = (((base + 16384) & 0x3FFFF) >> 4) | (512u << 16);
                wg_fence();
#pragma unroll
                for (int k = 0; k < 4; k++) wg256(acc, da + k * 2, db + k * 128, (kb | k) != 0);
                wg_commit();
                if (kb > 0) {
                    wg_wait<1>();
                    if (lane < 2) mbar_arrive_cluster(empty_dst + prev * 8);
                }
                prev = st;
                if (++st == G_STAGES) { st = 0; ph ^= 1; }
            }
            wg_wait<0>();
            reg_fence<128>(acc);
            if (lane < 2) mbar_arrive_cluster(empty_dst + prev * 8);
            uint32_t o[32];
            if (!dn) {
#pragma unroll
                for (int i = 0; i < 32; i++) o[i] = pack2(sigmoidf_(acc[2 * i]) * acc[64 + 2 * i], sigmoidf_(acc[2 * i + 1]) * acc[65 + 2 * i]);
                put(o);
            } else {
#pragma unroll
                for (int hp = 0; hp < 2; hp++) {
#pragma unroll
                    for (int i = 0; i < 32; i++) {
                        const float a = acc[hp * 64 + 2 * i], b = acc[hp * 64 + 2 * i + 1];
                        o[i] = pack2(sigmoidf_(a) * a, sigmoidf_(b) * b);
                    }
                    put(o);
                }
            }
        }
        bar_sync(3 + cw, 160);
        if (tid == 128) TL(2, 1);
        cluster_sync();
    }
}

constexpr int O_STAGES = 7;
constexpr uint32_t O_STAGE = 32768, O_BAR = O_STAGES * O_STAGE, O_SMEM = O_BAR + 256;

__global__ void __cluster_dims__(2, 1, 1) __launch_bounds__(384, 1)
out_kernel(const __grid_constant__ CUtensorMap tOx, const __grid_constant__ CUtensorMap tWo, const __grid_constant__ CUtensorMap tX,
           const __grid_constant__ CUtensorMap tY, const __grid_constant__ CUtensorMap tOut) {
    extern __shared__ __align__(1024) uint8_t smem[];
    const uint32_t sb = smem_u32(smem);
    const uint32_t full = sb + O_BAR, empty = full + 64;
    const int tid = threadIdx.x, lane = tid & 31;
    const int warp = uni(tid >> 5), wg = warp >> 2;
    const int rank = blockIdx.x & 1, nt = (blockIdx.x >> 1) & 7, rb = (blockIdx.x >> 4) * 2 + rank;
    constexpr int NKB = HD / 64;
    if (warp == 0) {
        if (tid == 0) { TL(3, 0); TLSM(3); }
        if (lane < O_STAGES) { mbar_init(full + lane * 8, 1); mbar_init(empty + lane * 8, 16); mbar_expect(full + lane * 8, O_STAGE); }
        asm volatile("fence.mbarrier_init.release.cluster;" ::: "memory");
        fence_async();
    }
    if (tid == 32) wait_count(CNT_OX + rb, 32);
    __syncwarp();
    asm volatile("barrier.cluster.arrive.relaxed.aligned;" ::: "memory");
    __syncthreads();
    if (warp == 1) {
        if (elect()) {
            TL(3, 2);
            asm volatile("fence.proxy.async.global;" ::: "memory");
            for (int kb = 0; kb < O_STAGES; kb++) tma2d(sb + kb * O_STAGE, &tOx, kb * 64, rb * 128, full + kb * 8);
        }
        __syncwarp();
    }
    asm volatile("barrier.cluster.wait.aligned;" ::: "memory");
    if (wg == 0) {
        if (warp == 0 && elect()) {
            asm volatile("fence.proxy.async.global;" ::: "memory");
            for (int kb = 0; kb < O_STAGES; kb++)
                tma2d_mc(sb + kb * O_STAGE + 16384 + rank * 8192, &tWo, nt * 128 + rank * 64, kb * 64, full + kb * 8, 3);
            uint32_t st = 0, ph = 0;
            for (int kb = O_STAGES; kb < NKB + 2; kb++) {
                const uint32_t base = sb + st * O_STAGE;
                mbar_wait(empty + st * 8, ph);
                mbar_expect(full + st * 8, O_STAGE);
                if (kb < NKB) {
                    tma2d(base, &tOx, kb * 64, rb * 128, full + st * 8);
                    tma2d_mc(base + 16384 + rank * 8192, &tWo, nt * 128 + rank * 64, kb * 64, full + st * 8, 3);
                } else {
                    if (kb == NKB) wait_count(CNT_Y + rb * 8 + nt, 2);
                    tma2d(base, &tX, nt * 128 + (kb - NKB) * 64, rb * 128, full + st * 8);
                    tma2d(base + 16384, &tY, nt * 128 + (kb - NKB) * 64, rb * 128, full + st * 8);
                }
                if (++st == O_STAGES) { st = 0; ph ^= 1; }
            }
        }
        __syncwarp();
    } else {
        const int cw = wg - 1, w4 = warp & 3;
        const uint32_t empty_dst = mapa(empty, lane & 1);
        const int er = cw * 64 + w4 * 16 + (lane & 15), ec = lane >> 4;
        uint32_t st = 0, ph = 0, prev = 0;
        float acc[64];
#pragma unroll 1
        for (int kb = 0; kb < NKB; kb++) {
            mbar_wait(full + st * 8, ph);
            const uint32_t base = sb + st * O_STAGE;
            const uint32_t da = (((base + cw * 8192) & 0x3FFFF) >> 4) | (1u << 16);
            const uint32_t db = (((base + 16384) & 0x3FFFF) >> 4) | (512u << 16);
            wg_fence();
#pragma unroll
            for (int k = 0; k < 4; k++) wg128(acc, da + k * 2, db + k * 128, (kb | k) != 0);
            wg_commit();
            wg_wait<1>();
            if (lane < 2 && kb > 0 && kb <= NKB + 2 - O_STAGES) mbar_arrive_cluster(empty_dst + prev * 8);
            prev = st;
            if (++st == O_STAGES) { st = 0; ph ^= 1; }
        }
        wg_wait<0>();
        reg_fence<64>(acc);
#pragma unroll
        for (int bx = 0; bx < 2; bx++) {
            mbar_wait(full + st * 8, ph);
            const uint32_t base = sb + st * O_STAGE;
#pragma unroll
            for (int j = 0; j < 4; j++) {
                uint32_t xv[4], yv[4];
                const uint32_t ad = base + er * 128 + (((2 * j + ec) ^ (er & 7)) << 4);
                ldsm4(xv, ad); ldsm4(yv, ad + 16384);
                const float* a = acc + bx * 32 + j * 8;
#pragma unroll
                for (int i = 0; i < 4; i++)
                    xv[i] = pack2(fmaf(a[2 * i], bf_lo(yv[i]), bf_lo(xv[i])), fmaf(a[2 * i + 1], bf_hi(yv[i]), bf_hi(xv[i])));
                stsm4(ad, xv[0], xv[1], xv[2], xv[3]);
            }
            fence_async();
            bar_sync(1 + cw, 128);
            if ((tid & 127) == 0) {
                tma2d_store(&tOut, nt * 128 + bx * 64, rb * 128 + cw * 64, base + cw * 8192);
                asm volatile("cp.async.bulk.commit_group;" ::: "memory");
            }
            if (++st == O_STAGES) { st = 0; ph ^= 1; }
        }
        if ((tid & 127) == 0) asm volatile("cp.async.bulk.wait_group.read 0;" ::: "memory");
        if (tid == 128) TL(3, 1);
        __syncwarp();
    }
    asm volatile("barrier.cluster.arrive.relaxed.aligned;\nbarrier.cluster.wait.aligned;" ::: "memory");
}

typedef CUresult (*EncodeFn)(CUtensorMap*, CUtensorMapDataType, cuuint32_t, void*, const cuuint64_t*, const cuuint64_t*, const cuuint32_t*,
                             const cuuint32_t*, CUtensorMapInterleave, CUtensorMapSwizzle, CUtensorMapL2promotion, CUtensorMapFloatOOBfill);

CUtensorMap make_map(EncodeFn enc, const void* p, int rows, int cols, int box_rows) {
    CUtensorMap m;
    cuuint64_t dims[2] = {(cuuint64_t)cols, (cuuint64_t)rows}, strides[1] = {(cuuint64_t)cols * 2};
    cuuint32_t box[2] = {64, (cuuint32_t)box_rows}, es[2] = {1, 1};
    enc(&m, CU_TENSOR_MAP_DATA_TYPE_BFLOAT16, 2, const_cast<void*>(p), dims, strides, box, es, CU_TENSOR_MAP_INTERLEAVE_NONE,
        CU_TENSOR_MAP_SWIZZLE_128B, CU_TENSOR_MAP_L2_PROMOTION_L2_128B, CU_TENSOR_MAP_FLOAT_OOB_FILL_NONE);
    return m;
}

}

#define PDL 7
extern "C" void kernel_launch(void* const* d_in, const int* in_sizes, int n_in, void* d_out, int out_size) {
    const __nv_bfloat16* x = (const __nv_bfloat16*)d_in[0];
    const __nv_bfloat16* mem0 = (const __nv_bfloat16*)d_in[1];
    void* fn = nullptr;
    cudaDriverEntryPointQueryResult qr;
    cudaGetDriverEntryPoint("cuTensorMapEncodeTiled", &fn, cudaEnableDefault, &qr);
    EncodeFn enc = (EncodeFn)fn;
    void *xn, *ox, *h, *y;
    cudaGetSymbolAddress(&xn, g_xn); cudaGetSymbolAddress(&ox, g_ox); cudaGetSymbolAddress(&h, g_h); cudaGetSymbolAddress(&y, g_y);

    const CUtensorMap tq = make_map(enc, d_in[2], DM, HD, 128), tk = make_map(enc, d_in[3], DM, HD, 128), tv = make_map(enc, d_in[4], DM, HD, 128);
    const CUtensorMap two16 = make_map(enc, d_in[5], HD, DM, 16);
    const CUtensorMap txn128 = make_map(enc, xn, SEQ, DM, 128), tg = make_map(enc, d_in[8], DM, FF, 64), tu = make_map(enc, d_in[9], DM, FF, 64);
    const CUtensorMap th64 = make_map(enc, h, SEQ, FF, 64), th128 = make_map(enc, h, SEQ, FF, 128), td = make_map(enc, d_in[10], FF, DM, 64);
    const CUtensorMap ty64 = make_map(enc, y, SEQ, DM, 64), ty128 = make_map(enc, y, SEQ, DM, 128), tx128 = make_map(enc, x, SEQ, DM, 128);
    const CUtensorMap tox = make_map(enc, ox, SEQ, HD, 128), two64 = make_map(enc, d_in[5], HD, DM, 64), tout = make_map(enc, d_out, SEQ, DM, 64);

    cudaFuncSetAttribute(chain_kernel, cudaFuncAttributeMaxDynamicSharedMemorySize, C_SMEM);
    cudaFuncSetAttribute(glu_kernel, cudaFuncAttributeMaxDynamicSharedMemorySize, G_SMEM);
    cudaFuncSetAttribute(out_kernel, cudaFuncAttributeMaxDynamicSharedMemorySize, O_SMEM);

    Descs D;
    for (int i = 0; i < 4; i++) D.sw[i] = DSW;
    D.ns = DNS;
    cudaStream_t st = cudaStreamPerThread;
    cudaLaunchAttribute at;
    at.id = cudaLaunchAttributeProgrammaticStreamSerialization;
    at.val.programmaticStreamSerializationAllowed = 1;
    cudaLaunchConfig_t cfg = {};
    cfg.stream = st; cfg.attrs = &at; cfg.numAttrs = 0;
    cfg.gridDim = dim3(96); cfg.blockDim = dim3(256); cfg.dynamicSmemBytes = C_SMEM;
    cudaLaunchKernelEx(&cfg, chain_kernel, tq, tk, tv, two16, D, D, x, mem0);
    cfg.gridDim = dim3(2 * G_PAIRS); cfg.blockDim = dim3(384); cfg.dynamicSmemBytes = G_SMEM; cfg.numAttrs = (PDL >> 1) & 1;
    cudaLaunchKernelEx(&cfg, glu_kernel, txn128, tg, tu, th64, th128, td, ty64);
    cfg.gridDim = dim3(128); cfg.dynamicSmemBytes = O_SMEM; cfg.numAttrs = (PDL >> 2) & 1;
    cudaLaunchKernelEx(&cfg, out_kernel, tox, two64, tx128, ty128, tout);
}
```
